```python
import torch

def _softmax(x, axis=-1):
    return torch.softmax(x, dim=axis)
def _gelu(x):
    return torch.nn.functional.gelu(x, approximate="tanh")
def _silu(x):
    return torch.nn.functional.silu(x)
def _sigmoid(x):
    return torch.sigmoid(x)
def _layernorm(x, axis=-1, eps=1e-5):
    m = x.mean(dim=axis, keepdim=True)
    v = x.var(dim=axis, keepdim=True, unbiased=False)
    return (x - m) / torch.sqrt(v + eps)
def _scatter_add(tgt, idx, src, axis=0):
    return tgt.clone().index_add_(axis, idx, src)
def _segment_sum(src, seg, n):
    out = torch.zeros((n,) + src.shape[1:], dtype=src.dtype)
    return out.index_add_(0, seg, src)
def _pad(x, pw):
    flat = tuple(v for pair in reversed(pw) for v in pair)
    return torch.nn.functional.pad(x, flat)

kernel_name = 'interleave_layers__sliding_local_dilated__glu_gated_swiglu__prompt'

def setup_inputs():

    _w = (lambda a: (lambda t: t.to(torch.bfloat16) if t.is_floating_point() else t)(torch.as_tensor(a)))
    def _A_setup():
        B, S, D = 1, 2048, 1024
        return {
            "x": _w((lambda *s: torch.randn(*s, dtype=torch.bfloat16) * 0.05)(B, S, D)),
            "wqkv": _w((lambda *s: torch.randn(*s, dtype=torch.bfloat16) * 0.05)(D, 3 * D)),
            "wo": _w((lambda *s: torch.randn(*s, dtype=torch.bfloat16) * 0.05)(D, D)),
        }
    _A_in = _A_setup()

    def _B_setup():
        B, S, D, F = 1, 2048, 1024, 3584
        return {
            "x": _w((lambda *s: torch.randn(*s, dtype=torch.bfloat16) * 0.05)(B, S, D)),
            "w1": _w((lambda *s: torch.randn(*s, dtype=torch.bfloat16) * 0.8)(D, F) * (2.0 / D) ** 0.5),
            "w3": _w((lambda *s: torch.randn(*s, dtype=torch.bfloat16) * 0.8)(D, F) * (2.0 / D) ** 0.5),
            "w2": _w((lambda *s: torch.randn(*s, dtype=torch.bfloat16) * 0.8)(F, D) * (2.0 / F) ** 0.5),
        }
    _B_in = _B_setup()

    return {
        "A_x": _A_in["x"],
        "A_wqkv": _A_in["wqkv"],
        "A_wo": _A_in["wo"],
        "B_x": _B_in["x"],
        "B_w1": _B_in["w1"],
        "B_w3": _B_in["w3"],
        "B_w2": _B_in["w2"],
    }

def reference(A_x, A_wqkv, A_wo, B_x, B_w1, B_w3, B_w2):
    def _A_ref(x, wqkv, wo):
        B, S, D = x.shape
        H = 32; Dh = D // H
        W, dil = 8, 2
        qkv = (lambda x, *d: x.permute(*d))((x @ wqkv).reshape(B, S, 3, H, Dh), 2, 0, 3, 1, 4)
        q, k, v = qkv[0], qkv[1], qkv[2]
        scale = Dh ** -0.5
        pos = torch.arange(S)
        off = torch.arange(W) * dil
        idx = pos[:, None] - off[None, :]
        mask = idx >= 0
        idx_c = torch.where(mask, idx, 0).reshape(-1)
        kg = k[:, :, idx_c, :].reshape(B, H, S, W, Dh)
        vg = v[:, :, idx_c, :].reshape(B, H, S, W, Dh)
        logits = torch.einsum("bhsd,bhswd->bhsw", q, kg) * scale
        logits = torch.where(mask[None, None, :, :], logits, -1e9)
        attn = _softmax(logits, axis=-1)
        o = torch.einsum("bhsw,bhswd->bhsd", attn, vg)
        return (lambda x, *d: x.permute(*d))(o, 0, 2, 1, 3).reshape(B, S, D) @ wo

    def _B_ref(x, w1, w3, w2):
        gate = torch.einsum("bsd,df->bsf", x, w1)
        up = torch.einsum("bsd,df->bsf", x, w3)
        h = _silu(gate) * up
        out = torch.einsum("bsf,fd->bsd", h, w2)
        return out

    x = A_x
    x = x + _A_ref(_layernorm(x, axis=-1), A_wqkv, A_wo)
    x = x + _B_ref(_layernorm(x, axis=-1), B_w1, B_w3, B_w2)
    x = x + _A_ref(_layernorm(x, axis=-1), A_wqkv, A_wo)
    x = x + _B_ref(_layernorm(x, axis=-1), B_w1, B_w3, B_w2)
    return x
```

```cpp
#include <cuda_runtime.h>
#include <cuda_bf16.h>
#include <cuda.h>
#include <stdint.h>
#include <stddef.h>

typedef __nv_bfloat16 bf16;
#define GU_E 3
#define G_N1 6
#define G_R1 16
#define Q_P1 5
#define Q_P2 7
#define Q_P0 0
#define O_P1 2
#define ST_DELTA 280
#define ST_T0 600
#define ST_ROWS 6000
#define ST_RAW 0
#define PROWS 16
#define GAP_O 250
#define GAP_Y 50
#define GAP_H 450
#define GAP_H6 1000
#define DEP32 0x1fc
#define HOLD 3
#define ST_NX 1
#define ST_NW 2
#define GLA 3
#define LATE_O 1
#define RELQ 3
#define RELG 1
#define RELD 3
#define WARM_T 4000
#define GATE_T 0
#define RLA 1
#define PXF 1
#define LATE_GO 1
#define HALO_D 0
#define TANH 0
#define QSH 0
#define TAILQ 1
#define TAIL 2
#define D_GATE 5
#define WARM_X 1

namespace {

constexpr int S_ = 2048, D_ = 1024, F_ = 3584;
constexpr int NCTA = 128;
constexpr int NHELP = 4;

constexpr uint32_t SB = 1024;
constexpr int NU = 25;
constexpr uint32_t SM_STG  = SB + NU * 8192;
constexpr uint32_t SM_STAT = SM_STG + 16384;
constexpr uint32_t SM_CS   = SM_STAT + 4096;
constexpr uint32_t BARS    = SM_CS + 5120;
constexpr int SM_TOTAL = BARS + 896 - SB;
static_assert(BARS % 128 == 0 && SM_TOTAL <= 232448, "smem");
constexpr int B_FULL = 0, B_EMPTY = 16, B_SIG = 32, B_XCH = 36, B_STAT = 37, B_TURN = 41, B_CS = 43, B_FREE = 52, B_SF = 53, B_QT = 55, B_GATE = 56, B_PASS = 57,
              B_DEP = 58, B_PUB = 74, B_N = 90;
__host__ __device__ constexpr uint32_t bar(int i) { return BARS + 8 * i; }
constexpr uint32_t SM_TAG = BARS + 8 * B_N, SM_ZERO = BARS + 768;
constexpr int NB_WG = 1, NB_PX = 3, NB_PY = 4, NB_OGO = 5, NB_INIT = 6;

constexpr int E_O0 = 0, E_O1 = 1, E_YA = 2, E_YB = 3, E_H4 = 4, E_XA = 7, E_XB = 8, E_N = 9;

constexpr int M_X0 = 0, M_O = 1, M_Y = 2, M_H = 3;
constexpr int M_WQKV = 4, M_WO = 5, M_W1 = 6, M_W3 = 7, M_W2 = 8;
constexpr int M_OL = 9, M_YL = 10, M_HL = 11, M_N = 12;

constexpr int FIRST = 5;
constexpr int NOPA = 416, NOPB = 480, NSEG = 64;
constexpr uint32_t A_END = 1, A_TURN = 2, A_DRAIN = 4, A_WAIT = 8, A_SYNC = 16,
                   A_MARK = 0;
struct Task { uint32_t seg, stg, res, sig; };
struct Seg { uint32_t i8, end8, a, b; };
constexpr uint32_t LO_A = 0x10000 + SB / 16, LO_B = 0x2000000 + SB / 16;
struct Sched { Task task[22]; uint32_t gate[2], pad[6]; Seg seg[NSEG]; };
struct Ops { uint2 a[NOPA + 32], b[NOPB + 32]; };
struct Gen {
  Sched s{}; Ops o{};
  int n[2] = {0, 0}, nseg = 0, cur = -1, pos = 0, err = 0, solo = -1;
  int mask[400] = {}, sa[400] = {}, sb[400][2] = {}, own[NU][2] = {}, tok[NU] = {}, known[2][2] = {{-1, -1}, {-1, -1}};
  constexpr void emit(int p, int wait, int par, int dst, int map, int kb8, int arr, int load, int y) {
    if (cur < FIRST) return;
    const uint2 e{(uint32_t)(wait | (par & 1) << 7 | dst << 8 | map << 13 | (cur & 15) << 17 | kb8 << 21 | arr << 24 | load << 25 |
                              (!p && arr && mask[cur] != 3 && solo != cur) << 26), (uint32_t)y};
    if (!p && arr) solo = cur;
    if (p) o.b[n[1]++] = e; else o.a[n[0]++] = e;
  }
  constexpr bool done(int p, int x) const { return x < 0 || ((!(mask[x] & 1) || known[p][0] >= x) && (!(mask[x] & 2) || known[p][1] >= x)); }
  constexpr void op(int p, int dst, int nu, int map, int kb8, int arr, int y, int xw = -1, int xp = 0) {
    int w[8] = {}, wp[8] = {}, nw = 0;
    if (xw >= 0) { w[nw] = xw; wp[nw++] = xp; }
    for (int u = dst; u < dst + nu; u++) if (tok[u] && (u == dst || tok[u] != tok[u - 1])) { w[nw] = (tok[u] - 1) >> 1; wp[nw++] = tok[u] - 1; }
    for (int x = cur - 1; x >= 0; x--) {
      bool need = x <= cur - 12;
      for (int u = dst; u < dst + nu; u++) need = need || own[u][0] == x + 1 || own[u][1] == x + 1;
      if (!need || done(p, x)) continue;
      if (cur - x >= 16 || !done(p, x - 16)) err |= 1;
      w[nw] = B_EMPTY + ((x + 2) & 15); wp[nw++] = x >> 4;
      for (int g = 0; g < 2; g++) if (((mask[x] >> g) & 1) && known[p][g] < x) known[p][g] = x;
    }
    for (; nw > 1; nw--) emit(p, w[nw - 1], wp[nw - 1], 0, 0, 0, 0, 0, 0);
    emit(p, nw ? w[0] : B_PASS, nw ? wp[0] : 1, dst, map, kb8, arr, nu > 0, y);
    for (int u = dst; u < dst + nu; u++) { own[u][0] = cur + 1; own[u][1] = 0; tok[u] = 0; }
  }
  constexpr int step(int m) { mask[++cur] = m; return cur; }
  constexpr int slot() { int u = (pos + 1) & ~1; if (u >= 24) u = 0; pos = u + 2; return u; }
  constexpr int qslot() { int u = (pos + 4) / 5 * 5; if (u >= NU) u = 0; pos = u + 5; return u; }
  constexpr void stage(int u, int first, int t) {
    for (int x = u; x < u + 2; x++) { if (own[x][0] > first - TAIL - 1 || own[x][1] > first - TAIL - 1 || tok[x]) err |= 2; own[x][0] = cur + 1; own[x][1] = 0; tok[x] = t; }
  }
  static constexpr int kown(int hi) { return hi * 8 | 1 << 9; }
  static constexpr int kskip(int hi, int j) { return (hi * 8 + j) | (j + 1) << 6; }
  static constexpr int kpos(int p) { return p < 2 ? kown(p) : p < 9 ? kskip(0, p - 2) : kskip(1, p - 9); }
  constexpr void segs(int t, const int* st, const uint32_t* act, int cnt, int tail, int inc0) {
    const int g = t & 1, wrap = inc0 == 5 ? NU : 24;
    s.task[t].seg = nseg;
    int j0 = 0;
    for (int j = 0; j < cnt; j++) {
      const int x = st[j], inc = inc0 ? inc0 : mask[st[j0]] == 3 ? 6 : 4;
      const bool next = j + 1 < cnt && st[j + 1] == x + 1 && mask[x + 1] == mask[x] && sa[x + 1] == (sa[x] + inc) % wrap && sb[x + 1][g] == (sb[x][g] + inc) % wrap;
      if (j >= cnt - tail - 1 && j + 1 < cnt && !next) err |= 4;
      if (j + 1 < cnt && st[j + 1] != x + 1 && !(act[j] & A_DRAIN)) err |= 8;
      if (j >= cnt - tail || (next && !act[j] && j != cnt - tail - 1)) continue;
      if (j == j0 && (j == 0 || (inc0 != 4 && (act[j - 1] & (A_DRAIN | A_SYNC))))) err |= 16;
      const int y = st[j0];
      s.seg[nseg++] = Seg{(uint32_t)y * 8 | (act[j] | (j == cnt - tail - 1 ? A_END : 0)) << 16, (uint32_t)(x + 1) * 8 | inc * 512 << 16, LO_A + sa[y] * 512, LO_B + sb[y][g] * 512};
      j0 = j + 1;
    }
  }
  constexpr void residual(int t, int map) {
    step(1 << (t & 1));
    const int u0 = slot(), u1 = slot();
    op(0, u0, 2, map, 2, 1, kown(0)); op(0, u1, 2, map, 2, 1, kown(1));
    s.task[t].res = cur | u0 << 16 | u1 << 24;
  }
  constexpr Gen() {
    int cs[4] = {};
    for (int t = 0; t < 22; t++) {
      const int i = t % 11, use = i < 2 ? 2 : (i == 2 || i == 10) ? 14 : 3;
      for (int x = 0; x < 4; x++) if ((use >> x) & 1) s.task[t].sig |= (cs[x]++ & 1) << x;
    }
    for (int l = 0; l < 2; l++) {
      const int T = l * 11, dep = B_DEP + l * E_N;
      int st[7][56] = {};
      uint32_t act[7][56] = {};
      if (l == 1) {
        const int first = cur + 1;
        for (int j = 0; j < 4; j++) {
          const int x = st[j >> 1][j & 1] = step(1 << ((T + (j >> 1)) & 1)), u = qslot();
          sb[x][0] = sb[x][1] = u + 2;
          if (j < 2) { sa[x] = u; stage(u, first, j ? 1 + B_SF * 2 + 1 : 0); s.task[10].stg |= u << (8 * j); op(0, 0, 0, 0, 0, 1, 1 << 13, B_SIG + 1 + j, s.task[10].sig >> (1 + j)); }
          else { sa[x] = sa[x - 2]; own[sa[x]][1] = own[sa[x] + 1][1] = x + 1; op(0, 0, 0, 0, 0, 1, 0); }
          op(1, u + 2, 3, M_WQKV, 3, 1, kown(j & 1) | (j >> 1) << 10);
        }
        act[0][1] = A_DRAIN; act[1][1] = A_DRAIN | A_WAIT;
      }
      for (int i = 0; i < 2; i++) {
        for (int j = 2 * l; j < 16; j++) {
          const int x = st[i][j] = step(1 << ((T + i) & 1)), u = qslot(), k = l ? kpos(j) : j;
          sa[x] = u; sb[x][0] = sb[x][1] = u + 2;
          op(0, u, 2, l ? M_Y : M_X0, 2, 1, k, l && i == 0 && (j == 2 || j == 9) ? B_DEP + (j == 2 ? E_XA : E_XB) : -1);
          op(1, u + 2, 3, M_WQKV, 3, 1, k | i << 10, (HOLD & 2) && l && i == 0 && j == 2 ? (HOLD & 4 ? B_DEP : B_PUB) + E_XA : -1);
        }
        if (i) act[1][Q_P1 - 1 + (l ? 2 : Q_P0)] = act[1][Q_P2 - 1 + (l ? 2 : Q_P0)] = A_SYNC;
        segs(T + i, st[i], act[i], 16, TAILQ, 5);
      }
      residual(T + 2, l ? M_Y : M_X0);
      for (int j = 0; j < 16; j++) {
        const int x = st[0][j] = step(1 << (T & 1)), k = j < 8 ? j : j == 8 ? kown(1) : kskip(1, j - 9);
        act[0][j] = j == O_P1 - 1 ? A_SYNC : 0;
        if (j == 8) { sa[x] = NU; op(0, 0, 0, 0, 0, 1, 1 << 13, B_SIG + 1, s.task[T + 1].sig >> 1); }
        else { sa[x] = slot(); op(0, sa[x], 2, M_O, 2, 1, k, j == 0 ? dep + E_O0 : j == 9 ? dep + E_O1 : -1); }
        sb[x][0] = sb[x][1] = slot();
        op(1, sb[x][0], 2, M_WO, 2, 1, k);
      }
      segs(T + 2, st[0], act[0], 16, TAIL, 4);
      int beg[8] = {0, G_R1}, end[7] = {16, G_R1 + 16 - G_N1}, cnt[7] = {};
      for (int j = 2; j < 7; j++) { beg[j] = end[j - 2] + GU_E; end[j] = beg[j] + 16; }
      beg[7] = end[6];
      const int first = cur + 1;
      for (int j = 0; j < end[6]; j++) {
        int tl[2] = {-1, -1}, m = 0;
        for (int v = 0; v < 7; v++) if ((j >= beg[v] && j < end[v]) || (v == 1 && j < G_N1)) { const int g = (T + 3 + v) & 1; if (tl[g] >= 0) err |= 32; tl[g] = v; m |= 1 << g; }
        if (!m) err |= 32;
        const int x = step(m), k = kpos(j < 16 ? j : (j + G_N1) & 15);
        sa[x] = slot();
        if (j < 2) { stage(sa[x], first, j ? 1 + B_SF * 2 : 0); s.task[T + 2].stg |= sa[x] << (8 * j); op(0, 0, 0, 0, 0, 1, 1 << 13, B_SIG + 1 + j, s.task[T + 2].sig >> (1 + j)); }
        else op(0, sa[x], 2, M_Y, 2, 1, k, j == 2 ? dep + E_YA : j == 9 ? dep + E_YB : -1);
        for (int g = 0; g < 2; g++) {
          const int v = tl[g];
          if (v < 0) continue;
          sb[x][g] = slot();
          op(1, sb[x][g], 2, M_W1, m == 3 ? 4 : 2, g == 0 || m != 3, k | v << 10 | 1 << 13, (HOLD & 1) && j == 2 && g == 1 ? (HOLD & 4 ? B_DEP : B_PUB) + l * E_N + E_YA : -1);
          act[v][cnt[v]] = j == beg[v + 1] - 1 ? A_TURN : v == 1 && j == G_N1 - 1 ? A_DRAIN | A_WAIT : v == 0 && j == 1 ? A_MARK : 0;
          st[v][cnt[v]++] = x;
        }
      }
      for (int v = 0; v < 7; v++) { if (cnt[v] != 16) err |= 64; segs(T + 3 + v, st[v], act[v], 16, 0, 0); }
      s.gate[l] = bar(B_EMPTY + ((cur - D_GATE + 2) & 15)) | (uint32_t)((cur - D_GATE) >> 4) << 31;
      residual(T + 10, M_Y);
      for (int j = 0; j < 56; j++) {
        const int x = st[0][j] = step(1 << (T & 1));
        act[0][j] = 0;
        sa[x] = slot(); op(0, sa[x], 2, M_H, 2, 1, j, j == 0 ? dep + E_H4 : j == 40 ? dep + E_H4 + 1 : j == 48 ? dep + E_H4 + 2 : -1);
        sb[x][0] = sb[x][1] = slot(); op(1, sb[x][0], 2, M_W2, 2, 1, j);
      }
      segs(T + 10, st[0], act[0], 56, TAIL, 4);
    }
    { const int u0 = slot(), u1 = slot(); stage(u0, cur + 1, 0); stage(u1, cur + 1, 0); s.task[21].stg = u0 | u1 << 8; }
    if (n[0] > NOPA || n[1] > NOPB || nseg > NSEG) err |= 128;
    for (int x = n[0]; x < NOPA + 32; x++) o.a[x] = uint2{B_PASS | 1 << 7, 0};
    for (int x = n[1]; x < NOPB + 32; x++) o.b[x] = uint2{B_PASS | 1 << 7, 0};
  }
};
constexpr Gen GEN{};
static_assert(GEN.err == 0, "schedule");
constexpr int NOP0 = (GEN.n[0] + 31) / 32 * 32, NOP1 = (GEN.n[1] + 31) / 32 * 32;

struct __align__(64) Params {
  CUtensorMap tm[M_N];
  const bf16 *x0, *wqkv;
  bf16* out;
};

}

__constant__ Sched c_sched = GEN.s;
__device__ const Ops g_ops = GEN.o;
__device__ __align__(1024) bf16 g_o[S_ * D_];
__device__ __align__(1024) bf16 g_y[S_ * D_];
__device__ __align__(1024) bf16 g_h[S_ * F_];
__device__ __align__(128) float2 g_stat[3][16][8][128];
__device__ __align__(128) uint4 g_stat0[16][128];
__device__ __align__(128) uint4 g_halo[4][16][8][6][32];
__device__ __align__(128) uint4 g_cs[9][8][64];
__device__ __align__(128) uint4 g_gate[NCTA][8];
__device__ __align__(128) uint32_t g_flags[NCTA][32];
__device__ uint32_t g_epoch[NCTA + NHELP];

#define TL(t, i) do {} while (0)
#define TL1(t, i) do {} while (0)
#define TS(i8, wg) do {} while (0)
#define TLW(t, i) do {} while (0)
#define MB_LIMIT (1 << 20)
#define FL_LIMIT (1 << 21)

namespace {

__device__ __forceinline__ uint32_t smem_u32(const void* p) { return (uint32_t)__cvta_generic_to_shared(p); }
__device__ __forceinline__ void mbar_init(uint32_t br, uint32_t cnt) { asm volatile("mbarrier.init.shared::cta.b64 [%0], %1;" ::"r"(br), "r"(cnt)); }
__device__ __forceinline__ void mbar_expect_tx(uint32_t br, uint32_t bytes) { asm volatile("mbarrier.arrive.expect_tx.shared::cta.b64 _, [%0], %1;" ::"r"(br), "r"(bytes) : "memory"); }
__device__ __forceinline__ void mbar_arrive(uint32_t br) { asm volatile("mbarrier.arrive.shared::cta.b64 _, [%0];" ::"r"(br) : "memory"); }
__device__ __forceinline__ void mbar_arrive_if(uint32_t br, uint32_t p) {
  asm volatile("{\n.reg .pred q;\nsetp.ne.u32 q, %1, 0;\n@q mbarrier.arrive.shared::cta.b64 _, [%0];\n}\n" ::"r"(br), "r"(p) : "memory");
}
__device__ __forceinline__ void mbar_arrive_cnt(uint32_t br, uint32_t cnt) {
  asm volatile("{\n.reg .pred q;\nsetp.ne.u32 q, %1, 0;\n@q mbarrier.arrive.shared::cta.b64 _, [%0], %1;\n}\n" ::"r"(br), "r"(cnt) : "memory");
}
__device__ __forceinline__ void mbar_arrive_warp(uint32_t br) {
  asm volatile("{\n.reg .pred q;\nbar.warp.sync 0xffffffff;\nelect.sync _|q, 0xffffffff;\n@q mbarrier.arrive.shared::cta.b64 _, [%0];\n}\n" ::"r"(br) : "memory");
}
__device__ __forceinline__ bool mbar_try_wait(uint32_t br, uint32_t parity) {
  uint32_t ok;
  asm volatile("{\n.reg .pred p;\nmbarrier.try_wait.parity.shared::cta.b64 p, [%1], %2;\nselp.u32 %0, 1, 0, p;\n}\n" : "=r"(ok) : "r"(br), "r"(parity) : "memory");
  return ok;
}
__device__ __forceinline__ bool mbar_test_wait(uint32_t br, uint32_t parity) {
  uint32_t ok;
  asm volatile("{\n.reg .pred p;\nmbarrier.test_wait.parity.shared::cta.b64 p, [%1], %2;\nselp.u32 %0, 1, 0, p;\n}\n" : "=r"(ok) : "r"(br), "r"(parity) : "memory");
  return ok;
}
__device__ __forceinline__ void mbar_wait(uint32_t br, uint32_t parity) {
#pragma unroll 1
  for (int it = 0; it < MB_LIMIT; ++it) { if (mbar_try_wait(br, parity)) return; }
  __trap();
}
__device__ __forceinline__ bool elect_one() { uint32_t p; asm volatile("{\n.reg .pred P;\nelect.sync _|P, 0xffffffff;\nselp.u32 %0, 1, 0, P;\n}\n" : "=r"(p)); return p; }
__device__ __forceinline__ void fence_proxy_async_smem() { asm volatile("fence.proxy.async.shared::cta;" ::: "memory"); }
__device__ __forceinline__ void tma3d(uint32_t dst, const CUtensorMap* m, int c0, int c1, int c2, uint32_t br) {
  asm volatile("cp.async.bulk.tensor.3d.shared::cluster.global.mbarrier::complete_tx::bytes [%0], [%1, {%3, %4, %5}], [%2];" ::"r"(dst), "l"(m), "r"(br), "r"(c0), "r"(c1), "r"(c2) : "memory");
}
__device__ __forceinline__ void tma3d_prefetch(const CUtensorMap* m, int c0, int c1, int c2) {
  asm volatile("cp.async.bulk.prefetch.tensor.3d.L2.global.tile [%0, {%1, %2, %3}];" ::"l"(m), "r"(c0), "r"(c1), "r"(c2) : "memory");
}
__device__ __forceinline__ void tma3d_store(const CUtensorMap* m, uint32_t src, int c0, int c1, int c2) {
  asm volatile("cp.async.bulk.tensor.3d.global.shared::cta.bulk_group [%0, {%2, %3, %4}], [%1];" ::"l"(m), "r"(src), "r"(c0), "r"(c1), "r"(c2) : "memory");
}
__device__ __forceinline__ void stsm4(uint32_t a, uint32_t x, uint32_t y, uint32_t z, uint32_t w) {
  asm volatile("stmatrix.sync.aligned.m8n8.x4.shared.b16 [%0], {%1,%2,%3,%4};" ::"r"(a), "r"(x), "r"(y), "r"(z), "r"(w) : "memory");
}
__device__ __forceinline__ void ldsm4(uint32_t a, uint32_t& x, uint32_t& y, uint32_t& z, uint32_t& w) {
  asm volatile("ldmatrix.sync.aligned.m8n8.x4.shared.b16 {%0,%1,%2,%3}, [%4];" : "=r"(x), "=r"(y), "=r"(z), "=r"(w) : "r"(a) : "memory");
}
__device__ __forceinline__ void st_tag(uint4* p, uint32_t a, uint32_t b, uint32_t c, uint32_t tag) {
  asm volatile("{\n.reg .b64 x, y;\n.reg .b128 z;\nmov.b64 x, {%1, %2};\nmov.b64 y, {%3, %4};\nmov.b128 z, {x, y};\nst.relaxed.gpu.global.b128 [%0], z;\n}\n" ::"l"(p), "r"(a), "r"(b), "r"(c), "r"(tag) : "memory");
}
__device__ __forceinline__ uint4 ld_tag(const uint4* p) {
  uint4 v;
  asm volatile("{\n.reg .b64 x, y;\n.reg .b128 z;\nld.relaxed.gpu.global.b128 z, [%4];\nmov.b128 {x, y}, z;\nmov.b64 {%0, %1}, x;\nmov.b64 {%2, %3}, y;\n}\n" : "=r"(v.x), "=r"(v.y), "=r"(v.z), "=r"(v.w) : "l"(p) : "memory");
  return v;
}
template <int NAP, int N> __device__ __forceinline__ void ld_tag_wait(uint4 (&v)[N], const uint4* p, uint32_t tag) {
#pragma unroll 1
  for (int it = 0; it < FL_LIMIT; ++it) {
    uint32_t bad = 0;
#pragma unroll
    for (int j = 0; j < N; j++) v[j] = ld_tag(p + j * 32);
#pragma unroll
    for (int j = 0; j < N; j++) bad |= v[j].w ^ tag;
    if (__all_sync(0xffffffffu, bad == 0)) return;
    if (NAP) __nanosleep(NAP);
  }
  __trap();
}
__device__ __forceinline__ void prefetch_tmap(const CUtensorMap* m) { asm volatile("prefetch.tensormap [%0];" ::"l"(m) : "memory"); }
__device__ __forceinline__ void wgmma_fence() { asm volatile("wgmma.fence.sync.aligned;" ::: "memory"); }
__device__ __forceinline__ void wgmma_commit() { asm volatile("wgmma.commit_group.sync.aligned;" ::: "memory"); }
template <int N> __device__ __forceinline__ void wgmma_wait() { asm volatile("wgmma.wait_group.sync.aligned %0;" ::"n"(N) : "memory"); }
template <int R> __device__ __forceinline__ void reg_alloc() { asm volatile("setmaxnreg.inc.sync.aligned.u32 %0;" ::"n"(R)); }
template <int R> __device__ __forceinline__ void reg_dealloc() { asm volatile("setmaxnreg.dec.sync.aligned.u32 %0;" ::"n"(R)); }
__device__ __forceinline__ void bar_sync(int id, int n) { asm volatile("bar.sync %0, %1;" ::"r"(id), "r"(n) : "memory"); }
__device__ __forceinline__ void bar_arrive(int id, int n) { asm volatile("bar.arrive %0, %1;" ::"r"(id), "r"(n) : "memory"); }
__device__ __forceinline__ uint32_t ld_acquire(const uint32_t* p) { uint32_t v; asm volatile("ld.acquire.gpu.global.u32 %0, [%1];" : "=r"(v) : "l"(p) : "memory"); return v; }
__device__ __forceinline__ void st_release(uint32_t* p, uint32_t v) { asm volatile("st.release.gpu.global.u32 [%0], %1;" ::"l"(p), "r"(v) : "memory"); }
__device__ __forceinline__ uint4 ldcg16(const void* p) { uint4 v; asm volatile("ld.global.cg.v4.u32 {%0,%1,%2,%3}, [%4];" : "=r"(v.x), "=r"(v.y), "=r"(v.z), "=r"(v.w) : "l"(p) : "memory"); return v; }
__device__ __forceinline__ float ldcgf(const void* p) { float v; asm volatile("ld.global.cg.f32 %0, [%1];" : "=f"(v) : "l"(p) : "memory"); return v; }
__device__ __forceinline__ float2 lds8f(uint32_t a) { float2 v; asm volatile("ld.shared.v2.f32 {%0,%1}, [%2];" : "=f"(v.x), "=f"(v.y) : "r"(a)); return v; }
__device__ __forceinline__ float lds4f(uint32_t a) { float v; asm volatile("ld.shared.f32 %0, [%1];" : "=f"(v) : "r"(a)); return v; }
__device__ __forceinline__ uint32_t lds4(uint32_t a) { uint32_t v; asm volatile("ld.shared.u32 %0, [%1];" : "=r"(v) : "r"(a) : "memory"); return v; }
__device__ __forceinline__ void lds16f(uint32_t a, float& x, float& y, float& z, float& w) { asm volatile("ld.shared.v4.f32 {%0,%1,%2,%3}, [%4];" : "=f"(x), "=f"(y), "=f"(z), "=f"(w) : "r"(a) : "memory"); }
__device__ __forceinline__ void sts8f(uint32_t a, float x, float y) { asm volatile("st.shared.v2.f32 [%0], {%1,%2};" ::"r"(a), "f"(x), "f"(y) : "memory"); }
__device__ __forceinline__ void sts4f(uint32_t a, float x) { asm volatile("st.shared.f32 [%0], %1;" ::"r"(a), "f"(x) : "memory"); }
__device__ __forceinline__ void sts16(uint32_t a, uint32_t x, uint32_t y, uint32_t z, uint32_t w) { asm volatile("st.shared.v4.u32 [%0], {%1,%2,%3,%4};" ::"r"(a), "r"(x), "r"(y), "r"(z), "r"(w) : "memory"); }
__device__ __forceinline__ void lds16(uint32_t a, uint32_t& x, uint32_t& y, uint32_t& z, uint32_t& w) { asm volatile("ld.shared.v4.u32 {%0,%1,%2,%3}, [%4];" : "=r"(x), "=r"(y), "=r"(z), "=r"(w) : "r"(a) : "memory"); }
__device__ __forceinline__ uint32_t pack_bf16(float a, float b) { uint32_t r; asm("cvt.rn.bf16x2.f32 %0, %1, %2;" : "=r"(r) : "f"(b), "f"(a)); return r; }
__device__ __forceinline__ uint32_t pack_bf16_v(float a, float b) { uint32_t r; asm volatile("cvt.rn.bf16x2.f32 %0, %1, %2;" : "=r"(r) : "f"(b), "f"(a)); return r; }
__device__ __forceinline__ float bf_lo(uint32_t v) { return __uint_as_float(v << 16); }
__device__ __forceinline__ float bf_hi(uint32_t v) { return __uint_as_float(v & 0xffff0000u); }
constexpr float LOG2E = 1.4426950408889634f;
__device__ __forceinline__ float ex2f(float x) { float y; asm("ex2.approx.ftz.f32 %0, %1;" : "=f"(y) : "f"(x)); return y; }
__device__ __forceinline__ float tanhf_(float x) { float y; asm("tanh.approx.f32 %0, %1;" : "=f"(y) : "f"(x)); return y; }
__device__ __forceinline__ float rcpf(float x) { float y; asm("rcp.approx.ftz.f32 %0, %1;" : "=f"(y) : "f"(x)); return y; }
__device__ __forceinline__ float bf_round(float a) { return bf_lo(pack_bf16(a, 0.f)); }
__device__ __forceinline__ uint32_t movmat(uint32_t a) { uint32_t d; asm volatile("movmatrix.sync.aligned.m8n8.trans.b16 %0, %1;" : "=r"(d) : "r"(a)); return d; }
__device__ __forceinline__ void mma16816(float& d0, float& d1, float& d2, float& d3, uint32_t a0, uint32_t a1, uint32_t a2, uint32_t a3, uint32_t b0, uint32_t b1,
                                         float c0, float c1, float c2, float c3) {
  asm volatile("mma.sync.aligned.m16n8k16.row.col.f32.bf16.bf16.f32 {%0,%1,%2,%3}, {%4,%5,%6,%7}, {%8,%9}, {%10,%11,%12,%13};"
               : "=f"(d0), "=f"(d1), "=f"(d2), "=f"(d3) : "r"(a0), "r"(a1), "r"(a2), "r"(a3), "r"(b0), "r"(b1), "f"(c0), "f"(c1), "f"(c2), "f"(c3));
}
template <int N> __device__ __forceinline__ void copy_out(uint32_t a, char* g, int pitch, int lane) {
  a += (lane >> 3) * 128 + (((lane ^ (lane >> 3)) & 7) << 4);
  g += (lane >> 3) * pitch + (lane & 7) * 16;
  uint32_t v[N][4];
  __syncwarp();
#pragma unroll
  for (int j = 0; j < N; j++) lds16((a ^ ((j & 1) * 64)) + j * 512, v[j][0], v[j][1], v[j][2], v[j][3]);
#pragma unroll
  for (int j = 0; j < N; j++) asm volatile("st.global.v4.u32 [%0], {%1, %2, %3, %4};" ::"l"(g + j * 4 * pitch), "r"(v[j][0]), "r"(v[j][1]), "r"(v[j][2]), "r"(v[j][3]) : "memory");
}
__device__ __forceinline__ int lane_now() { int v; asm volatile("mov.u32 %0, %%laneid;" : "=r"(v)); return v; }
__device__ __forceinline__ uint32_t uni(uint32_t x, int lane) { return __shfl_sync(0xffffffffu, x + lane, 0); }
__device__ __forceinline__ uint64_t dsc(uint32_t hi, uint32_t lo) { return ((uint64_t)hi << 32) | lo; }

#define R8(a, o) "+f"(a[o]), "+f"(a[o + 1]), "+f"(a[o + 2]), "+f"(a[o + 3]), "+f"(a[o + 4]), "+f"(a[o + 5]), "+f"(a[o + 6]), "+f"(a[o + 7])
#define R32(a, o) R8(a, o), R8(a, o + 8), R8(a, o + 16), R8(a, o + 24)
#define REG64 "%0, %1, %2, %3, %4, %5, %6, %7, %8, %9, %10, %11, %12, %13, %14, %15, %16, %17, %18, %19, %20, %21, %22, %23, %24, %25, %26, %27, %28, %29, %30, %31, " \
              "%32, %33, %34, %35, %36, %37, %38, %39, %40, %41, %42, %43, %44, %45, %46, %47, %48, %49, %50, %51, %52, %53, %54, %55, %56, %57, %58, %59, %60, %61, %62, %63"
#define REG96 REG64 ", %64, %65, %66, %67, %68, %69, %70, %71, %72, %73, %74, %75, %76, %77, %78, %79, %80, %81, %82, %83, %84, %85, %86, %87, %88, %89, %90, %91, %92, %93, %94, %95"
__device__ __forceinline__ void wgmma(float (&d)[64], uint64_t da, uint64_t db) {
  asm volatile("wgmma.mma_async.sync.aligned.m64n128k16.f32.bf16.bf16 {" REG64 "}, %64, %65, 1, 1, 1, 0, 1;\n"
               : R32(d, 0), R32(d, 32) : "l"(da), "l"(db));
}
__device__ __forceinline__ void wgmma(float (&d)[96], uint64_t da, uint64_t db) {
  asm volatile("wgmma.mma_async.sync.aligned.m64n192k16.f32.bf16.bf16 {" REG96 "}, %96, %97, 1, 1, 1, 0, 1;\n"
               : R32(d, 0), R32(d, 32), R32(d, 64) : "l"(da), "l"(db));
}
#define W8(a, o) "=f"(a[o]), "=f"(a[o + 1]), "=f"(a[o + 2]), "=f"(a[o + 3]), "=f"(a[o + 4]), "=f"(a[o + 5]), "=f"(a[o + 6]), "=f"(a[o + 7])
#define W32(a, o) W8(a, o), W8(a, o + 8), W8(a, o + 16), W8(a, o + 24)
__device__ __forceinline__ void wgmma_z(float (&d)[64], uint64_t da, uint64_t db) {
  asm volatile("wgmma.mma_async.sync.aligned.m64n128k16.f32.bf16.bf16 {" REG64 "}, %64, %65, 0, 1, 1, 0, 1;\n"
               : W32(d, 0), W32(d, 32) : "l"(da), "l"(db));
}
__device__ __forceinline__ void wgmma_z(float (&d)[96], uint64_t da, uint64_t db) {
  asm volatile("wgmma.mma_async.sync.aligned.m64n192k16.f32.bf16.bf16 {" REG96 "}, %96, %97, 0, 1, 1, 0, 1;\n"
               : W32(d, 0), W32(d, 32), W32(d, 64) : "l"(da), "l"(db));
}

__device__ __forceinline__ void wgmma_cs(float (&d)[4], uint64_t da, uint64_t db) {
  asm volatile("wgmma.mma_async.sync.aligned.m64n8k16.f32.bf16.bf16 {%0, %1, %2, %3}, %4, %5, 1, 1, 1, 1, 0;\n" : "+f"(d[0]), "+f"(d[1]), "+f"(d[2]), "+f"(d[3]) : "l"(da), "l"(db));
}
__device__ __forceinline__ void bulk_commit() { asm volatile("cp.async.bulk.commit_group;" ::: "memory"); }
__device__ __forceinline__ void bulk_wait() { asm volatile("cp.async.bulk.wait_group 0;" ::: "memory"); }
__device__ __forceinline__ void fence_bar_init() { asm volatile("fence.mbarrier_init.release.cluster;" ::: "memory"); }
__device__ __forceinline__ void prefetch_l2(const void* p) { asm volatile("prefetch.global.L2 [%0];" ::"l"(p) : "memory"); }

__device__ __forceinline__ uint32_t clock_now() { uint32_t v; asm volatile("mov.u32 %0, %%clock;" : "=r"(v)); return v; }
__device__ __forceinline__ void delay_until(uint32_t t0, int cycles) {
#pragma unroll 1
  for (int it = 0; it < 1000 && (int)(clock_now() - t0) < cycles; it++) __nanosleep(40);
}
__device__ __forceinline__ void spin_until(uint32_t t0, int cycles) {
#pragma unroll 1
  for (int it = 0; it < 10000 && (int)(clock_now() - t0) < cycles; it++) {}
}
__device__ __forceinline__ uint32_t ld_epoch(int b) { uint32_t v; asm volatile("ld.global.u32 %0, [%1];" : "=r"(v) : "l"(g_epoch + b) : "memory"); return v + 1; }
__device__ __forceinline__ void wait_flags(const uint32_t* f, uint32_t tag, uint32_t nap) {
#pragma unroll 1
  for (int it = 0; it < FL_LIMIT; ++it) { if (__all_sync(0xffffffffu, (int)(ld_acquire(f) - tag) >= 0)) return; if (nap) __nanosleep(nap); }
  __trap();
}

__device__ __forceinline__ float2 ln_finish(float mean, float var) {
  const float mb = bf_round(mean);
  const float vb = bf_round(var);
  const float sd = bf_round(sqrtf(bf_round(vb + 1e-5f)));
  return make_float2(1.0f / sd, -mb);
}

__device__ __forceinline__ void helper_cta(const Params& P, int e, int wg, int w) {
  const int tid = threadIdx.x;
  if (tid == 0) {
#pragma unroll
    for (int i = 0; i < 16; i++) mbar_init(bar(i), 1);
    fence_bar_init();
  }
  if (tid < 64) sts16(SM_STAT + tid * 16, 0x3f803f80u, 0x3f803f80u, 0x3f803f80u, 0x3f803f80u);
  fence_proxy_async_smem();
  __syncthreads();
  if (wg == 2) {
    if (w == 0) {
#pragma unroll 1
      for (int n = 0; n < 9 * 32; n++) {
        const int job = n >> 5, col = (job < 2 ? job : job - 2) * 512 + (e * 2 + (n & 1)) * 64, row = (n & 30) * 32;
        const uint32_t fb = bar(n & 7), dst = SB + (n & 7) * 24576;
        mbar_wait(bar(8 + (n & 7)), (n >> 3) + 1);
        if (elect_one()) {
          mbar_expect_tx(fb, job < 2 ? 24576 : 16384);
          tma3d(dst, &P.tm[job < 2 ? M_WQKV : M_W1], col, row, 0, fb);
          if (job >= 2) tma3d(dst + 8192, &P.tm[M_W3], col, row, 0, fb);
        }
        __syncwarp();
      }
    }
  } else {
    const uint32_t tag = ld_epoch(NCTA + e);
    const int lane = tid & 31;
#pragma unroll 1
    for (int job = 0; job < 9; job++) {
      float s[3][4] = {};
#pragma unroll 1
      for (int n = job * 32 + wg; n < job * 32 + 32; n += 2) {
        mbar_wait(bar(n & 7), n >> 3);
        wgmma_fence();
        const uint32_t a = ((SB + (n & 7) * 24576) >> 4) + 0x2000000;
#pragma unroll
        for (int k = 0; k < 8; k++) wgmma_cs(s[k & 1], dsc(0x40000040u, a + (k & 1) * 512 + (k >> 1) * 128), dsc(0x40000040u, (SM_STAT >> 4) + 0x10000));
        if (job < 2) {
          wgmma_fence();
#pragma unroll
          for (int k = 0; k < 4; k++) wgmma_cs(s[2], dsc(0x40000040u, a + 1024 + k * 128), dsc(0x40000040u, (SM_STAT >> 4) + 0x10000));
        }
        wgmma_commit();
        wgmma_wait<0>();
        mbar_arrive_if(bar(8 + (n & 7)), (tid & 127) == 0);
      }
      if (!(lane & 2))
        st_tag(&g_cs[job][e * 2 + wg][w * 16 + (lane & 1) * 8 + (lane >> 2)], __float_as_uint(lane & 1 ? s[0][2] : s[0][0]), __float_as_uint(lane & 1 ? s[1][2] : s[1][0]),
               __float_as_uint(lane & 1 ? s[2][2] : s[2][0]), tag);
      __syncwarp();
    }
    bar_sync(NB_INIT, 256);
    if (tid == 0) g_epoch[NCTA + e] = tag;
  }
}

template <bool WEIGHTS>
__device__ __forceinline__ void producer(const Params& P, const uint2* tab, int nop, int lane, int c, int row, int par) {
  uint64_t pol;
  asm volatile("createpolicy.fractional.L2::evict_first.b64 %0, 1.0;" : "=l"(pol));
  if (elect_one()) {
#pragma unroll
    for (int j = 0; j < FIRST; j++) {
      mbar_expect_tx(bar(B_FULL + j), WEIGHTS ? 24576 : 16384);
      if (WEIGHTS) tma3d(SB + j * 40960 + 16384, &P.tm[M_WQKV], c * 64, j * 64, 0, bar(B_FULL + j));
      else tma3d(SB + j * 40960, &P.tm[M_X0], j * 64, row, par, bar(B_FULL + j));
    }
  }
  __syncwarp();
  if (!WEIGHTS) TLW(0, 1);
  uint2 nx = __ldg(tab + lane);
  __syncthreads();
  if (!WEIGHTS && lane == 0) {
#pragma unroll
    for (int j = 0; j < FIRST; j++) mbar_arrive(bar(B_EMPTY + 2 + j));
  }
  __syncwarp();
#pragma unroll 1
  for (int base = 0; base < nop; base += 32) {
    const uint2 e = nx;
    nx = __ldg(tab + base + 32 + lane);
    const uint32_t wb = BARS + (e.x & 127) * 8, wp = e.x >> 7, fb = BARS + ((e.x >> 14) & 0x78), bytes = (e.x >> 8) & 0xe000, arr = e.x & (1 << 24);
    const uint32_t dst = e.x & (1 << 25) ? SB + ((e.x << 5) & 0x3e000) : 0, map = ((e.x >> 6) & 0x780) | (e.y >> 13);
    const uint32_t eb = e.x & (1 << 26) ? bar(B_EMPTY) + (((e.x >> 14) + 16) & 0x78) : 0;
    const int kc = ((e.y & 63) + ((int)((e.y >> 6) & 7) > c) + (e.y & (1 << 9) ? c : 0)) * 64, col = ((e.y >> 1) & 0xe00) + c * 64;
#pragma unroll 1
    for (int j = 0; j < 32; j++) {
      const uint32_t ud = __shfl_sync(0xffffffffu, dst, j), uf = __shfl_sync(0xffffffffu, fb, j), um = __shfl_sync(0xffffffffu, map, j);
      const int uk = __shfl_sync(0xffffffffu, kc, j), uc = WEIGHTS ? __shfl_sync(0xffffffffu, col, j) : 0;
      const CUtensorMap* mp = reinterpret_cast<const CUtensorMap*>(reinterpret_cast<const char*>(P.tm) + (um & 0x780));
#define OP_HEAD "{\n.reg .pred pe, pm, pa, pl, pg, pw;\n.reg .u32 it;\n" \
                "elect.sync _|pe, 0xffffffff;\nsetp.eq.u32 pm, %0, %1;\nsetp.ne.and.u32 pa, %2, 0, pm;\nsetp.ne.and.u32 pl, %7, 0, pe;\n"
#define OP_WAIT "mov.u32 it, 0;\n" \
                "WAIT_%=:\n" \
                "mov.pred pw, 0;\n@pm mbarrier.try_wait.parity.shared::cta.b64 pw, [%3], %4;\nvote.sync.any.pred pw, pw, 0xffffffff;\n" \
                "@pw bra.uni GO_%=;\n" \
                "add.u32 it, it, 1;\nsetp.lt.u32 pw, it, 0x100000;\n" \
                "@pw bra.uni WAIT_%=;\n" \
                "trap;\n" \
                "GO_%=:\n"
      if (WEIGHTS)
        asm volatile(OP_HEAD "setp.ne.and.u32 pg, %15, 0, pe;\n" OP_WAIT
                     "@pa mbarrier.arrive.expect_tx.shared::cta.b64 _, [%5], %6;\n"
                     "@pl cp.async.bulk.tensor.3d.shared::cluster.global.mbarrier::complete_tx::bytes.L2::cache_hint [%7], [%8, {%9, %10, %11}], [%12], %16;\n"
                     "@pg cp.async.bulk.tensor.3d.shared::cluster.global.mbarrier::complete_tx::bytes.L2::cache_hint [%13], [%14, {%9, %10, %11}], [%12], %16;\n"
                     "}\n" ::"r"(lane), "r"(j), "r"(arr), "r"(wb), "r"(wp), "r"(fb), "r"(bytes), "r"(ud), "l"(mp), "r"(uc), "r"(uk), "r"(0), "r"(uf),
                     "r"(ud + 8192), "l"(mp + 1), "r"(um & 1), "l"(pol) : "memory");
      else
        asm volatile(OP_HEAD ".reg .pred ps;\nsetp.ne.u32 pg, %14, 0;\nsetp.ne.and.u32 ps, %13, 0, pm;\n" OP_WAIT
                     "@pg fence.proxy.async.shared::cta;\n"
                     "@pa mbarrier.arrive.expect_tx.shared::cta.b64 _, [%5], %6;\n"
                     "@pl cp.async.bulk.tensor.3d.shared::cluster.global.mbarrier::complete_tx::bytes [%7], [%8, {%9, %10, %11}], [%12];\n"
                     "@ps mbarrier.arrive.shared::cta.b64 _, [%13];\n"
                     "}\n" ::"r"(lane), "r"(j), "r"(arr), "r"(wb), "r"(wp), "r"(fb), "r"(bytes), "r"(ud), "l"(mp), "r"(uk), "r"(row), "r"(par), "r"(uf), "r"(eb), "r"(um & 1) : "memory");
    }
  }
}

template <int N, uint32_t LO> __device__ __forceinline__ void advance(uint32_t& x, uint32_t inc) {
  constexpr uint32_t LEN = (N == 192 ? NU : 24) * 512;
  x += inc; if (x >= LO + LEN) x -= LEN;
}
__device__ __forceinline__ bool full_test(uint32_t i8) {
  uint32_t ok;
  asm volatile("{\n.reg .pred p;\nmbarrier.test_wait.parity.shared::cta.b64 p, [%1 + %3], %2;\nselp.u32 %0, 1, 0, p;\n}\n" : "=r"(ok) : "r"(i8 & 0x78), "r"(i8 >> 7), "n"(bar(B_FULL)) : "memory");
  return ok;
}
__device__ __forceinline__ void full_wait(uint32_t i8) { mbar_wait(bar(B_FULL) + (i8 & 0x78), i8 >> 7); }
__device__ __forceinline__ void release(uint32_t i8, uint32_t p) {
  asm volatile("{\n.reg .pred q;\nsetp.ne.u32 q, %1, 0;\n@q mbarrier.arrive.shared::cta.b64 _, [%0 + %2];\n}\n" ::"r"(i8 & 0x78), "r"(p), "n"(bar(B_EMPTY)) : "memory");
}
template <int N, int RELK, int FIRSTK>
__device__ __forceinline__ bool kstep(float (&acc)[2][N / 2], uint32_t hiA, uint32_t hiB, uint32_t& a, uint32_t& b, uint32_t inc, uint32_t& i8, uint32_t x) {
  constexpr uint32_t MI = N == 192 ? 64 : 512;
  wgmma_fence();
  if (FIRSTK == 2) { wgmma_z(acc[0], dsc(hiA, a), dsc(hiB, b)); wgmma_z(acc[1], dsc(hiA, a + MI), dsc(hiB, b)); }
  else { wgmma(acc[0], dsc(hiA, a), dsc(hiB, b)); wgmma(acc[1], dsc(hiA, a + MI), dsc(hiB, b)); }
  i8 += 8;
  const bool ok = full_test(i8);
#pragma unroll
  for (int k = 1; k < 4; k++) {
    wgmma(acc[0], dsc(hiA, a + 2 * k), dsc(hiB, b + 128 * k)); wgmma(acc[1], dsc(hiA, a + MI + 2 * k), dsc(hiB, b + 128 * k));
    if (k == RELK || k == 3) wgmma_commit();
    if (k == 3) { advance<N, LO_A>(a, inc); advance<N, LO_B>(b, inc); }
    if (!FIRSTK && k == RELK) {
      wgmma_wait<1>();
      release(i8, x);
    }
  }
  return ok;
}
template <int MODE, int N, class F>
__device__ __forceinline__ void mainloop(float (&acc)[2][N], uint32_t sig, int t, int wg, F&& first_half) {
  uint32_t sp = c_sched.task[t].seg;
  const uint32_t turn = bar(B_TURN) + 8 * (wg ^ 1);
  const uint32_t hiA = uni(MODE == 0 ? 0x40000080u : 0x40000040u, lane_now()), hiB = uni(0x40000040u, lane_now() * 2);
  uint32_t i8 = c_sched.seg[sp].i8 & 0xffff, nxt = c_sched.seg[sp].end8 & 0xffff, a = c_sched.seg[sp].a, b = c_sched.seg[sp].b;
  uint32_t inc = MODE == 0 ? 2560 : MODE == 2 ? 2048 : c_sched.seg[sp].end8 >> 16;
  full_wait(i8);
  TL(t, 2);
  TS(i8, wg);
  bool ok = kstep<N * 2, 3, MODE == 2 ? 1 : 2>(acc, hiA, hiB, a, b, inc, i8, 0);
#pragma unroll 1
  while (true) {
    uint32_t act;
#pragma unroll 1
    while (true) {
      if (!ok) full_wait(i8);
      TS(i8, wg);
      ok = kstep<N * 2, MODE == 0 ? RELQ : MODE == 1 ? RELG : RELD, 0>(acc, hiA, hiB, a, b, inc, i8, sig);
      if (__builtin_expect(i8 == nxt, 0)) {
        act = c_sched.seg[sp++].i8 >> 16;
        if (MODE == 1) mbar_arrive_if(turn, sig & (act >> 1));
        if (MODE == 0 || (act & (MODE == 1 ? A_END | A_DRAIN : A_END))) break;
        if (MODE == 2 && (act & A_SYNC)) bar_sync(NB_OGO, 256);
        nxt = c_sched.seg[sp].end8 & 0xffff; a = c_sched.seg[sp].a; b = c_sched.seg[sp].b;
        if (MODE == 1) inc = c_sched.seg[sp].end8 >> 16;
      }
    }
    if (MODE == 2 || (act & A_END)) break;
    nxt = c_sched.seg[sp].end8 & 0xffff; a = c_sched.seg[sp].a; b = c_sched.seg[sp].b;
    if (MODE == 1) inc = c_sched.seg[sp].end8 >> 16;
    wgmma_wait<0>();
    if (MODE == 0 && (act & A_SYNC)) bar_arrive(NB_PX, 256);
    release(i8 + 8, sig);
    i8 = c_sched.seg[sp].i8 & 0xffff;
    if (MODE == 1 || (act & A_WAIT)) mbar_wait(bar(B_TURN) + 8 * wg, (t - 1) >> 1);
    full_wait(i8);
    if (MODE == 0 && (act & A_SYNC)) bar_sync(NB_PY, 256);
    TS(i8, wg);
    ok = kstep<N * 2, 3, 1>(acc, hiA, hiB, a, b, inc, i8, 0);
  }
  if (MODE != 1) {
    constexpr int TL_ = MODE == 0 ? TAILQ : TAIL;
    uint32_t ta[TL_], tb[TL_];
#pragma unroll
    for (int x = 0; x < TL_; x++) {
      full_wait(i8 + 8 * x);
      TS(i8 + 8 * x, wg);
      ta[x] = a; tb[x] = b;
      advance<N * 2, LO_A>(a, inc); advance<N * 2, LO_B>(b, inc);
    }
    mbar_arrive_if(turn, MODE == 2 || !LATE_O || t == 0 || t == 11 ? sig : 0);
#pragma unroll
    for (int h = 0; h < 2; h++) {
      const int mi = MODE == 0 ? 1 - h : h;
      wgmma_fence();
#pragma unroll
      for (int x = 0; x < TL_; x++)
#pragma unroll
        for (int k = 0; k < 4; k++) wgmma(acc[mi], dsc(hiA, ta[x] + mi * (MODE == 0 ? 64 : 512) + 2 * k), dsc(hiB, tb[x] + 128 * k));
      wgmma_commit();
      if (TL_ > 1 && h == 0) { wgmma_wait<1>(); release(i8 + 8, sig); }
    }
    if (TL_ == 1) { wgmma_wait<2>(); release(i8 + 8, sig); }
    wgmma_wait<1>();
    first_half();
    wgmma_wait<0>();
#pragma unroll
    for (int x = 0; x < TL_; x++) release(i8 + 16 + 8 * x, sig);
  } else {
    first_half();
    wgmma_wait<0>();
    release(i8 + 8, sig);
  }
}

__global__ void __launch_bounds__(384, 1) fused_kernel(const __grid_constant__ Params P) {
  extern __shared__ __align__(1024) uint8_t smem_raw[];
  const int tid = threadIdx.x;
  const int wg = __shfl_sync(0xffffffffu, tid >> 7, 0);
  const int w = __shfl_sync(0xffffffffu, (tid >> 5) & 3, 0);
  const int lane = tid & 31;
  const int b = blockIdx.x;
  const uint32_t t_entry = clock_now();
  const int mg = (b >> 5) & 3;
  const int c = ((b >> 2) & 7) ^ ((mg & 1) * 7);
  const int m = mg * 4 + (b & 3);
  const int row0 = (m & 7) * 128, par = m >> 3;
  if (__builtin_expect(b >= NCTA, 0)) { helper_cta(P, b - NCTA, wg, w); return; }

  if (__builtin_expect(wg == 2, 0)) {
    reg_dealloc<40>();
    if (w < 2) {
      if (tid == 256) {
#pragma unroll
        for (int x = 0; x < FIRST; x++) mbar_init(bar(B_FULL + x), 2);
        fence_bar_init();
        fence_proxy_async_smem();
      }
      bar_sync(NB_INIT, 64);
      if (w == 0) producer<false>(P, g_ops.a, NOP0, lane, c, row0, par);
      else producer<true>(P, g_ops.b, NOP1, lane, c, row0, par);
    } else if (w == 2) {
      if (smem_u32(smem_raw) != SB) __trap();
      if (lane == 0) {
#pragma unroll
        for (int x = FIRST; x < B_CS; x++) mbar_init(bar(x), x < B_SIG ? 2 : x <= B_STAT ? 4 : 1);
        fence_bar_init();
        fence_proxy_async_smem();
      }
      __syncthreads();
      const uint32_t tag = ld_epoch(b);
#pragma unroll 1
      for (int k = FIRST; k < 16; k++)
        if (k >> 1 == c || k == m) {
          delay_until(t_entry, (k - FIRST) * ST_DELTA + ST_T0);
          if (elect_one()) {
            if (k >> 1 == c) tma3d_prefetch(&P.tm[M_X0], k * 64, row0, par);
            if (k == m) tma3d_prefetch(&P.tm[M_WQKV], c * 64, k * 64, 0);
          }
          __syncwarp();
        }
      uint32_t* const flag = g_flags[m * 8 + c];
      if (lane < 4) asm volatile("st.relaxed.gpu.global.v4.u32 [%0], {%1, %1, %1, %1};" ::"l"(flag + lane * 4), "r"(tag * 32 - 1) : "memory");
      __syncwarp();
      int ev = 0;
      uint32_t t_st = t_entry;
#pragma unroll 1
      for (int t = 0; t < 21; t++) {
        const int i = t >= 11 ? t - 11 : t;
        const bool od = i == 2 || i == 10;
        const uint32_t sig = c_sched.task[t].sig;
        const uint32_t pf = i == 0 ? 1 << M_OL | 1 << M_O | 1 << M_WO : i == 1 ? 1 << M_W1 | 1 << M_W3 | 1 << M_YL | 1 << M_Y : i == 3 ? 1 << M_HL :
                            i == 7 ? 1 << M_H | 1 << M_W2 : i == 10 ? 1 << M_WQKV | 1 << M_YL | 1 << M_Y : 0;
        if ((pf >> lane) & 1) prefetch_tmap(&P.tm[lane]);
        __syncwarp();
#pragma unroll 1
        for (int x = i == 1 || od ? 0 : 1; x < (i == 1 ? 1 : 2); x++) {
          if (x == 0) mbar_wait(bar(B_SIG + 1), sig >> 1);
          else {
            const CUtensorMap* mp = &P.tm[i == 0 ? M_OL : od ? M_YL : M_HL];
            const uint32_t src = od ? SB + ((c_sched.task[t].stg >> 8) & 31) * 8192 : SM_STG;
            const int col = ((od ? 1 : i ? i - 3 : 0) * 8 + c) * 64, gap = i == 0 ? GAP_O : od ? GAP_Y : i == 9 ? GAP_H6 : GAP_H;
#pragma unroll 1
            for (int r = 0; r < 128; r += PROWS) {
              if (r == 0 || (r == 64 && i && !od)) {
                const int s = od ? 3 : i ? r >> 6 : 1;
                mbar_wait(bar(B_SIG) + 8 * s, sig >> s);
                fence_proxy_async_smem();
              }
              delay_until(t_st, gap);
              t_st = clock_now();
              if (elect_one()) tma3d_store(mp, src + r * 128, col, row0 + r, par);
              __syncwarp();
            }
          }
          if (elect_one()) {
            if (x) { bulk_commit(); bulk_wait(); }
            if (x || !od) mbar_arrive(od ? bar(B_SF) : bar(B_FREE));
            if (i < 3 || i > 6) {
              if (PXF) asm volatile("fence.proxy.async.global;" ::: "memory");
              st_release(flag, tag * 32 + ev); mbar_arrive(bar(B_PUB) + 8 * ev);
            }
          }
          __syncwarp();
          if (i < 3 || i > 6) ev++;
          if (x == 0 || !od) TLW(t, 4);
        }
      }
      if (lane == 0) g_epoch[b] = tag;
    } else {
      if (lane == 0) {
#pragma unroll
        for (int x = B_CS; x < B_N; x++) mbar_init(bar(x), 1);
        fence_bar_init();
      }
      __syncthreads();
      const uint32_t tag = ld_epoch(b);
      delay_until(t_entry, WARM_T);
      asm volatile("st.shared.u32 [%0], %1;" ::"r"(SM_TAG + 4), "r"(reinterpret_cast<const uint32_t*>(&c_sched)[min(lane * 16, (int)sizeof(Sched) / 4 - 1)]) : "memory");
      if (GATE_T && lane < 2) st_tag(&g_gate[b][lane], t_entry, 0, 0, tag);
      int ncs = 0;
#pragma unroll 1
      for (int it = 0; it < 20; it++) {
        const int l = it >= 11, i = it - l * 11, e = i < 2 ? 0 : i - 2, ev = l * E_N + e;
#pragma unroll 1
        for (; ncs < (it < 2 ? it + 1 : it < 6 ? 2 : 9); ncs++) {
          uint4 v[2];
          ld_tag_wait<200>(v, &g_cs[ncs][c][lane], tag);
          const uint32_t a = SM_CS + (ncs < 2 ? ncs * 768 : 512 + ncs * 512) + lane * 4;
#pragma unroll
          for (int j = 0; j < 2; j++) {
            sts4f(a + j * 128, __uint_as_float(v[j].x)); sts4f(a + j * 128 + 256, __uint_as_float(v[j].y));
            if (ncs < 2) sts4f(a + j * 128 + 512, __uint_as_float(v[j].z));
          }
          mbar_arrive_warp(bar(B_CS) + 8 * ncs);
        }
        if (i == 0 || i == 2) {
          const int u = l * 2 + (i >> 1);
          uint4 v[6] = {};
          mbar_wait(bar(B_QT), u);
          if (HALO_D) delay_until(clock_now(), HALO_D);
          if (m & 7) ld_tag_wait<0>(v, &g_halo[u][m - 1][c][0][lane], tag);
          const uint32_t xa = SM_STG + lane * 16;
          sts16(xa, v[0].x, v[0].y, v[0].z, v[1].x); sts16(xa + 512, v[1].y, v[1].z, v[2].x, v[2].y);
          sts16(xa + 1024, v[2].z, v[3].x, v[3].y, v[3].z); sts16(xa + 1536, v[4].x, v[4].y, v[4].z, v[5].x);
          sts16(xa + 2048, v[5].y, v[5].z, 0, 0);
          mbar_arrive_warp(bar(B_XCH));
          continue;
        }
        if (e == E_H4 + 1) {
          const uint32_t g = c_sched.gate[l];
          if (GATE_T) {
            const uint4* const pp = &g_gate[min(max(b - 16 + lane, 0), NCTA - 1)][0];
            const uint4 v0 = ld_tag(pp);
            const bool near = v0.w == tag && abs((int)(v0.x - t_entry)) < 100000;
            mbar_wait(g & 0x3ffff, g >> 31);
            const uint32_t now = clock_now();
            if (lane == 0) st_tag(&g_gate[b][0], t_entry, now, l + 1, tag);
            __syncwarp();
            uint4 v;
#pragma unroll 1
            for (int x = 0; x < FL_LIMIT; ++x) { v = ld_tag(pp); if (__all_sync(0xffffffffu, !near || v.z > (uint32_t)l)) break; }
            spin_until(now, min(__reduce_max_sync(0xffffffffu, near && v.z == l + 1 ? (int)(v.y - now) : 0), 8000) + GATE_T);
          } else {
            mbar_wait(g & 0x3ffff, g >> 31);
            if (lane == 0) asm volatile("st.relaxed.gpu.global.u32 [%0], %1;" ::"l"(&g_flags[m * 8 + c][8]), "r"(tag * 32 + l) : "memory");
            __syncwarp();
            wait_flags(&g_flags[mg * 32 + lane][8], tag * 32 + l, 0);
          }
          mbar_arrive_warp(bar(B_GATE));
        }
        mbar_wait(bar(B_PUB) + 8 * ev, 0);
        wait_flags(g_flags[(DEP32 >> e) & 1 ? mg * 32 + lane : m * 8 + (lane & 7)], tag * 32 + ev, 0);
        mbar_arrive_warp(bar(B_DEP) + 8 * ev);
        if (e == E_YB || e == E_XB) {
          const int p = e == E_XB ? 1 : l * 2;
#pragma unroll 1
          for (int h = 0; h < 2; h++) {
            float s0 = 0.f, q0 = 0.f, s1 = 0.f, q1 = 0.f;
#pragma unroll 1
            for (int j0 = 0; j0 < 8; j0 += 4) {
              uint4 v[4];
#pragma unroll
              for (int j = 0; j < 4; j++) v[j] = ldcg16(&g_stat[p][m][j0 + j][h * 64 + lane * 2]);
#pragma unroll
              for (int j = 0; j < 4; j++) { s0 += __uint_as_float(v[j].x); q0 += __uint_as_float(v[j].y); s1 += __uint_as_float(v[j].z); q1 += __uint_as_float(v[j].w); }
            }
            s0 *= 1.f / 1024.f; s1 *= 1.f / 1024.f;
            const float2 r0 = ln_finish(s0, fmaxf(fmaf(-s0, s0, q0 * (1.f / 1024.f)), 0.f)), r1 = ln_finish(s1, fmaxf(fmaf(-s1, s1, q1 * (1.f / 1024.f)), 0.f));
            sts16(SM_STAT + (p + 1) * 1024 + (h * 64 + lane * 2) * 8, __float_as_uint(r0.x), __float_as_uint(r0.y), __float_as_uint(r1.x), __float_as_uint(r1.y));
          }
          mbar_arrive_warp(bar(B_STAT) + 8 * (p + 1));
        }
      }
    }
  } else {
    const int tw = tid & 127;
    if (wg == 0 && w < 2) asm volatile("st.shared.u32 [%0], %1;" ::"r"(SM_TAG + 4), "r"(reinterpret_cast<const uint32_t*>(&c_sched)[w ? offsetof(Sched, seg) / 4 : 0]) : "memory");
    if (ST_RAW == 2) {
      uint32_t x;
      if (wg == 0) { if (tw < 16 * ST_NX) asm volatile("ld.global.L2::256B.u32 %0, [%1];" : "=r"(x) : "l"(P.x0 + (size_t)((row0 + c * 16 + (tw & 15)) * 2 + par) * D_ + (tw >> 4) * 128)); }
      else if (tw < 8 * ST_NW && (tw & 3) < 3) asm volatile("ld.global.L2::256B.u32 %0, [%1];" : "=r"(x) : "l"(P.wqkv + (size_t)((tw >> 3) * 64 + m * 4 + (c & 1) * 2 + ((tw >> 2) & 1)) * (3 * D_) + (tw & 3) * D_ + (c >> 1) * 128));
    } else if (ST_RAW) {
      if (wg == 0) { if (tw < 16 * FIRST) prefetch_l2(P.x0 + (size_t)((row0 + c * 16 + (tw & 15)) * 2 + par) * D_ + (tw >> 4) * 64); }
      else if (tw < 16 * FIRST && (tw & 3) < 3) prefetch_l2(P.wqkv + (size_t)((tw >> 4) * 64 + m * 4 + ((tw >> 2) & 3)) * (3 * D_) + (tw & 3) * D_ + c * 64);
    }
    reg_alloc<232>();
    uint32_t sig;
    asm volatile("mov.u32 %0, %1;" : "=r"(sig) : "r"((uint32_t)(tw == 0)));
    __syncthreads();

    if (wg == 1) {
      const uint32_t tag = ld_epoch(b);
      uint4* const mine = &g_stat0[m][c * 16 + w * 4 + (lane >> 3)];
      if (WARM_X && (lane & 7) == 0) st_tag(mine, 0, 0, 0, 0);
      __syncwarp();
      delay_until(t_entry, ST_ROWS);
      uint4 xv[16];
      const bf16* xr = P.x0 + (size_t)((row0 + c * 16 + w * 4 + (lane >> 3)) * 2 + par) * D_ + (lane & 7) * 8;
#pragma unroll
      for (int j = 0; j < 16; j++) xv[j] = ldcg16(xr + j * 64);
      float s[4] = {0.f, 0.f, 0.f, 0.f};
#pragma unroll
      for (int j = 0; j < 16; j++) { s[0] += bf_lo(xv[j].x) + bf_hi(xv[j].x); s[1] += bf_lo(xv[j].y) + bf_hi(xv[j].y); s[2] += bf_lo(xv[j].z) + bf_hi(xv[j].z); s[3] += bf_lo(xv[j].w) + bf_hi(xv[j].w); }
      float mean = (s[0] + s[1]) + (s[2] + s[3]);
#pragma unroll
      for (int o = 4; o > 0; o >>= 1) mean += __shfl_xor_sync(0xffffffffu, mean, o);
      mean *= 1.f / 1024.f;
      s[0] = s[1] = s[2] = s[3] = 0.f;
#pragma unroll
      for (int j = 0; j < 16; j++) {
        const uint32_t x[4] = {xv[j].x, xv[j].y, xv[j].z, xv[j].w};
#pragma unroll
        for (int e = 0; e < 4; e++) { const float d0 = bf_lo(x[e]) - mean, d1 = bf_hi(x[e]) - mean; s[e] = fmaf(d0, d0, s[e]); s[e] = fmaf(d1, d1, s[e]); }
      }
      float m2 = (s[0] + s[1]) + (s[2] + s[3]);
#pragma unroll
      for (int o = 4; o > 0; o >>= 1) m2 += __shfl_xor_sync(0xffffffffu, m2, o);
      const float2 fin = ln_finish(mean, m2 * (1.f / 1024.f));
      if ((lane & 7) == 0) st_tag(mine, __float_as_uint(fin.x), __float_as_uint(fin.y), 0, tag);
      __syncwarp();
      TL(22, 5);
      uint4 v[1];
      ld_tag_wait<200>(v, &g_stat0[m][tw], tag);
      sts8f(SM_STAT + tw * 8, __uint_as_float(v[0].x), __uint_as_float(v[0].y));
      if (tw == 0) { asm volatile("st.shared.u32 [%0], %1;" ::"r"(SM_TAG), "r"(tag) : "memory"); sts16(SM_ZERO, 0, 0, 0, 0); }
      mbar_arrive_warp(bar(B_STAT));
      TL(22, 6);
    }

#pragma unroll 1
    for (int t = wg; t < 22; t += 2) {
      const int l = t >= 11, i = t - l * 11;
      if (t == 0) TL(t, 0);
      if (i < 2) {
        float acc[2][96];
        if (WARM_X && w == 3 && (m & 7) < 7) {
#pragma unroll
          for (int j = 0; j < 6; j++) st_tag(&g_halo[l * 2 + i][m][c][j][lane_now()], 0, 0, 0, 0);
        }
        if (t != 0 && t != 12) mbar_wait(bar(B_TURN) + 8 * wg, (t - 1) >> 1);
        uint32_t Q[4][8], K[4][8], V[4][8], sta, csa;
        float2 st[4];
        auto fix = [&](int g, int j, float2 cs) {
          const int mi = g & 1, half = g >> 1;
          return pack_bf16_v(fmaf(st[g].y, cs.x, acc[mi][j * 4 + half * 2]), fmaf(st[g].y, cs.y, acc[mi][j * 4 + half * 2 + 1]));
        };
        mainloop<0>(acc, sig, t, wg, [&]() {
          const int lane = lane_now();
          mbar_wait(bar(B_FREE), l * 9 + i - 1);
          mbar_arrive_if(bar(B_QT), sig);
          mbar_wait(bar(B_STAT) + l * 16, 0);
          mbar_wait(bar(B_CS) + i * 8, 0);
          sta = SM_STAT + l * 2048 + w * 256;
          csa = SM_CS + (i * 192 + 2 * (lane & 3)) * 4;
          st[1] = lds8f(sta + (8 + (lane >> 2)) * 8); st[3] = lds8f(sta + (24 + (lane >> 2)) * 8);
          const uint32_t r0 = lds4(sta + (24 + 2 * (lane & 3)) * 8), r1 = lds4(sta + (25 + 2 * (lane & 3)) * 8);
#pragma unroll
          for (int j = 0; j < 8; j++) { K[3][j] = fix(3, 8 + j, lds8f(csa + (8 + j) * 32)); V[3][j] = movmat(fix(3, 16 + j, lds8f(csa + (16 + j) * 32))); }
          if (w < 3) {
            const uint32_t xa = SM_STG + (w + 1) * 4096 + lane * 16;
            sts16(xa, K[3][0], K[3][1], K[3][2], K[3][3]); sts16(xa + 512, K[3][4], K[3][5], K[3][6], K[3][7]);
            sts16(xa + 1024, V[3][0], V[3][1], V[3][2], V[3][3]); sts16(xa + 1536, V[3][4], V[3][5], V[3][6], V[3][7]);
            sts8f(xa + 2048, __uint_as_float(r0), __uint_as_float(r1));
            mbar_arrive_warp(bar(B_XCH));
          } else if ((m & 7) < 7) {
            const uint32_t tag = lds4(SM_TAG);
            uint4* const p = &g_halo[l * 2 + i][m][c][0][lane];
            st_tag(p, K[3][0], K[3][1], K[3][2], tag); st_tag(p + 32, K[3][3], K[3][4], K[3][5], tag); st_tag(p + 64, K[3][6], K[3][7], V[3][0], tag);
            st_tag(p + 96, V[3][1], V[3][2], V[3][3], tag); st_tag(p + 128, V[3][4], V[3][5], V[3][6], tag); st_tag(p + 160, V[3][7], r0, r1, tag);
          }
#pragma unroll
          for (int j = 0; j < QSH; j++) { const float2 cs = lds8f(csa + j * 32); Q[1][j] = fix(1, j, cs); Q[3][j] = fix(3, j, cs); }
        });
        TL(t, 3);
        const int lane = lane_now(), q = lane & 3, r8 = lane >> 2;
        st[0] = lds8f(sta + r8 * 8); st[2] = lds8f(sta + (16 + r8) * 8);
#pragma unroll
        for (int j = 0; j < 24; j++) {
          const float2 cs = lds8f(csa + j * 32);
#pragma unroll
          for (int g = 0; g < (j < 8 ? 4 : 3); g++) {
            if (j < QSH && (g & 1)) continue;
            const uint32_t pk = fix(g, j, cs);
            if (j < 8) Q[g][j] = pk; else if (j < 16) K[g][j - 8] = pk; else V[g][j - 16] = movmat(pk);
          }
        }
        const bool up0 = (2 * q) > r8, up1 = (2 * q + 1) > r8;
        const uint32_t mskP = (up0 ? 0xffffu : 0u) | (up1 ? 0xffff0000u : 0u);
        const uint32_t xa = SM_STG + w * 4096 + lane * 16;
        TL(t, 5);
        if (LATE_O) mbar_arrive_if(bar(B_TURN) + 8 * (wg ^ 1), i ? sig : 0);
        mbar_wait(bar(B_XCH), i);
        uint32_t Kp[8], Vp[8];
        lds16(xa, Kp[0], Kp[1], Kp[2], Kp[3]); lds16(xa + 512, Kp[4], Kp[5], Kp[6], Kp[7]);
        lds16(xa + 1024, Vp[0], Vp[1], Vp[2], Vp[3]); lds16(xa + 1536, Vp[4], Vp[5], Vp[6], Vp[7]);
        float rk[4][2], fs[4][2];
#pragma unroll
        for (int g = 0; g < 4; g++) {
          rk[g][0] = lds4f(g == 0 && up0 ? xa + 2048 : sta + (g * 8 + 2 * q - (up0 ? 8 : 0)) * 8);
          rk[g][1] = lds4f(g == 0 && up1 ? xa + 2052 : sta + (g * 8 + 2 * q + 1 - (up1 ? 8 : 0)) * 8);
          const float f = st[g].x * (0.17677669529663687f * LOG2E);
          fs[g][0] = f * rk[g][0]; fs[g][1] = f * rk[g][1];
        }
        TL(i == 0 ? 22 : 23, t < 11 ? 3 : 4);
        float sS[2][4][2], sP[2][4][2], z0, z1, z2, z3;
        if (i == 0) bar_sync(NB_PX, 256);
        lds16f(SM_ZERO, z0, z1, z2, z3);
#pragma unroll
        for (int h = 0; h < 2; h++) {
          float dm0, dm1;
          const int j0 = h * 4;
#pragma unroll
          for (int g = 0; g < 3; g++) mma16816(sS[h][g][0], sS[h][g][1], sP[h][g + 1][0], sP[h][g + 1][1], Q[g][j0], Q[g + 1][j0], Q[g][j0 + 1], Q[g + 1][j0 + 1], K[g][j0], K[g][j0 + 1], z0, z1, z2, z3);
          mma16816(sS[h][3][0], sS[h][3][1], dm0, dm1, Q[3][j0], Q[3][j0], Q[3][j0 + 1], Q[3][j0 + 1], K[3][j0], K[3][j0 + 1], z0, z1, z2, z3);
          mma16816(sP[h][0][0], sP[h][0][1], dm0, dm1, Q[0][j0], Q[0][j0], Q[0][j0 + 1], Q[0][j0 + 1], Kp[j0], Kp[j0 + 1], z0, z1, z2, z3);
        }
#pragma unroll
        for (int h = 0; h < 2; h++) {
          float dm0, dm1;
          const int j0 = h * 4 + 2;
#pragma unroll
          for (int g = 0; g < 3; g++) mma16816(sS[h][g][0], sS[h][g][1], sP[h][g + 1][0], sP[h][g + 1][1], Q[g][j0], Q[g + 1][j0], Q[g][j0 + 1], Q[g + 1][j0 + 1], K[g][j0], K[g][j0 + 1],
                                               sS[h][g][0], sS[h][g][1], sP[h][g + 1][0], sP[h][g + 1][1]);
          mma16816(sS[h][3][0], sS[h][3][1], dm0, dm1, Q[3][j0], Q[3][j0], Q[3][j0 + 1], Q[3][j0 + 1], K[3][j0], K[3][j0 + 1], sS[h][3][0], sS[h][3][1], 0.f, 0.f);
          mma16816(sP[h][0][0], sP[h][0][1], dm0, dm1, Q[0][j0], Q[0][j0], Q[0][j0 + 1], Q[0][j0 + 1], Kp[j0], Kp[j0 + 1], sP[h][0][0], sP[h][0][1], 0.f, 0.f);
        }
        {
          uint32_t x = 0;
#pragma unroll
          for (int h = 0; h < 2; h++) x |= (__float_as_uint(sS[h][0][0]) | __float_as_uint(sS[h][1][0]) | __float_as_uint(sS[h][2][0]) | __float_as_uint(sS[h][3][0]) | __float_as_uint(sP[h][0][0]));
          if (i == 0) bar_arrive(NB_PY + (x & __float_as_uint(z0)), 256);
        }
        const bool noprev = (m & 7) == 0 && w == 0;
        uint32_t PS[2][4], PP[2][4];
#pragma unroll
        for (int h = 0; h < 2; h++)
#pragma unroll
          for (int g = 0; g < 4; g++) {
            float v0 = (up0 ? sP[h][g][0] : sS[h][g][0]) * fs[g][0], v1 = (up1 ? sP[h][g][1] : sS[h][g][1]) * fs[g][1];
            if (g == 0) { if (noprev && up0) v0 = -1e9f * LOG2E; if (noprev && up1) v1 = -1e9f * LOG2E; }
            float mx = fmaxf(v0, v1);
            mx = fmaxf(mx, __shfl_xor_sync(0xffffffffu, mx, 1)); mx = fmaxf(mx, __shfl_xor_sync(0xffffffffu, mx, 2));
            const float e0 = ex2f(v0 - mx), e1 = ex2f(v1 - mx);
            float sum = e0 + e1;
            sum += __shfl_xor_sync(0xffffffffu, sum, 1); sum += __shfl_xor_sync(0xffffffffu, sum, 2);
            const float inv = rcpf(sum);
            const uint32_t pk = pack_bf16_v(e0 * inv * rk[g][0], e1 * inv * rk[g][1]);
            PS[h][g] = pk & ~mskP; PP[h][g] = pk & mskP;
          }
        TL(23, i == 0 ? (t < 11 ? 5 : 6) : 7);
        float O[2][4][4][2];
        {
          uint32_t x = 0;
#pragma unroll
          for (int h = 0; h < 2; h++) x |= PS[h][0] | PS[h][1] | PS[h][2] | PS[h][3];
          if (i == 0) bar_sync(NB_PX + (x & __float_as_uint(z0)), 256);
        }
        lds16f(SM_ZERO, z0, z1, z2, z3);
#pragma unroll
        for (int h = 0; h < 2; h++)
#pragma unroll
          for (int j = 0; j < 4; j++) {
            const int jj = h * 4 + j;
            float dm0, dm1;
            mma16816(O[h][1][j][0], O[h][1][j][1], O[h][2][j][0], O[h][2][j][1], PS[h][1], PP[h][2], PP[h][1], 0u, V[1][jj], V[0][jj], z0, z1, z2, z3);
            mma16816(O[h][0][j][0], O[h][0][j][1], dm0, dm1, PS[h][0], 0u, PP[h][0], 0u, V[0][jj], Vp[jj], z0, z1, z2, z3);
          }
#pragma unroll
        for (int h = 0; h < 2; h++)
#pragma unroll
          for (int j = 0; j < 4; j++) {
            const int jj = h * 4 + j;
            mma16816(O[h][3][j][0], O[h][3][j][1], O[h][2][j][0], O[h][2][j][1], PS[h][3], 0u, PP[h][3], PS[h][2], V[3][jj], V[2][jj], 0.f, 0.f, O[h][2][j][0], O[h][2][j][1]);
          }
        {
          uint32_t x = 0;
#pragma unroll
          for (int h = 0; h < 2; h++)
#pragma unroll
            for (int j = 0; j < 4; j++) x |= __float_as_uint(O[h][0][j][0]) | __float_as_uint(O[h][3][j][0]);
          if (i == 0 || !LATE_GO) bar_arrive((i == 0 ? NB_PY : NB_OGO) + (x & __float_as_uint(z0)), 256);
        }
        const uint32_t sa = SM_STG + (w * 32 + (lane & 7)) * 128 + (((lane >> 3) ^ (lane & 7)) << 4);
#pragma unroll
        for (int h = 0; h < 2; h++)
#pragma unroll
          for (int g = 0; g < 4; g++)
            stsm4((sa ^ (h * 64)) + g * 1024, pack_bf16(O[h][g][0][0], O[h][g][0][1]), pack_bf16(O[h][g][1][0], O[h][g][1][1]),
                  pack_bf16(O[h][g][2][0], O[h][g][2][1]), pack_bf16(O[h][g][3][0], O[h][g][3][1]));
        if (i) copy_out<8>(SM_STG + w * 4096, reinterpret_cast<char*>(g_o + (size_t)(m * 128 + w * 32) * D_ + (8 + c) * 64), D_ * 2, lane);
        mbar_arrive_warp(bar(B_SIG + 1));
        if (LATE_GO && i) bar_arrive(NB_OGO, 256);
        TL(t, 6);
      } else if (i > 2 && i < 10) {
        float acc[2][64];
        if (i != 4) mbar_wait(bar(B_TURN) + 8 * wg, (t - 1) >> 1);
        float2 cs[16];
        float c1[4], vr[4];
        uint32_t so, sta;
        mainloop<1>(acc, sig, t, wg, [&]() {
          const int lane = lane_now();
          so = SM_STG + (w * 16 + (lane & 7)) * 128 + (((lane >> 3) ^ (lane & 7)) << 4);
          sta = SM_STAT + (l * 2 + 1) * 1024 + (w * 16 + (lane >> 2)) * 8;
          mbar_wait(bar(B_STAT + 1) + l * 16, 0);
          mbar_wait(bar(B_CS - 1) + 8 * i, 0);
#pragma unroll
          for (int j = 0; j < 16; j++) cs[j] = lds8f(SM_CS + i * 512 + (lane & 3) * 8 + j * 32);
#pragma unroll
          for (int j = 0; j < 4; j++) {
            const float r = lds4f(sta + (j >> 1) * 512 + (j & 1) * 64);
            if (TANH) { vr[j] = r; c1[j] = r * 0.5f; }
            else {
              asm volatile("rcp.approx.ftz.f32 %0, %1;" : "=f"(vr[j]) : "f"(r * r));
              c1[j] = r * -LOG2E;
            }
          }
          mbar_wait(bar(B_FREE), l * 9 + i - 2);
        });
        TL(t, 3);
        float mn[8];
#pragma unroll
        for (int x = 0; x < GLA; x++) mn[x] = __uint_as_float(lds4(sta + 4 + (x >> 2) * 512 + ((x >> 1) & 1) * 64));
#pragma unroll
        for (int x = 0; x < 8; x++) {
          const int mi = x >> 2, half = (x >> 1) & 1, g = x & 1;
          const float var = vr[x >> 1], cc = c1[x >> 1];
          uint32_t v[4];
#pragma unroll
          for (int j = 0; j < 4; j++) {
            const int jj = g * 4 + j;
            const float2 cg = cs[jj], cu = cs[8 + jj];
            const float g0 = fmaf(mn[x], cg.x, acc[mi][jj * 4 + half * 2]), g1 = fmaf(mn[x], cg.y, acc[mi][jj * 4 + half * 2 + 1]);
            const float u0 = fmaf(mn[x], cu.x, acc[mi][(jj + 8) * 4 + half * 2]), u1 = fmaf(mn[x], cu.y, acc[mi][(jj + 8) * 4 + half * 2 + 1]);
            if (TANH) {
              const float a0 = g0 * cc, a1 = g1 * cc;
              const float s0 = fmaf(a0, tanhf_(a0), a0), s1 = fmaf(a1, tanhf_(a1), a1);
              v[j] = TANH == 2 ? pack_bf16(s0 * u0, s1 * u1) : pack_bf16(s0 * u0 * var, s1 * u1 * var);
            } else {
              const float r0 = rcpf(fmaf(ex2f(g0 * cc), var, var)), r1 = rcpf(fmaf(ex2f(g1 * cc), var, var));
              v[j] = pack_bf16(g0 * u0 * r0, g1 * u1 * r1);
            }
          }
          stsm4((so ^ (g * 64)) + (mi * 64 + half * 8) * 128, v[0], v[1], v[2], v[3]);
          if ((x & 3) == 3) mbar_arrive_warp(bar(B_SIG + mi));
          if (x + GLA < 8) mn[x + GLA] = __uint_as_float(lds4(sta + 4 + ((x + GLA) >> 2) * 512 + (((x + GLA) >> 1) & 1) * 64));
        }
        TL(t, 6);
      } else {
        float acc[2][64], rsc[4];
        {
          const int lane = lane_now();
          const uint32_t e = c_sched.task[t].res, rs = e & 0xffff;
          const uint32_t ra = SB + (w * 16 + (lane & 7)) * 128 + (((lane >> 3) ^ (lane & 7)) << 4);
          float sd[4];
#pragma unroll
          for (int j = 0; j < 4; j++) {
            rsc[j] = i == 10 ? lds4f(SM_STAT + (l * 2 + 1) * 1024 + ((j >> 1) * 64 + w * 16 + (j & 1) * 8 + (lane >> 2)) * 8) : 1.f;
            sd[j] = rcpf(rsc[j]);
          }
          const uint32_t zero = lds4(SM_ZERO);
          mbar_wait(bar(B_FULL) + (rs & 15) * 8, rs >> 4);
          uint32_t dep[16];
#pragma unroll
          for (int x = 0; x < 16; x++) {
            const int mi = x >> 3, half = (x >> 2) & 1, g = x & 3;
            uint32_t v[4];
            ldsm4(((e >> (16 + (g >> 1) * 8)) & 31) * 8192 + ((ra ^ ((g & 1) * 64)) | (RLA && x >= RLA ? dep[x - RLA] : 0)) + (mi * 64 + half * 8) * 128, v[0], v[1], v[2], v[3]);
#pragma unroll
            for (int j = 0; j < 4; j++) {
              asm volatile("shl.b32 %0, %1, 16;" : "=f"(acc[mi][(g * 4 + j) * 4 + half * 2]) : "r"(v[j]));
              asm volatile("and.b32 %0, %1, 0xffff0000;" : "=f"(acc[mi][(g * 4 + j) * 4 + half * 2 + 1]) : "r"(v[j]));
              if (TANH == 2) { acc[mi][(g * 4 + j) * 4 + half * 2] *= sd[mi * 2 + half]; acc[mi][(g * 4 + j) * 4 + half * 2 + 1] *= sd[mi * 2 + half]; }
            }
            asm("and.b32 %0, %1, %2;" : "=r"(dep[x]) : "f"(acc[mi][(g * 4 + 3) * 4 + half * 2 + 1]), "r"(zero));
          }
          bar_sync(NB_WG + wg, 128);
          release(rs * 8 + 16, sig);
        }
        mbar_wait(bar(B_TURN) + 8 * wg, (t - 1) >> 1);
        if (i == 10) mbar_wait(bar(B_GATE), l);
        auto stage = [&](int mi, int hi) {
          const int lane = lane_now();
          const uint32_t sw = SB + ((c_sched.task[t].stg >> (8 * hi)) & 31) * 8192 + (mi * 64 + w * 16) * 128, so = sw + (lane & 7) * 128 + (((lane >> 3) ^ (lane & 7)) << 4);
#pragma unroll
          for (int half = 0; half < 2; half++)
#pragma unroll
            for (int g = 0; g < 2; g++) {
              uint32_t v[4];
#pragma unroll
              for (int j = 0; j < 4; j++) {
                if (TANH == 2) { acc[mi][(hi * 8 + g * 4 + j) * 4 + half * 2] *= rsc[mi * 2 + half]; acc[mi][(hi * 8 + g * 4 + j) * 4 + half * 2 + 1] *= rsc[mi * 2 + half]; }
                v[j] = pack_bf16(acc[mi][(hi * 8 + g * 4 + j) * 4 + half * 2], acc[mi][(hi * 8 + g * 4 + j) * 4 + half * 2 + 1]);
              }
              stsm4((so ^ (g * 64)) + half * 1024, v[0], v[1], v[2], v[3]);
            }
          if (hi == 0 || t == 21) {
            const int r = mi * 64 + w * 16;
            bf16* const g = t == 21 ? P.out + (size_t)((row0 + r) * 2 + par) * D_ : g_y + (size_t)(m * 128 + r) * D_;
            copy_out<4>(sw, reinterpret_cast<char*>(g + (hi * 8 + c) * 64), t == 21 ? D_ * 4 : D_ * 2, lane);
          }
        };
        mainloop<2>(acc, sig, t, wg, [&]() { stage(0, 0); stage(0, 1); });
        TL(t, 3);
        stage(1, 0); mbar_arrive_warp(bar(B_SIG + 1));
        TL(t, 6);
        stage(1, 1); mbar_arrive_warp(bar(B_SIG + 2));
        if (t < 21) {
          const int lane = lane_now(), q = lane & 3;
          float s[4], s2[4];
#pragma unroll
          for (int x = 0; x < 4; x++) {
            float a0 = 0.f, a1 = 0.f, b0 = 0.f, b1 = 0.f;
#pragma unroll
            for (int j = 0; j < 16; j++) {
              const float d0 = acc[x >> 1][j * 4 + (x & 1) * 2], d1 = acc[x >> 1][j * 4 + (x & 1) * 2 + 1];
              a0 += d0; a1 += d1; b0 = fmaf(d0, d0, b0); b1 = fmaf(d1, d1, b1);
            }
            s[x] = a0 + a1; s2[x] = b0 + b1;
          }
#pragma unroll
          for (int x = 0; x < 2; x++) {
            s[x] = (q & 2 ? s[x + 2] : s[x]) + __shfl_xor_sync(0xffffffffu, q & 2 ? s[x] : s[x + 2], 2);
            s2[x] = (q & 2 ? s2[x + 2] : s2[x]) + __shfl_xor_sync(0xffffffffu, q & 2 ? s2[x] : s2[x + 2], 2);
          }
          const float r = (q & 1 ? s[1] : s[0]) + __shfl_xor_sync(0xffffffffu, q & 1 ? s[0] : s[1], 1);
          const float r2 = (q & 1 ? s2[1] : s2[0]) + __shfl_xor_sync(0xffffffffu, q & 1 ? s2[0] : s2[1], 1);
          asm volatile("st.global.v2.f32 [%0], {%1, %2};" ::"l"(&g_stat[i == 10 ? 1 : l * 2][m][c][(q >> 1) * 64 + w * 16 + (q & 1) * 8 + (lane >> 2)]), "f"(r), "f"(r2) : "memory");
          mbar_arrive_warp(bar(B_SIG + 3));
        }
      }
    }
  }
}

typedef CUresult (*PFN_encodeTiled)(CUtensorMap*, CUtensorMapDataType, cuuint32_t, void*, const cuuint64_t*, const cuuint64_t*, const cuuint32_t*,
                                    const cuuint32_t*, CUtensorMapInterleave, CUtensorMapSwizzle, CUtensorMapL2promotion, CUtensorMapFloatOOBfill);

void make_map(PFN_encodeTiled enc, CUtensorMap* mp, const void* ptr, uint64_t d0, uint64_t d1, uint64_t d2, uint64_t s1, uint64_t s2, uint32_t b1, uint32_t b2) {
  cuuint64_t gd[3] = {d0, d1, d2}, gs[2] = {s1 * 2, s2 * 2};
  cuuint32_t bd[3] = {64, b1, b2}, es[3] = {1, 1, 1};
  enc(mp, CU_TENSOR_MAP_DATA_TYPE_BFLOAT16, 3, const_cast<void*>(ptr), gd, gs, bd, es, CU_TENSOR_MAP_INTERLEAVE_NONE, CU_TENSOR_MAP_SWIZZLE_128B,
      CU_TENSOR_MAP_L2_PROMOTION_L2_256B, CU_TENSOR_MAP_FLOAT_OOB_FILL_NONE);
}
void make_map_act(PFN_encodeTiled enc, CUtensorMap* mp, const void* ptr, uint64_t cols, bool natural, uint32_t rows) {
  make_map(enc, mp, ptr, cols, S_ / 2, 2, natural ? 2 * cols : cols, natural ? cols : cols * (S_ / 2), rows, 1);
}
void make_map_w(PFN_encodeTiled enc, CUtensorMap* mp, const void* ptr, uint64_t rows, uint64_t cols, uint32_t nb) {
  make_map(enc, mp, ptr, cols / nb, rows, nb, cols, cols / nb, 64, nb);
}

}

extern "C" void kernel_launch(void* const* d_in, const int* in_sizes, int n_in, void* d_out, int out_size) {
  (void)in_sizes; (void)n_in; (void)out_size;
  static PFN_encodeTiled enc = nullptr;
  static void *p_o, *p_y, *p_h;
  if (!enc) {
    void* fn = nullptr; cudaDriverEntryPointQueryResult qr;
    cudaGetDriverEntryPoint("cuTensorMapEncodeTiled", &fn, cudaEnableDefault, &qr);
    enc = (PFN_encodeTiled)fn;
    cudaGetSymbolAddress(&p_o, g_o); cudaGetSymbolAddress(&p_y, g_y); cudaGetSymbolAddress(&p_h, g_h);
    cudaFuncSetAttribute(fused_kernel, cudaFuncAttributeMaxDynamicSharedMemorySize, SM_TOTAL);
  }
  Params P;
  P.x0 = (const bf16*)d_in[0]; P.wqkv = (const bf16*)d_in[1]; P.out = (bf16*)d_out;
  make_map_act(enc, &P.tm[M_X0], d_in[0], D_, true, 128);
  make_map_act(enc, &P.tm[M_O], p_o, D_, false, 128);
  make_map_act(enc, &P.tm[M_Y], p_y, D_, false, 128);
  make_map_act(enc, &P.tm[M_H], p_h, F_, false, 128);
  make_map_act(enc, &P.tm[M_OL], p_o, D_, false, PROWS);
  make_map_act(enc, &P.tm[M_YL], p_y, D_, false, PROWS);
  make_map_act(enc, &P.tm[M_HL], p_h, F_, false, PROWS);
  make_map_w(enc, &P.tm[M_WQKV], d_in[1], D_, 3 * D_, 3);
  make_map_w(enc, &P.tm[M_WO], d_in[2], D_, D_, 2);
  make_map_w(enc, &P.tm[M_W1], d_in[4], D_, F_, 1);
  make_map_w(enc, &P.tm[M_W3], d_in[5], D_, F_, 1);
  make_map_w(enc, &P.tm[M_W2], d_in[6], F_, D_, 2);
  fused_kernel<<<NCTA + NHELP, 384, SM_TOTAL>>>(P);
}
```

```cpp
#include <cuda_runtime.h>
#include <cuda_bf16.h>
#include <cuda.h>
#include <stdint.h>
#include <stddef.h>

typedef __nv_bfloat16 bf16;
#define GU_E 3
#define G_N1 7
#define G_R1 16
#define Q_P1 4
#define Q_P2 6
#define Q_P0 0
#define O_W 0
#define O_NW ((O_W & 1) + ((O_W >> 1) & 1))
#define ST_ROWS 6000
#define PROWS 16
#define GAP_O 100
#define GAP_Y 50
#define GAP_H 450
#define GAP_H6 1000
#define DEP32 0x84
#define HOLD 17
#define GLA 2
#define RELQ 3
#define RELG 1
#define RELD 3
#define WARM_T 4000
#define RLA 1
#define PUNR_ 1
constexpr int PUNR = PUNR_;
#define PF0 1
#define PXE 1
#define HOLD_O (6 + O_NW)
#define SH1 0
#define CPY 0
#define RES_O 3
#define RES_D 3
#define ST_N0 1
#define ST_T1 900
#define ST_D1 500
#define SCH 1
#define QUIET 1
#define QOWN 1
#define TANH 2
#define TAILQ 1
#define TAIL 2
#define WARM_X 1

namespace {

constexpr int S_ = 2048, D_ = 1024, F_ = 3584;
constexpr int NCTA = 128;
constexpr int NHELP = 4;

constexpr uint32_t SB = 1024;
constexpr int NU = 25;
constexpr uint32_t SM_STG  = SB + NU * 8192;
__host__ __device__ constexpr uint32_t xch(int i, int w) { return i ? SM_STG - 8192 + w * 2048 : SM_STG + w * 4096; }
constexpr uint32_t SM_STAT = SM_STG + 16384;
__host__ __device__ constexpr uint32_t stat(int set) { return SM_STAT + set * 1088 + 64; }
constexpr uint32_t SM_CS   = SM_STAT + 4352;
constexpr uint32_t BARS    = SM_CS + 5120;
constexpr int SM_TOTAL = BARS + 896 - SB;
static_assert(BARS % 128 == 0 && SM_TOTAL <= 232448, "smem");
constexpr int B_FULL = 0, B_EMPTY = 16, B_SIG = 32, B_XCH = 36, B_STAT = 37, B_TURN = 41, B_CS = 43, B_FREE = 52, B_SF = 53, B_QT = 55, B_PASS = 56,
              B_DEP = 57, B_PUB = 73, B_RES = 89, B_RF = 90, B_N = 91;
__host__ __device__ constexpr uint32_t bar(int i) { return BARS + 8 * i; }
constexpr uint32_t SM_TAG = BARS + 8 * B_N, SM_ZERO = BARS + 768;
constexpr int NB_WG = 1, NB_PX = 3, NB_PY = 4, NB_INIT = 5, NB_OGO = 6;

constexpr int E_O0 = 0, E_O1 = 1, E_YA = 2, E_YB = 3, E_H4 = 4, E_XA = 7, E_XB = 8, E_N = 9;

constexpr int M_X0 = 0, M_O = 1, M_Y = 2, M_H = 3;
constexpr int M_WQKV = 4, M_WO = 5, M_W13 = 6, M_W13P = 7, M_W2 = 8;
constexpr int M_OL = 9, M_YL = 10, M_HL = 11, M_N = 12;

constexpr int FIRST = 5;
constexpr int NOPA = 416, NOPB = 416, NSEG = 80;
constexpr uint32_t A_END = 1, A_TURN = 2, A_DRAIN = 4, A_WAIT = 8, A_SYNC = 16,
                   A_MARK = 0;
struct Task { uint32_t seg, stg, res, sig; };
struct Seg { uint32_t i8, end8, a, b; };
constexpr uint32_t LO_A = 0x10000 + SB / 16, LO_B = 0x2000000 + SB / 16;
struct Sched { Task task[22]; uint32_t pad[8]; Seg seg[NSEG]; };
struct Ops { uint2 a[NOPA + 64], b[NOPB + 64]; };
struct Gen {
  Sched s{}; Ops o{};
  int n[2] = {0, 0}, nseg = 0, cur = -1, pos = 0, err = 0, res = 0, nres = 0;
  int mask[400] = {}, sa[400] = {}, sb[400][2] = {}, own[NU][2] = {}, tok[NU] = {}, known[2][2] = {{-1, -1}, {-1, -1}};
  constexpr void emit(int p, int wait, int par, int dst, int map, int kb8, int arr, int load, int y) {
    if (cur < FIRST) return;
    const uint2 e{(uint32_t)(dst | (cur & 15) << 5 | map << 9 | (y & 63) << 13 | (y >> 10) << 19 | load << 22 | wait << 23 | res << 30) | (uint32_t)(par & 1) << 31,
                  (uint32_t)(((y >> 6) & 15) | arr << 4 | (!p && arr && mask[cur] != 3 && !res) << 5 | kb8 << 13)};
    if (p) o.b[n[1]++] = e; else o.a[n[0]++] = e;
  }
  constexpr bool done(int p, int x) const { return x < 0 || ((!(mask[x] & 1) || known[p][0] >= x) && (!(mask[x] & 2) || known[p][1] >= x)); }
  constexpr void op(int p, int dst, int nu, int map, int kb8, int arr, int y, int xw = -1, int xp = 0) {
    int w[8] = {}, wp[8] = {}, nw = 0;
    if (xw >= 0) { w[nw] = xw; wp[nw++] = xp; }
    for (int u = dst; u < dst + nu; u++) if (tok[u] && (u == dst || tok[u] != tok[u - 1])) { w[nw] = (tok[u] - 1) >> 1; wp[nw++] = tok[u] - 1; }
    for (int x = cur - 1; x >= 0; x--) {
      bool need = x <= cur - 12;
      for (int u = dst; u < dst + nu; u++) need = need || own[u][0] == x + 1 || own[u][1] == x + 1;
      if (!need || done(p, x)) continue;
      if (cur - x >= 16 || !done(p, x - 16)) err |= 1;
      w[nw] = B_EMPTY + ((x + 2) & 15); wp[nw++] = x >> 4;
      for (int g = 0; g < 2; g++) if (((mask[x] >> g) & 1) && known[p][g] < x) known[p][g] = x;
    }
    for (; nw > 1; nw--) emit(p, w[nw - 1], wp[nw - 1], 0, 0, 0, 0, 0, 0);
    emit(p, nw ? w[0] : B_PASS, nw ? wp[0] : 1, dst, map, kb8, arr, nu > 0, y);
    for (int u = dst; u < dst + nu; u++) { own[u][0] = cur + 1; own[u][1] = 0; tok[u] = 0; }
  }
  constexpr int step(int m) { mask[++cur] = m; return cur; }
  constexpr int slot() { int u = (pos + 1) & ~1; if (u >= 24) u = 0; pos = u + 2; return u; }
  constexpr int qslot() { int u = (pos + 4) / 5 * 5; if (u >= NU) u = 0; pos = u + 5; return u; }
  constexpr void stage(int u, int first, int t) {
    if (!(SH1 && t)) first -= TAIL;
    for (int x = u; x < u + 2; x++) { if (own[x][0] > first || own[x][1] > first || tok[x]) err |= 2; own[x][0] = cur + 1; own[x][1] = 0; tok[x] = t; }
  }
  static constexpr int kown(int hi) { return hi * 8 | 1 << 9; }
  static constexpr int kskip(int hi, int j) { return (hi * 8 + j) | (j + 1) << 6; }
  static constexpr int kpos(int p) { return p < 2 ? kown(p) : p < 9 ? kskip(0, p - 2) : kskip(1, p - 9); }
  constexpr void segs(int t, const int* st, const uint32_t* act, int cnt, int tail, int inc0) {
    const int g = t & 1, wrap = inc0 == 5 ? NU : 24;
    s.task[t].seg = nseg;
    int j0 = 0;
    for (int j = 0; j < cnt; j++) {
      const int x = st[j], inc = inc0 ? inc0 : mask[st[j0]] == 3 ? 6 : 4;
      const bool next = j + 1 < cnt && st[j + 1] == x + 1 && mask[x + 1] == mask[x] && sa[x + 1] == (sa[x] + inc) % wrap && sb[x + 1][g] == (sb[x][g] + inc) % wrap;
      if (j >= cnt - tail - 1 && j + 1 < cnt && !next) err |= 4;
      if (j + 1 < cnt && st[j + 1] != x + 1 && !(act[j] & A_DRAIN)) err |= 8;
      if (j >= cnt - tail || (next && !act[j] && j != cnt - tail - 1)) continue;
      if (j == j0 && (j == 0 || (inc0 != 4 && (act[j - 1] & (A_DRAIN | A_SYNC))))) err |= 16;
      const int y = st[j0];
      s.seg[nseg++] = Seg{(uint32_t)y * 8 | (act[j] | (j == cnt - tail - 1 ? A_END : 0)) << 16, (uint32_t)(x + 1) * 8 | inc * 512 << 16, LO_A + sa[y] * 512, LO_B + sb[y][g] * 512};
      j0 = j + 1;
    }
  }
  constexpr void residual(int t, int map, bool q) {
    const int u0 = q ? qslot() : slot(), u1 = q ? u0 + 2 : slot();
    res = 1;
    op(0, u0, 2, map, 4, 1, kown(0)); op(0, u1, 2, map, 0, 0, kown(1));
    res = 0;
    for (int x = 0; x < 4; x++) { const int u = (x < 2 ? u0 : u1) + (x & 1); own[u][0] = 0; tok[u] = 1 + B_RF * 2 + (nres & 1); }
    nres++;
    s.task[t].res = u0 | u1 << 8;
  }
  constexpr Gen() {
    int cs[4] = {};
    for (int t = 0; t < 22; t++) {
      const int i = t % 11, use = i < 2 ? 2 : (i == 2 || i == 10) ? 15 : 3;
      for (int x = 0; x < 4; x++) if ((use >> x) & 1) s.task[t].sig |= (cs[x]++ & 1) << x;
    }
    for (int l = 0; l < 2; l++) {
      const int T = l * 11, dep = B_DEP + l * E_N;
      int st[7][56] = {};
      uint32_t act[7][56] = {};
      if (l == 1) {
        const int first = cur + 1;
        for (int j = 0; j < 4; j++) {
          const int x = st[j >> 1][j & 1] = step(1 << ((T + (j >> 1)) & 1)), u = qslot();
          sb[x][0] = sb[x][1] = u + 2;
          if (j < 2) {
            sa[x] = (u + QOWN * 5) % NU; stage(sa[x], first, j ? 1 + B_SF * 2 + 1 : 0); s.task[10].stg |= sa[x] << (8 * j);
            op(0, 0, 0, 0, 0, 1, 1 << 10, B_SIG + 2 * j, s.task[10].sig >> (2 * j));
          }
          else { sa[x] = sa[x - 2]; own[sa[x]][1] = own[sa[x] + 1][1] = x + 1; op(0, 0, 0, 0, 0, 1, 0); }
          op(1, u + 2, 3, M_WQKV, 3, 1, kown(j & 1) | (j >> 1) << 10);
        }
        act[0][1] = A_DRAIN; act[1][1] = A_DRAIN | A_WAIT;
      }
      for (int i = 0; i < 2; i++) {
        for (int j = 2 * l; j < 16; j++) {
          if (i && j == 16 - RES_O) residual(T + 2, l ? M_Y : M_X0, true);
          const int x = st[i][j] = step(1 << ((T + i) & 1)), u = qslot(), k = l ? kpos(j) : j;
          sa[x] = u; sb[x][0] = sb[x][1] = u + 2;
          op(0, u, 2, l ? M_Y : M_X0, 2, 1, k, l && i == 0 && (j == 2 || j == 9) ? B_DEP + (j == 2 ? E_XA : E_XB) : -1);
          op(1, u + 2, 3, M_WQKV, 3, 1, k | i << 10, (HOLD & 2) && l && i == 0 && j == 2 ? B_PUB + E_XA : (HOLD & 8) && l && i == 0 && j == 3 ? B_DEP + E_XA : -1);
        }
        if (i) act[1][Q_P1 - 1 + (l ? 2 : Q_P0)] = act[1][Q_P2 - 1 + (l ? 2 : Q_P0)] = A_SYNC;
        if (i && own[NU - 1][0] > cur - TAILQ) err |= 256;
        segs(T + i, st[i], act[i], 16, TAILQ, 5);
      }
      if (!RES_O) residual(T + 2, l ? M_Y : M_X0, false);
      for (int j = 0; j < 16; j++) {
        const int x = st[0][j] = step(1 << (T & 1)), k = j < 8 ? j : j == 8 ? kown(1) : kskip(1, j - 9);
        act[0][j] = j > 0 && j <= O_NW ? A_SYNC | j << 8 : j == 8 ? A_MARK : 0;
        if (j == 8) { sa[x] = NU; op(0, 0, 0, 0, 0, 1, 1 << 10, B_SIG + 1, s.task[T + 1].sig >> 1); }
        else { sa[x] = slot(); op(0, sa[x], 2, M_O, 2, 1, k, j == 0 ? dep + E_O0 : j == 9 ? dep + E_O1 : j == HOLD_O ? B_PUB + l * E_N + E_O1 : -1); }
        sb[x][0] = sb[x][1] = slot();
        op(1, sb[x][0], 2, M_WO, 2, 1, k, j == HOLD_O ? B_PUB + l * E_N + E_O1 : -1);
      }
      segs(T + 2, st[0], act[0], 16, TAIL, 4);
      int beg[8] = {0, G_R1}, end[7] = {16, G_R1 + 16 - G_N1}, cnt[7] = {};
      for (int j = 2; j < 7; j++) { beg[j] = end[j - 2] + GU_E; end[j] = beg[j] + 16; }
      beg[7] = end[6];
      const int first = cur + 1;
      for (int j = 0; j < end[6]; j++) {
        int tl[2] = {-1, -1}, m = 0;
        for (int v = 0; v < 7; v++) if ((j >= beg[v] && j < end[v]) || (v == 1 && j < G_N1)) { const int g = (T + 3 + v) & 1; if (tl[g] >= 0) err |= 32; tl[g] = v; m |= 1 << g; }
        if (!m) err |= 32;
        if (j == end[6] - RES_D) residual(T + 10, M_Y, false);
        const int x = step(m), k = kpos(j < 16 ? j : (j + G_N1) & 15);
        const int v0 = m == 3 ? (tl[0] < tl[1] ? tl[0] : tl[1]) : tl[m >> 1];
        const int ps = (pos + 1) / 2 % 12;
        const bool last = m == 3 && (ps % 3 == 1 || (QUIET && j >= 2 && j < G_N1 && (ps % 3 == 0 || (j == 2 && ps != 11))));
        if (!last) sa[x] = slot();
        const int u = slot();
        if (m == 3 && slot() != u + 2) err |= 32;
        if (last) sa[x] = slot();
        if (j < 2) { stage(sa[x], first, j ? 1 + B_SF * 2 : 0); s.task[T + 2].stg |= sa[x] << (8 * j); op(0, 0, 0, 0, 0, 1, 1 << 10, B_SIG + 2 * j, s.task[T + 2].sig >> (2 * j)); }
        else op(0, sa[x], 2, M_Y, 2, 1, k, j == 2 ? dep + E_YA : j == 9 ? dep + E_YB : -1);
        op(1, u, m == 3 ? 4 : 2, m == 3 ? M_W13P : M_W13, m == 3 ? 4 : 2, 1, k | v0 << 10, (HOLD & 1) && j == 2 + QUIET ? (HOLD & 4 ? B_DEP : B_PUB) + l * E_N + E_YA : -1);
        for (int g = 0; g < 2; g++) {
          const int v = tl[g];
          if (v < 0) continue;
          sb[x][g] = u + (v - v0) * 2;
          act[v][cnt[v]] = j == beg[v + 1] - 1 ? A_TURN : v == 1 && j == G_N1 - 1 ? A_DRAIN | A_WAIT : v == 0 && j == 1 ? A_MARK : 0;
          st[v][cnt[v]++] = x;
        }
      }
      for (int v = 0; v < 7; v++) { if (cnt[v] != 16) err |= 64; segs(T + 3 + v, st[v], act[v], 16, 0, 0); }
      if (!RES_D) residual(T + 10, M_Y, false);
      for (int j = 0; j < 56; j++) {
        const int x = st[0][j] = step(1 << (T & 1));
        act[0][j] = 0;
        sa[x] = slot(); op(0, sa[x], 2, M_H, 2, 1, j, j == 0 ? dep + E_H4 : j == 40 ? dep + E_H4 + 1 : j == 48 ? dep + E_H4 + 2 : -1);
        sb[x][0] = sb[x][1] = slot(); op(1, sb[x][0], 2, M_W2, 2, 1, j);
      }
      segs(T + 10, st[0], act[0], 56, TAIL, 4);
    }
    { const int u0 = slot(), u1 = slot(); stage(u0, cur + 1, 0); stage(u1, cur + 1, 0); s.task[21].stg = u0 | u1 << 8; }
    if (n[0] > NOPA || n[1] > NOPB || nseg > NSEG) err |= 128;
    for (int x = n[0]; x < NOPA + 64; x++) o.a[x] = uint2{B_PASS << 23 | 1u << 31, 0};
    for (int x = n[1]; x < NOPB + 64; x++) o.b[x] = uint2{B_PASS << 23 | 1u << 31, 0};
  }
};
constexpr Gen GEN{};
static_assert(GEN.err == 0, "schedule");
constexpr int NOP0 = (GEN.n[0] + 31) / 32 * 32, NOP1 = (GEN.n[1] + 31) / 32 * 32;

struct __align__(64) Params {
  CUtensorMap tm[M_N];
  const bf16* x0;
  bf16* out;
  int by_sm;
};

}

__constant__ Sched c_sched = GEN.s;
__device__ const Ops g_ops = GEN.o;
__device__ __align__(1024) bf16 g_o[S_ * D_];
__device__ __align__(1024) bf16 g_y[S_ * D_];
__device__ __align__(1024) bf16 g_h[S_ * F_];
__device__ __align__(1024) bf16 g_w13[2 * D_ * F_];
__device__ __align__(128) float2 g_stat[3][16][8][128];
__device__ __align__(128) uint4 g_stat0[16][128];
__device__ __align__(128) uint4 g_halo[4][16][8][6][32];
__device__ __align__(128) uint4 g_cs[9][8][64];
__device__ __align__(128) uint32_t g_flags[NCTA][32];
__device__ uint32_t g_epoch[NCTA + NHELP];

#define TL(t, i) do {} while (0)
#define TL1(t, i) do {} while (0)
#define TS(i8, wg) do {} while (0)
#define TLW(t, i) do {} while (0)
#define MB_LIMIT (1 << 16)
#define FL_LIMIT (1 << 21)

namespace {

__device__ __forceinline__ uint32_t smem_u32(const void* p) { return (uint32_t)__cvta_generic_to_shared(p); }
__device__ __forceinline__ void mbar_init(uint32_t br, uint32_t cnt) { asm volatile("mbarrier.init.shared::cta.b64 [%0], %1;" ::"r"(br), "r"(cnt)); }
__device__ __forceinline__ void mbar_expect_tx(uint32_t br, uint32_t bytes) { asm volatile("mbarrier.arrive.expect_tx.shared::cta.b64 _, [%0], %1;" ::"r"(br), "r"(bytes) : "memory"); }
__device__ __forceinline__ void mbar_arrive(uint32_t br) { asm volatile("mbarrier.arrive.shared::cta.b64 _, [%0];" ::"r"(br) : "memory"); }
__device__ __forceinline__ void mbar_arrive_if(uint32_t br, uint32_t p) {
  asm volatile("{\n.reg .pred q;\nsetp.ne.u32 q, %1, 0;\n@q mbarrier.arrive.shared::cta.b64 _, [%0];\n}\n" ::"r"(br), "r"(p) : "memory");
}
__device__ __forceinline__ void mbar_arrive_cnt(uint32_t br, uint32_t cnt) {
  asm volatile("{\n.reg .pred q;\nsetp.ne.u32 q, %1, 0;\n@q mbarrier.arrive.shared::cta.b64 _, [%0], %1;\n}\n" ::"r"(br), "r"(cnt) : "memory");
}
__device__ __forceinline__ void mbar_arrive_warp(uint32_t br) {
  asm volatile("{\n.reg .pred q;\nbar.warp.sync 0xffffffff;\nelect.sync _|q, 0xffffffff;\n@q mbarrier.arrive.shared::cta.b64 _, [%0];\n}\n" ::"r"(br) : "memory");
}
__device__ __forceinline__ bool mbar_try_wait(uint32_t br, uint32_t parity) {
  uint32_t ok;
  asm volatile("{\n.reg .pred p;\nmbarrier.try_wait.parity.shared::cta.b64 p, [%1], %2;\nselp.u32 %0, 1, 0, p;\n}\n" : "=r"(ok) : "r"(br), "r"(parity) : "memory");
  return ok;
}
__device__ __forceinline__ bool mbar_test_wait(uint32_t br, uint32_t parity) {
  uint32_t ok;
  asm volatile("{\n.reg .pred p;\nmbarrier.test_wait.parity.shared::cta.b64 p, [%1], %2;\nselp.u32 %0, 1, 0, p;\n}\n" : "=r"(ok) : "r"(br), "r"(parity) : "memory");
  return ok;
}
__device__ __forceinline__ void mbar_wait(uint32_t br, uint32_t parity) {
#pragma unroll 1
  for (int it = 0; it < MB_LIMIT; ++it) { if (mbar_try_wait(br, parity)) return; }
  __trap();
}
__device__ __forceinline__ bool elect_one() { uint32_t p; asm volatile("{\n.reg .pred P;\nelect.sync _|P, 0xffffffff;\nselp.u32 %0, 1, 0, P;\n}\n" : "=r"(p)); return p; }
__device__ __forceinline__ void fence_proxy_async_smem() { asm volatile("fence.proxy.async.shared::cta;" ::: "memory"); }
__device__ __forceinline__ void tma3d(uint32_t dst, const CUtensorMap* m, int c0, int c1, int c2, uint32_t br) {
  asm volatile("cp.async.bulk.tensor.3d.shared::cluster.global.mbarrier::complete_tx::bytes [%0], [%1, {%3, %4, %5}], [%2];" ::"r"(dst), "l"(m), "r"(br), "r"(c0), "r"(c1), "r"(c2) : "memory");
}
__device__ __forceinline__ void tma4d(uint32_t dst, const CUtensorMap* m, int c0, int c1, int c3, uint32_t br) {
  asm volatile("cp.async.bulk.tensor.4d.shared::cluster.global.mbarrier::complete_tx::bytes [%0], [%1, {%3, %4, %6, %5}], [%2];" ::"r"(dst), "l"(m), "r"(br), "r"(c0), "r"(c1), "r"(c3), "r"(0) : "memory");
}
__device__ __forceinline__ void tma3d_store(const CUtensorMap* m, uint32_t src, int c0, int c1, int c2) {
  asm volatile("cp.async.bulk.tensor.3d.global.shared::cta.bulk_group [%0, {%2, %3, %4}], [%1];" ::"l"(m), "r"(src), "r"(c0), "r"(c1), "r"(c2) : "memory");
}
__device__ __forceinline__ void stsm4(uint32_t a, uint32_t x, uint32_t y, uint32_t z, uint32_t w) {
  asm volatile("stmatrix.sync.aligned.m8n8.x4.shared.b16 [%0], {%1,%2,%3,%4};" ::"r"(a), "r"(x), "r"(y), "r"(z), "r"(w) : "memory");
}
__device__ __forceinline__ void ldsm4(uint32_t a, uint32_t& x, uint32_t& y, uint32_t& z, uint32_t& w) {
  asm volatile("ldmatrix.sync.aligned.m8n8.x4.shared.b16 {%0,%1,%2,%3}, [%4];" : "=r"(x), "=r"(y), "=r"(z), "=r"(w) : "r"(a) : "memory");
}
__device__ __forceinline__ void st_tag(uint4* p, uint32_t a, uint32_t b, uint32_t c, uint32_t tag) {
  asm volatile("{\n.reg .b64 x, y;\n.reg .b128 z;\nmov.b64 x, {%1, %2};\nmov.b64 y, {%3, %4};\nmov.b128 z, {x, y};\nst.relaxed.gpu.global.b128 [%0], z;\n}\n" ::"l"(p), "r"(a), "r"(b), "r"(c), "r"(tag) : "memory");
}
__device__ __forceinline__ uint4 ld_tag(const uint4* p) {
  uint4 v;
  asm volatile("{\n.reg .b64 x, y;\n.reg .b128 z;\nld.relaxed.gpu.global.b128 z, [%4];\nmov.b128 {x, y}, z;\nmov.b64 {%0, %1}, x;\nmov.b64 {%2, %3}, y;\n}\n" : "=r"(v.x), "=r"(v.y), "=r"(v.z), "=r"(v.w) : "l"(p) : "memory");
  return v;
}
template <int NAP, int N> __device__ __forceinline__ void ld_tag_wait(uint4 (&v)[N], const uint4* p, uint32_t tag) {
#pragma unroll 1
  for (int it = 0; it < FL_LIMIT; ++it) {
    uint32_t bad = 0;
#pragma unroll
    for (int j = 0; j < N; j++) v[j] = ld_tag(p + j * 32);
#pragma unroll
    for (int j = 0; j < N; j++) bad |= v[j].w ^ tag;
    if (__all_sync(0xffffffffu, bad == 0)) return;
    if (NAP) __nanosleep(NAP);
  }
  __trap();
}
__device__ __forceinline__ void prefetch_tmap(const CUtensorMap* m) { asm volatile("prefetch.tensormap [%0];" ::"l"(m) : "memory"); }
__device__ __forceinline__ void wgmma_fence() { asm volatile("wgmma.fence.sync.aligned;" ::: "memory"); }
__device__ __forceinline__ void wgmma_commit() { asm volatile("wgmma.commit_group.sync.aligned;" ::: "memory"); }
template <int N> __device__ __forceinline__ void wgmma_wait() { asm volatile("wgmma.wait_group.sync.aligned %0;" ::"n"(N) : "memory"); }
template <int R> __device__ __forceinline__ void reg_alloc() { asm volatile("setmaxnreg.inc.sync.aligned.u32 %0;" ::"n"(R)); }
template <int R> __device__ __forceinline__ void reg_dealloc() { asm volatile("setmaxnreg.dec.sync.aligned.u32 %0;" ::"n"(R)); }
__device__ __forceinline__ void bar_sync(int id, int n) { asm volatile("bar.sync %0, %1;" ::"r"(id), "r"(n) : "memory"); }
__device__ __forceinline__ void bar_arrive(int id, int n) { asm volatile("bar.arrive %0, %1;" ::"r"(id), "r"(n) : "memory"); }
__device__ __forceinline__ uint32_t ld_acquire(const uint32_t* p) { uint32_t v; asm volatile("ld.acquire.gpu.global.u32 %0, [%1];" : "=r"(v) : "l"(p) : "memory"); return v; }
__device__ __forceinline__ void st_release(uint32_t* p, uint32_t v) { asm volatile("st.release.gpu.global.u32 [%0], %1;" ::"l"(p), "r"(v) : "memory"); }
__device__ __forceinline__ uint4 ldcg16(const void* p) { uint4 v; asm volatile("ld.global.cg.v4.u32 {%0,%1,%2,%3}, [%4];" : "=r"(v.x), "=r"(v.y), "=r"(v.z), "=r"(v.w) : "l"(p) : "memory"); return v; }
__device__ __forceinline__ float ldcgf(const void* p) { float v; asm volatile("ld.global.cg.f32 %0, [%1];" : "=f"(v) : "l"(p) : "memory"); return v; }
__device__ __forceinline__ float2 lds8f(uint32_t a) { float2 v; asm volatile("ld.shared.v2.f32 {%0,%1}, [%2];" : "=f"(v.x), "=f"(v.y) : "r"(a)); return v; }
__device__ __forceinline__ float lds4f(uint32_t a) { float v; asm volatile("ld.shared.f32 %0, [%1];" : "=f"(v) : "r"(a)); return v; }
__device__ __forceinline__ uint32_t lds4(uint32_t a) { uint32_t v; asm volatile("ld.shared.u32 %0, [%1];" : "=r"(v) : "r"(a) : "memory"); return v; }
__device__ __forceinline__ void lds16f(uint32_t a, float& x, float& y, float& z, float& w) { asm volatile("ld.shared.v4.f32 {%0,%1,%2,%3}, [%4];" : "=f"(x), "=f"(y), "=f"(z), "=f"(w) : "r"(a) : "memory"); }
__device__ __forceinline__ void sts8f(uint32_t a, float x, float y) { asm volatile("st.shared.v2.f32 [%0], {%1,%2};" ::"r"(a), "f"(x), "f"(y) : "memory"); }
__device__ __forceinline__ void sts4f(uint32_t a, float x) { asm volatile("st.shared.f32 [%0], %1;" ::"r"(a), "f"(x) : "memory"); }
__device__ __forceinline__ void sts16(uint32_t a, uint32_t x, uint32_t y, uint32_t z, uint32_t w) { asm volatile("st.shared.v4.u32 [%0], {%1,%2,%3,%4};" ::"r"(a), "r"(x), "r"(y), "r"(z), "r"(w) : "memory"); }
__device__ __forceinline__ void lds16(uint32_t a, uint32_t& x, uint32_t& y, uint32_t& z, uint32_t& w) { asm volatile("ld.shared.v4.u32 {%0,%1,%2,%3}, [%4];" : "=r"(x), "=r"(y), "=r"(z), "=r"(w) : "r"(a) : "memory"); }
__device__ __forceinline__ uint32_t pack_bf16(float a, float b) { uint32_t r; asm("cvt.rn.bf16x2.f32 %0, %1, %2;" : "=r"(r) : "f"(b), "f"(a)); return r; }
__device__ __forceinline__ uint32_t pack_bf16_v(float a, float b) { uint32_t r; asm volatile("cvt.rn.bf16x2.f32 %0, %1, %2;" : "=r"(r) : "f"(b), "f"(a)); return r; }
__device__ __forceinline__ float bf_lo(uint32_t v) { return __uint_as_float(v << 16); }
__device__ __forceinline__ float bf_hi(uint32_t v) { return __uint_as_float(v & 0xffff0000u); }
constexpr float LOG2E = 1.4426950408889634f;
__device__ __forceinline__ float ex2f(float x) { float y; asm("ex2.approx.ftz.f32 %0, %1;" : "=f"(y) : "f"(x)); return y; }
__device__ __forceinline__ float tanhf_(float x) { float y; asm("tanh.approx.f32 %0, %1;" : "=f"(y) : "f"(x)); return y; }
__device__ __forceinline__ float rcpf(float x) { float y; asm("rcp.approx.ftz.f32 %0, %1;" : "=f"(y) : "f"(x)); return y; }
__device__ __forceinline__ float bf_round(float a) { return bf_lo(pack_bf16(a, 0.f)); }
__device__ __forceinline__ uint32_t movmat(uint32_t a) { uint32_t d; asm volatile("movmatrix.sync.aligned.m8n8.trans.b16 %0, %1;" : "=r"(d) : "r"(a)); return d; }
__device__ __forceinline__ void mma16816(float& d0, float& d1, float& d2, float& d3, uint32_t a0, uint32_t a1, uint32_t a2, uint32_t a3, uint32_t b0, uint32_t b1,
                                         float c0, float c1, float c2, float c3) {
  asm volatile("mma.sync.aligned.m16n8k16.row.col.f32.bf16.bf16.f32 {%0,%1,%2,%3}, {%4,%5,%6,%7}, {%8,%9}, {%10,%11,%12,%13};"
               : "=f"(d0), "=f"(d1), "=f"(d2), "=f"(d3) : "r"(a0), "r"(a1), "r"(a2), "r"(a3), "r"(b0), "r"(b1), "f"(c0), "f"(c1), "f"(c2), "f"(c3));
}
template <int N> __device__ __forceinline__ void copy_out(uint32_t a, char* g, int pitch, int lane) {
  a += (lane >> 3) * 128 + (((lane ^ (lane >> 3)) & 7) << 4);
  g += (lane >> 3) * pitch + (lane & 7) * 16;
  uint32_t v[N][4];
  __syncwarp();
#pragma unroll
  for (int j = 0; j < N; j++) lds16((a ^ ((j & 1) * 64)) + j * 512, v[j][0], v[j][1], v[j][2], v[j][3]);
#pragma unroll
  for (int j = 0; j < N; j++) asm volatile("st.global.v4.u32 [%0], {%1, %2, %3, %4};" ::"l"(g + j * 4 * pitch), "r"(v[j][0]), "r"(v[j][1]), "r"(v[j][2]), "r"(v[j][3]) : "memory");
}
__device__ __forceinline__ int lane_now() { int v; asm volatile("mov.u32 %0, %%laneid;" : "=r"(v)); return v; }
__device__ __forceinline__ uint32_t uni(uint32_t x, int lane) { return __shfl_sync(0xffffffffu, x + lane, 0); }
__device__ __forceinline__ uint64_t dsc(uint32_t hi, uint32_t lo) { return ((uint64_t)hi << 32) | lo; }

#define R8(a, o) "+f"(a[o]), "+f"(a[o + 1]), "+f"(a[o + 2]), "+f"(a[o + 3]), "+f"(a[o + 4]), "+f"(a[o + 5]), "+f"(a[o + 6]), "+f"(a[o + 7])
#define R32(a, o) R8(a, o), R8(a, o + 8), R8(a, o + 16), R8(a, o + 24)
#define REG64 "%0, %1, %2, %3, %4, %5, %6, %7, %8, %9, %10, %11, %12, %13, %14, %15, %16, %17, %18, %19, %20, %21, %22, %23, %24, %25, %26, %27, %28, %29, %30, %31, " \
              "%32, %33, %34, %35, %36, %37, %38, %39, %40, %41, %42, %43, %44, %45, %46, %47, %48, %49, %50, %51, %52, %53, %54, %55, %56, %57, %58, %59, %60, %61, %62, %63"
#define REG96 REG64 ", %64, %65, %66, %67, %68, %69, %70, %71, %72, %73, %74, %75, %76, %77, %78, %79, %80, %81, %82, %83, %84, %85, %86, %87, %88, %89, %90, %91, %92, %93, %94, %95"
__device__ __forceinline__ void wgmma(float (&d)[64], uint64_t da, uint64_t db) {
  asm volatile("wgmma.mma_async.sync.aligned.m64n128k16.f32.bf16.bf16 {" REG64 "}, %64, %65, 1, 1, 1, 0, 1;\n"
               : R32(d, 0), R32(d, 32) : "l"(da), "l"(db));
}
__device__ __forceinline__ void wgmma(float (&d)[96], uint64_t da, uint64_t db) {
  asm volatile("wgmma.mma_async.sync.aligned.m64n192k16.f32.bf16.bf16 {" REG96 "}, %96, %97, 1, 1, 1, 0, 1;\n"
               : R32(d, 0), R32(d, 32), R32(d, 64) : "l"(da), "l"(db));
}
#define W8(a, o) "=f"(a[o]), "=f"(a[o + 1]), "=f"(a[o + 2]), "=f"(a[o + 3]), "=f"(a[o + 4]), "=f"(a[o + 5]), "=f"(a[o + 6]), "=f"(a[o + 7])
#define W32(a, o) W8(a, o), W8(a, o + 8), W8(a, o + 16), W8(a, o + 24)
__device__ __forceinline__ void wgmma_z(float (&d)[64], uint64_t da, uint64_t db) {
  asm volatile("wgmma.mma_async.sync.aligned.m64n128k16.f32.bf16.bf16 {" REG64 "}, %64, %65, 0, 1, 1, 0, 1;\n"
               : W32(d, 0), W32(d, 32) : "l"(da), "l"(db));
}
__device__ __forceinline__ void wgmma_z(float (&d)[96], uint64_t da, uint64_t db) {
  asm volatile("wgmma.mma_async.sync.aligned.m64n192k16.f32.bf16.bf16 {" REG96 "}, %96, %97, 0, 1, 1, 0, 1;\n"
               : W32(d, 0), W32(d, 32), W32(d, 64) : "l"(da), "l"(db));
}

__device__ __forceinline__ void wgmma_cs(float (&d)[4], uint64_t da, uint64_t db) {
  asm volatile("wgmma.mma_async.sync.aligned.m64n8k16.f32.bf16.bf16 {%0, %1, %2, %3}, %4, %5, 1, 1, 1, 1, 0;\n" : "+f"(d[0]), "+f"(d[1]), "+f"(d[2]), "+f"(d[3]) : "l"(da), "l"(db));
}
__device__ __forceinline__ void bulk_commit() { asm volatile("cp.async.bulk.commit_group;" ::: "memory"); }
__device__ __forceinline__ void bulk_wait() { asm volatile("cp.async.bulk.wait_group 0;" ::: "memory"); }
__device__ __forceinline__ void fence_bar_init() { asm volatile("fence.mbarrier_init.release.cluster;" ::: "memory"); }
__device__ __forceinline__ void prefetch_l2(const void* p) { asm volatile("prefetch.global.L2 [%0];" ::"l"(p) : "memory"); }

__device__ __forceinline__ uint32_t clock_now() { uint32_t v; asm volatile("mov.u32 %0, %%clock;" : "=r"(v)); return v; }
__device__ __forceinline__ void delay_until(uint32_t t0, int cycles) {
#pragma unroll 1
  for (int it = 0; it < 1000 && (int)(clock_now() - t0) < cycles; it++) __nanosleep(40);
}
__device__ __forceinline__ uint32_t ld_epoch(int b) { uint32_t v; asm volatile("ld.global.u32 %0, [%1];" : "=r"(v) : "l"(g_epoch + b) : "memory"); return v + 1; }
__device__ __forceinline__ void wait_flags(const uint32_t* f, uint32_t tag) {
#pragma unroll 1
  for (int it = 0; it < FL_LIMIT; ++it) if (__all_sync(0xffffffffu, (int)(ld_acquire(f) - tag) >= 0)) return;
  __trap();
}

__device__ __forceinline__ float2 ln_finish(float sum, float sq) {
  const float mean = sum * (1.f / D_), var = fmaxf(fmaf(-mean, mean, sq * (1.f / D_)), 0.f);
  const float mb = bf_round(mean);
  const float vb = bf_round(var);
  const float sd = bf_round(sqrtf(bf_round(vb + 1e-5f)));
  return make_float2(1.0f / sd, -mb);
}

__device__ __forceinline__ void helper_cta(const Params& P, int e, int wg, int w) {
  const int tid = threadIdx.x;
  if (tid == 0) {
#pragma unroll
    for (int i = 0; i < 16; i++) mbar_init(bar(i), 1);
    fence_bar_init();
  }
  if (tid < 64) sts16(SM_STAT + tid * 16, 0x3f803f80u, 0x3f803f80u, 0x3f803f80u, 0x3f803f80u);
  fence_proxy_async_smem();
  __syncthreads();
  if (wg == 2) {
    if (w == 0) {
#pragma unroll 1
      for (int n = 0; n < 9 * 32; n++) {
        const int job = n >> 5;
        const uint32_t fb = bar(n & 7), dst = SB + (n & 7) * 24576;
        mbar_wait(bar(8 + (n & 7)), (n >> 3) + 1);
        if (elect_one()) {
          mbar_expect_tx(fb, job < 2 ? 24576 : 16384);
          tma4d(dst, &P.tm[job < 2 ? M_WQKV : M_W13], (e * 2 + (n & 1)) * 64, (n & 30) * 32, job < 2 ? job : job - 2, fb);
        }
        __syncwarp();
      }
    }
  } else {
    const uint32_t tag = ld_epoch(NCTA + e);
    const int lane = tid & 31;
#pragma unroll 1
    for (int job = 0; job < 9; job++) {
      float s[3][4] = {};
#pragma unroll 1
      for (int n = job * 32 + wg; n < job * 32 + 32; n += 2) {
        mbar_wait(bar(n & 7), n >> 3);
        wgmma_fence();
        const uint32_t a = ((SB + (n & 7) * 24576) >> 4) + 0x2000000;
#pragma unroll
        for (int k = 0; k < 8; k++) wgmma_cs(s[k & 1], dsc(0x40000040u, a + (k & 1) * 512 + (k >> 1) * 128), dsc(0x40000040u, (SM_STAT >> 4) + 0x10000));
        if (job < 2) {
          wgmma_fence();
#pragma unroll
          for (int k = 0; k < 4; k++) wgmma_cs(s[2], dsc(0x40000040u, a + 1024 + k * 128), dsc(0x40000040u, (SM_STAT >> 4) + 0x10000));
        }
        wgmma_commit();
        wgmma_wait<0>();
        mbar_arrive_if(bar(8 + (n & 7)), (tid & 127) == 0);
      }
      if (!(lane & 2))
        st_tag(&g_cs[job][e * 2 + wg][w * 16 + (lane & 1) * 8 + (lane >> 2)], __float_as_uint(lane & 1 ? s[0][2] : s[0][0]), __float_as_uint(lane & 1 ? s[1][2] : s[1][0]),
               __float_as_uint(lane & 1 ? s[2][2] : s[2][0]), tag);
      __syncwarp();
    }
    bar_sync(NB_INIT, 256);
    if (tid == 0) g_epoch[NCTA + e] = tag;
  }
}

template <bool WEIGHTS>
__device__ __forceinline__ void producer(const Params& P, const uint2* tab, int nop, int lane, int c, int row, int par, uint32_t t_entry) {
  uint64_t pol;
  asm volatile("createpolicy.fractional.L2::evict_first.b64 %0, 1.0;" : "=l"(pol));
  uint2 nx, n2;
#pragma unroll 1
  for (int j = 0; j < FIRST; j++) {
    if (j >= ST_N0) delay_until(t_entry, ST_T1 + (j - ST_N0) * ST_D1);
    if (elect_one()) {
      mbar_expect_tx(bar(B_FULL) + 8 * j, WEIGHTS ? 24576 : 16384);
      if (WEIGHTS) tma4d(SB + j * 40960 + 16384, &P.tm[M_WQKV], c * 64, j * 64, 0, bar(B_FULL) + 8 * j);
      else tma3d(SB + j * 40960, &P.tm[M_X0], j * 64, row, par, bar(B_FULL) + 8 * j);
    }
    __syncwarp();
    if (j == ST_N0 - 1) {
      if (!WEIGHTS) TLW(0, 1);
      nx = __ldg(tab + lane); n2 = __ldg(tab + 32 + lane);
      __syncthreads();
    }
  }
  if (!WEIGHTS && lane == 0) {
#pragma unroll
    for (int j = 0; j < FIRST; j++) mbar_arrive(bar(B_EMPTY + 2 + j));
  }
  __syncwarp();
  auto word = [&](uint2 e) { return e.x + (((int)(e.y & 7) > c) + (e.y & 8 ? c : 0)) * 8192; };
  uint32_t xn = __shfl_sync(0xffffffffu, word(nx), 0);
#pragma unroll 1
  for (int base = 0; base < nop; base += 32) {
    const uint2 e = nx;
    nx = n2;
    n2 = __ldg(tab + base + 64 + lane);
    const uint32_t xw = word(e), bytes = e.y & 0xe000;
    const int arr = e.y & 16 ? lane : -1, solo = e.y & 32 ? lane : -1;
#pragma unroll PUNR
    for (int j = 0; j < 32; j++) {
      const uint32_t x = xn;
      xn = __shfl_sync(0xffffffffu, j < 31 ? xw : word(nx), j + 1);
      const uint32_t dst = SB + (x & 31) * 8192, i8 = (x >> 2) & 0x78, wb = BARS + ((x >> 20) & 0x3f8);
      const int kc = (x >> 7) & 0xfc0, wv = (x >> 19) & 7;
      const CUtensorMap* mp = reinterpret_cast<const CUtensorMap*>(reinterpret_cast<const char*>(P.tm) + ((x >> 2) & 0x780));
#define OP_HEAD "{\n.reg .pred pe, pa, pl, pg, ps, pw;\n.reg .u32 it;\n" \
                "elect.sync _|pe, 0xffffffff;\nsetp.eq.u32 pa, %0, %1;\nsetp.ne.and.u32 pl, %2, 0, pe;\n"
#define OP_WAIT "mov.u32 it, 0;\n" \
                "WAIT_%=:\n" \
                "mbarrier.try_wait.parity.shared::cta.b64 pw, [%3], %4;\n" \
                "@pw bra.uni GO_%=;\n" \
                "add.u32 it, it, 1;\nsetp.lt.u32 pw, it, 0x10000;\n" \
                "@pw bra.uni WAIT_%=;\n" \
                "trap;\n" \
                "GO_%=:\n"
      if (WEIGHTS)
        asm volatile(OP_HEAD OP_WAIT
                     "@pl cp.async.bulk.tensor.4d.shared::cluster.global.mbarrier::complete_tx::bytes.L2::cache_hint [%7], [%8, {%9, %10, %11, %12}], [%5], %13;\n"
                     "@pa mbarrier.arrive.expect_tx.shared::cta.b64 _, [%5], %6;\n"
                     "}\n" ::"r"(arr), "r"(j), "r"(x & (1 << 22)), "r"(wb), "r"(x >> 31), "r"(bar(B_FULL) + i8), "r"(bytes), "r"(dst), "l"(mp), "r"(c * 64), "r"(kc), "r"(0), "r"(wv),
                     "l"(pol) : "memory");
      else
        asm volatile(OP_HEAD "setp.ne.u32 pg, %12, 0;\nsetp.eq.u32 ps, %13, %1;\n" OP_WAIT
                     "@pl cp.async.bulk.tensor.3d.shared::cluster.global.mbarrier::complete_tx::bytes [%7], [%8, {%9, %10, %11}], [%5];\n"
                     "@pg fence.proxy.async.shared::cta;\n"
                     "@pa mbarrier.arrive.expect_tx.shared::cta.b64 _, [%5], %6;\n"
                     "@ps mbarrier.arrive.shared::cta.b64 _, [%14];\n"
                     "}\n" ::"r"(arr), "r"(j), "r"(x & (1 << 22)), "r"(wb), "r"(x >> 31), "r"(x & (1 << 30) ? bar(B_RES) : bar(B_FULL) + i8), "r"(bytes), "r"(dst), "l"(mp), "r"(kc), "r"(row), "r"(par), "r"(wv),
                     "r"(solo), "r"(bar(B_EMPTY) + ((i8 + 16) & 0x78)) : "memory");
    }
  }
}

template <int N, uint32_t LO> __device__ __forceinline__ void advance(uint32_t& x, uint32_t inc) {
  constexpr uint32_t LEN = (N == 192 ? NU : 24) * 512;
  x += inc; if (x >= LO + LEN) x -= LEN;
}
__device__ __forceinline__ bool full_test(uint32_t i8) {
  uint32_t ok;
  asm volatile("{\n.reg .pred p;\nmbarrier.test_wait.parity.shared::cta.b64 p, [%1 + %3], %2;\nselp.u32 %0, 1, 0, p;\n}\n" : "=r"(ok) : "r"(i8 & 0x78), "r"(i8 >> 7), "n"(bar(B_FULL)) : "memory");
  return ok;
}
__device__ __forceinline__ void full_wait(uint32_t i8) { mbar_wait(bar(B_FULL) + (i8 & 0x78), i8 >> 7); }
__device__ __forceinline__ void release(uint32_t i8, uint32_t p) {
  asm volatile("{\n.reg .pred q;\nsetp.ne.u32 q, %1, 0;\n@q mbarrier.arrive.shared::cta.b64 _, [%0 + %2];\n}\n" ::"r"(i8 & 0x78), "r"(p), "n"(bar(B_EMPTY)) : "memory");
}
template <int N, int RELK, int FIRSTK>
__device__ __forceinline__ bool kstep(float (&acc)[2][N / 2], uint32_t hiA, uint32_t hiB, uint32_t& a, uint32_t& b, uint32_t inc, uint32_t& i8, uint32_t x) {
  constexpr uint32_t MI = N == 192 ? 64 : 512;
  wgmma_fence();
  if (FIRSTK == 2) { wgmma_z(acc[0], dsc(hiA, a), dsc(hiB, b)); wgmma_z(acc[1], dsc(hiA, a + MI), dsc(hiB, b)); }
  else { wgmma(acc[0], dsc(hiA, a), dsc(hiB, b)); wgmma(acc[1], dsc(hiA, a + MI), dsc(hiB, b)); }
  i8 += 8;
  const bool ok = full_test(i8);
#pragma unroll
  for (int k = 1; k < 4; k++) {
    wgmma(acc[0], dsc(hiA, a + 2 * k), dsc(hiB, b + 128 * k)); wgmma(acc[1], dsc(hiA, a + MI + 2 * k), dsc(hiB, b + 128 * k));
    if (k == RELK || k == 3) wgmma_commit();
    if (k == 3) { advance<N, LO_A>(a, inc); advance<N, LO_B>(b, inc); }
    if (!FIRSTK && k == RELK) {
      wgmma_wait<1>();
      release(i8, x);
    }
  }
  return ok;
}
template <int MODE, int N, class F, class G>
__device__ __forceinline__ void mainloop(float (&acc)[2][N], uint32_t sig, int t, int wg, F&& prepare, G&& first_half) {
  uint32_t sp = c_sched.task[t].seg;
  const uint32_t turn = bar(B_TURN) + 8 * (wg ^ 1);
  const uint32_t hiA = uni(MODE == 0 ? 0x40000080u : 0x40000040u, lane_now()), hiB = uni(0x40000040u, lane_now() * 2);
  uint32_t i8 = c_sched.seg[sp].i8 & 0xffff, nxt = c_sched.seg[sp].end8 & 0xffff, a = c_sched.seg[sp].a, b = c_sched.seg[sp].b;
  uint32_t inc = MODE == 0 ? 2560 : MODE == 2 ? 2048 : c_sched.seg[sp].end8 >> 16;
  full_wait(i8);
  TL(t, 2);
  TS(i8, wg);
  bool ok = kstep<N * 2, 3, MODE == 2 ? 1 : 2>(acc, hiA, hiB, a, b, inc, i8, 0);
  if (MODE == 2 && (t == 2 || t == 13)) bar_sync(NB_OGO, 256);
#pragma unroll 1
  while (true) {
    uint32_t act;
#pragma unroll 1
    while (true) {
      if (!ok) full_wait(i8);
      TS(i8, wg);
      ok = kstep<N * 2, MODE == 0 ? RELQ : MODE == 1 ? RELG : RELD, 0>(acc, hiA, hiB, a, b, inc, i8, sig);
      if (__builtin_expect(i8 == nxt, 0)) {
        act = c_sched.seg[sp++].i8 >> 16;
        if (MODE == 1) mbar_arrive_if(turn, sig & (act >> 1));
        if (act & (MODE == 0 ? A_END | A_DRAIN | A_SYNC : MODE == 1 ? A_END | A_DRAIN : A_END)) break;
        if (MODE == 2 && O_NW && (act & A_SYNC)) bar_sync(NB_OGO + (act >> 8), 256);
        nxt = c_sched.seg[sp].end8 & 0xffff; a = c_sched.seg[sp].a; b = c_sched.seg[sp].b;
        if (MODE == 1) inc = c_sched.seg[sp].end8 >> 16;
      }
    }
    if (MODE == 2 || (act & A_END)) break;
    nxt = c_sched.seg[sp].end8 & 0xffff; a = c_sched.seg[sp].a; b = c_sched.seg[sp].b;
    if (MODE == 1) inc = c_sched.seg[sp].end8 >> 16;
    if (PXE && MODE == 0 && (act & A_SYNC)) bar_arrive(NB_PX, 256);
    wgmma_wait<0>();
    if (!PXE && MODE == 0 && (act & A_SYNC)) bar_arrive(NB_PX, 256);
    release(i8 + 8, sig);
    i8 = c_sched.seg[sp].i8 & 0xffff;
    if (MODE == 1 || (act & A_WAIT)) mbar_wait(bar(B_TURN) + 8 * wg, (t - 1) >> 1);
    full_wait(i8);
    if (MODE == 0 && (act & A_SYNC)) bar_sync(NB_PY, 256);
    TS(i8, wg);
    ok = kstep<N * 2, 3, 1>(acc, hiA, hiB, a, b, inc, i8, 0);
  }
  if (MODE != 1) {
    constexpr int TL_ = MODE == 0 ? TAILQ : TAIL;
    uint32_t ta[TL_], tb[TL_];
#pragma unroll
    for (int x = 0; x < TL_; x++) {
      full_wait(i8 + 8 * x);
      TS(i8 + 8 * x, wg);
      ta[x] = a; tb[x] = b;
      advance<N * 2, LO_A>(a, inc); advance<N * 2, LO_B>(b, inc);
    }
    mbar_arrive_if(turn, sig);
#pragma unroll
    for (int h = 0; h < 2; h++) {
      const int mi = MODE == 0 ? 1 - h : h;
      wgmma_fence();
#pragma unroll
      for (int x = 0; x < TL_; x++)
#pragma unroll
        for (int k = 0; k < 4; k++) wgmma(acc[mi], dsc(hiA, ta[x] + mi * (MODE == 0 ? 64 : 512) + 2 * k), dsc(hiB, tb[x] + 128 * k));
      wgmma_commit();
      if (TL_ > 1 && h == 0) { wgmma_wait<1>(); release(i8 + 8, sig); }
    }
    if (TL_ == 1) { wgmma_wait<2>(); release(i8 + 8, sig); }
    prepare();
    wgmma_wait<1>();
    first_half();
    wgmma_wait<0>();
#pragma unroll
    for (int x = 0; x < TL_; x++) release(i8 + 16 + 8 * x, sig);
  } else {
    prepare();
    wgmma_wait<0>();
    release(i8 + 8, sig);
  }
}

template <int SWAP>
__global__ void __launch_bounds__(384, 1) fused_kernel(const __grid_constant__ Params P) {
  extern __shared__ __align__(1024) uint8_t smem_raw[];
  const int tid = threadIdx.x;
  if (PF0 && (tid & 127) == 0) prefetch_tmap(&P.tm[tid ? M_WQKV : M_X0]);
  const int wg = __shfl_sync(0xffffffffu, tid >> 7, 0);
  const int w = __shfl_sync(0xffffffffu, (tid >> 5) & 3, 0);
  const int lane = tid & 31;
  const uint32_t t_entry = clock_now();
  int b = blockIdx.x, c = ((b >> 2) & 7) ^ (((b >> 5) & 1) * 7), mr = b & 3;
  if (P.by_sm) {
    uint32_t smid; asm volatile("mov.u32 %0, %%smid;" : "=r"(smid));
    const int tp = smid >> 1;
    b = (tp < 32 ? (tp & 7) * 8 + (tp >> 3) : tp < 60 ? (1 + (tp - 32) % 7) * 8 + 4 + (tp - 32) / 7 : tp < 62 ? tp + 4 : tp - 58) * 2 + (smid & 1);
    c = (b & 1) | ((b >> 1) & 2) | ((b >> 2) & 4); mr = ((b >> 1) & 1) | ((b >> 2) & 2);
  }
  const int mg = (b >> 5) & 3, m = mg * 4 + mr;
  const int row0 = (m & 7) * 128, par = m >> 3;
  if (__builtin_expect(b >= NCTA, 0)) { helper_cta(P, b - NCTA, wg, w); return; }

  if (__builtin_expect(wg == 2, 0)) {
    reg_dealloc<40>();
    if (w < 2) {
      if (tid == 256) {
#pragma unroll
        for (int x = 0; x < FIRST; x++) mbar_init(bar(B_FULL + x), 2);
        fence_bar_init();
        fence_proxy_async_smem();
      }
      bar_sync(NB_INIT, 64);
      if (w == 0) producer<false>(P, g_ops.a, NOP0, lane, c, row0, par, t_entry);
      else producer<true>(P, g_ops.b, NOP1, lane, c, row0, par, t_entry);
    } else if (w == 2) {
      if (smem_u32(smem_raw) != SB) __trap();
      if (lane == 0) {
#pragma unroll
        for (int x = FIRST; x < B_CS; x++) mbar_init(bar(x), x < B_SIG ? 2 : x <= B_STAT ? 4 : 1);
        fence_bar_init();
        fence_proxy_async_smem();
      }
      __syncthreads();
      const uint32_t tag = ld_epoch(b);
      uint32_t* const flag = g_flags[m * 8 + c];
      if (lane < 4) asm volatile("st.relaxed.gpu.global.v4.u32 [%0], {%1, %1, %1, %1};" ::"l"(flag + lane * 4), "r"(tag * 32 - 1) : "memory");
      __syncwarp();
      int ev = 0;
      uint32_t t_st = t_entry;
#pragma unroll 1
      for (int t = 0; t < 21; t++) {
        const int i = t >= 11 ? t - 11 : t;
        const bool od = i == 2 || i == 10;
        const uint32_t sig = c_sched.task[t].sig;
        const uint32_t pf = i == 0 ? 1 << M_OL | 1 << M_O | 1 << M_WO : i == 1 ? 1 << M_W13 | 1 << M_W13P | 1 << M_YL | 1 << M_Y : i == 3 ? 1 << M_HL :
                            i == 7 ? 1 << M_H | 1 << M_W2 : i == 10 ? 1 << M_WQKV | 1 << M_YL | 1 << M_Y : 0;
        if ((pf >> lane) & 1) prefetch_tmap(&P.tm[lane]);
        __syncwarp();
#pragma unroll 1
        for (int x = i == 1 || od ? 0 : 1; x < (i == 1 ? 1 : 2); x++) {
          if (x == 0) mbar_wait(bar(B_SIG + 1), sig >> 1);
          else {
            const CUtensorMap* mp = &P.tm[i == 0 ? M_OL : od ? M_YL : M_HL];
            const uint32_t src = od ? SB + ((c_sched.task[t].stg >> 8) & 31) * 8192 : SM_STG;
            const int col = ((od ? 1 : i ? i - 3 : 0) * 8 + c) * 64, gap = i == 0 ? GAP_O : od ? GAP_Y : i == 9 ? GAP_H6 : GAP_H;
#pragma unroll 1
            for (int r = 0; r < 128; r += PROWS) {
              if (r == 0 || (r == 64 && i && !od)) {
                const int s = od ? 3 : i ? r >> 6 : 1;
                mbar_wait(bar(B_SIG) + 8 * s, sig >> s);
                if ((HOLD & 16) && od) mbar_wait(bar(B_DEP - 1) + 8 * ev, 0);
                fence_proxy_async_smem();
              }
              delay_until(t_st, gap);
              t_st = clock_now();
              if (elect_one()) tma3d_store(mp, src + r * 128, col, row0 + r, par);
              __syncwarp();
            }
          }
          if (elect_one()) {
            if (x) { bulk_commit(); bulk_wait(); }
            if (x || !od) mbar_arrive(od ? bar(B_SF) : bar(B_FREE));
            if (i < 3 || i > 6) {
              asm volatile("fence.proxy.async.global;" ::: "memory");
              st_release(flag, tag * 32 + ev); mbar_arrive(bar(B_PUB) + 8 * ev);
            }
          }
          __syncwarp();
          if (i < 3 || i > 6) ev++;
          if (x == 0 || !od) TLW(t, 4);
        }
      }
      if (lane == 0) g_epoch[b] = tag;
    } else {
      if (lane == 0) {
#pragma unroll
        for (int x = B_CS; x < B_N; x++) mbar_init(bar(x), x == B_RF ? 4 : 1);
        fence_bar_init();
      }
      __syncthreads();
      const uint32_t tag = ld_epoch(b);
      delay_until(t_entry, WARM_T);
      asm volatile("st.shared.u32 [%0], %1;" ::"r"(SM_TAG + 4), "r"(reinterpret_cast<const uint32_t*>(&c_sched)[min(lane * 16, (int)sizeof(Sched) / 4 - 1)]) : "memory");
      int ncs = 0;
#pragma unroll 1
      for (int it = 0; it < 20; it++) {
        const int l = it >= 11, i = it - l * 11, e = i < 2 ? 0 : i - 2, ev = l * E_N + e;
#pragma unroll 1
        for (; ncs < (it < 2 ? it + 1 : it < 6 ? 2 : 9); ncs++) {
          uint4 v[2];
          ld_tag_wait<200>(v, &g_cs[ncs][c][lane], tag);
          const uint32_t a = SM_CS + (ncs < 2 ? ncs * 768 : 512 + ncs * 512) + lane * 4;
#pragma unroll
          for (int j = 0; j < 2; j++) {
            sts4f(a + j * 128, __uint_as_float(v[j].x)); sts4f(a + j * 128 + 256, __uint_as_float(v[j].y));
            if (ncs < 2) sts4f(a + j * 128 + 512, __uint_as_float(v[j].z));
          }
          mbar_arrive_warp(bar(B_CS) + 8 * ncs);
        }
        if (i == 0 || i == 2) {
          const int u = l * 2 + (i >> 1);
          uint4 v[6] = {};
          mbar_wait(bar(B_QT), u);
          if (m & 7) ld_tag_wait<0>(v, &g_halo[u][m - 1][c][0][lane], tag);
          const uint32_t xa = xch(i, 0) + lane * 16;
          sts16(xa, v[0].x, v[0].y, v[0].z, v[1].x); sts16(xa + 512, v[1].y, v[1].z, v[2].x, v[2].y);
          sts16(xa + 1024, v[2].z, v[3].x, v[3].y, v[3].z); sts16(xa + 1536, v[4].x, v[4].y, v[4].z, v[5].x);
          if (lane < 4) sts16(stat(l * 2) - 64 + lane * 16, v[5].y, 0, v[5].z, 0);
          mbar_arrive_warp(bar(B_XCH));
          continue;
        }
        mbar_wait(bar(B_PUB) + 8 * ev, 0);
        wait_flags(g_flags[(DEP32 >> e) & 1 ? mg * 32 + lane : m * 8 + (lane & 7)], tag * 32 + ev);
        mbar_arrive_warp(bar(B_DEP) + 8 * ev);
        if (e == E_YB || e == E_XB) {
          const int p = e == E_XB ? 1 : l * 2;
          if (elect_one()) {
            mbar_expect_tx(bar(B_SF + 1), 8192);
            asm volatile("cp.async.bulk.shared::cluster.global.mbarrier::complete_tx::bytes [%0], [%1], 8192, [%2];" ::"r"(SM_STG), "l"(&g_stat[p][m][0][0]), "r"(bar(B_SF + 1)) : "memory");
          }
          __syncwarp();
          mbar_wait(bar(B_SF + 1), p);
#pragma unroll 1
          for (int h = 0; h < 2; h++) {
            float s0 = 0.f, q0 = 0.f, s1 = 0.f, q1 = 0.f;
#pragma unroll 4
            for (int j = 0; j < 8; j++) {
              float x0, x1, x2, x3;
              lds16f(SM_STG + j * 1024 + h * 512 + lane * 16, x0, x1, x2, x3);
              s0 += x0; q0 += x1; s1 += x2; q1 += x3;
            }
            const float2 r0 = ln_finish(s0, q0), r1 = ln_finish(s1, q1);
            sts16(stat(p + 1) + (h * 64 + lane * 2) * 8, __float_as_uint(r0.x), __float_as_uint(r0.y), __float_as_uint(r1.x), __float_as_uint(r1.y));
          }
          mbar_arrive_warp(bar(B_STAT) + 8 * (p + 1));
        }
      }
    }
  } else {
    const int tw = tid & 127;
    if (wg == 0 && w < 2) asm volatile("st.shared.u32 [%0], %1;" ::"r"(SM_TAG + 4), "r"(reinterpret_cast<const uint32_t*>(&c_sched)[w ? offsetof(Sched, seg) / 4 : 0]) : "memory");
    reg_alloc<232>();
    uint32_t sig;
    asm volatile("mov.u32 %0, %1;" : "=r"(sig) : "r"((uint32_t)(tw == 0)));
    __syncthreads();

    if (wg == 1) {
      const uint32_t tag = ld_epoch(b);
      uint4* const mine = &g_stat0[m][c * 16 + w * 4 + (lane >> 3)];
      if (WARM_X && (lane & 7) == 0) st_tag(mine, 0, 0, 0, 0);
      __syncwarp();
      delay_until(t_entry, ST_ROWS);
      uint4 xv[16];
      const bf16* xr = P.x0 + (size_t)((row0 + c * 16 + w * 4 + (lane >> 3)) * 2 + par) * D_ + (lane & 7) * 8;
#pragma unroll
      for (int j = 0; j < 16; j++) xv[j] = ldcg16(xr + j * 64);
      float s[SCH] = {}, q[SCH] = {};
#pragma unroll
      for (int j = 0; j < 16; j++) {
        const uint32_t x[4] = {xv[j].x, xv[j].y, xv[j].z, xv[j].w};
#pragma unroll
        for (int e = 0; e < 8; e++) { const float d = e & 1 ? bf_hi(x[e >> 1]) : bf_lo(x[e >> 1]); s[e % SCH] += d; q[e % SCH] = fmaf(d, d, q[e % SCH]); }
      }
      if (SCH == 2) { s[0] += s[SCH - 1]; q[0] += q[SCH - 1]; }
#pragma unroll
      for (int o = 4; o > 0; o >>= 1) { s[0] += __shfl_xor_sync(0xffffffffu, s[0], o); q[0] += __shfl_xor_sync(0xffffffffu, q[0], o); }
      const float2 fin = ln_finish(s[0], q[0]);
      if ((lane & 7) == 0) st_tag(mine, __float_as_uint(fin.x), __float_as_uint(fin.y), 0, tag);
      __syncwarp();
      TL(22, 5);
      uint4 v[1];
      ld_tag_wait<200>(v, &g_stat0[m][tw], tag);
      sts8f(stat(0) + tw * 8, __uint_as_float(v[0].x), __uint_as_float(v[0].y));
      if (tw == 0) { asm volatile("st.shared.u32 [%0], %1;" ::"r"(SM_TAG), "r"(tag) : "memory"); sts16(SM_ZERO, 0, 0, 0, 0); }
      mbar_arrive_warp(bar(B_STAT));
      TL(22, 6);
    }

#pragma unroll 1
    for (int t = wg; t < 22; t += 2) {
      const int l = t >= 11, i = t - l * 11;
      if (t == 0) TL(t, 0);
      if (i < 2) {
        float acc[2][96];
        if (WARM_X && w == 3 && (m & 7) < 7) {
#pragma unroll
          for (int j = 0; j < 6; j++) st_tag(&g_halo[l * 2 + i][m][c][j][lane_now()], 0, 0, 0, 0);
        }
        if (t != 0 && t != 12) mbar_wait(bar(B_TURN) + 8 * wg, (t - 1) >> 1);
        uint32_t Q[4][8], K[4][8], V[4][8], sta, csa;
        float2 st[4];
        auto fix = [&](int g, int j, float2 cs) {
          const int mi = g & 1, half = g >> 1;
          return pack_bf16_v(fmaf(st[g].y, cs.x, acc[mi][j * 4 + half * 2]), fmaf(st[g].y, cs.y, acc[mi][j * 4 + half * 2 + 1]));
        };
        mainloop<0>(acc, sig, t, wg, [&]() {
          const int lane = lane_now();
          mbar_wait(bar(B_FREE), l * 9 + i - 1);
          mbar_wait(bar(B_STAT) + l * 16, 0);
          mbar_wait(bar(B_CS) + i * 8, 0);
          sta = stat(l * 2) + w * 256;
          csa = SM_CS + (i * 192 + 2 * (lane & 3)) * 4;
          st[1] = lds8f(sta + (8 + (lane >> 2)) * 8); st[3] = lds8f(sta + (24 + (lane >> 2)) * 8);
        }, [&]() {
          const int lane = lane_now();
          mbar_arrive_if(bar(B_QT), sig);
#pragma unroll
          for (int j = 0; j < 8; j++) { K[3][j] = fix(3, 8 + j, lds8f(csa + (8 + j) * 32)); V[3][j] = movmat(fix(3, 16 + j, lds8f(csa + (16 + j) * 32))); }
          if (w < 3) {
            const uint32_t xa = xch(i, w + 1) + lane * 16;
            sts16(xa, K[3][0], K[3][1], K[3][2], K[3][3]); sts16(xa + 512, K[3][4], K[3][5], K[3][6], K[3][7]);
            sts16(xa + 1024, V[3][0], V[3][1], V[3][2], V[3][3]); sts16(xa + 1536, V[3][4], V[3][5], V[3][6], V[3][7]);
            mbar_arrive_warp(bar(B_XCH));
          } else if ((m & 7) < 7) {
            const uint32_t tag = lds4(SM_TAG), r0 = lds4(sta + (24 + 2 * (lane & 3)) * 8), r1 = lds4(sta + (25 + 2 * (lane & 3)) * 8);
            uint4* const p = &g_halo[l * 2 + i][m][c][0][lane];
            st_tag(p, K[3][0], K[3][1], K[3][2], tag); st_tag(p + 32, K[3][3], K[3][4], K[3][5], tag); st_tag(p + 64, K[3][6], K[3][7], V[3][0], tag);
            st_tag(p + 96, V[3][1], V[3][2], V[3][3], tag); st_tag(p + 128, V[3][4], V[3][5], V[3][6], tag); st_tag(p + 160, V[3][7], r0, r1, tag);
          }
        });
        TL(t, 3);
        const int lane = lane_now(), q = lane & 3, r8 = lane >> 2;
        st[0] = lds8f(sta + r8 * 8); st[2] = lds8f(sta + (16 + r8) * 8);
#pragma unroll
        for (int j = 0; j < 24; j++) {
          const float2 cs = lds8f(csa + j * 32);
#pragma unroll
          for (int g = 0; g < (j < 8 ? 4 : 3); g++) {
            const uint32_t pk = fix(g, j, cs);
            if (j < 8) Q[g][j] = pk; else if (j < 16) K[g][j - 8] = pk; else V[g][j - 16] = movmat(pk);
          }
        }
        const bool up0 = (2 * q) > r8, up1 = (2 * q + 1) > r8;
        const uint32_t mskP = (up0 ? 0xffffu : 0u) | (up1 ? 0xffff0000u : 0u);
        TL(t, 5);
        uint32_t Kp[8] = {}, Vp[8] = {}, PS[2][4] = {}, PP[2][4] = {};
        float sS[2][4][2], sP[2][4][2], O[2][4][4][2], z0, z1, z2, z3;
        auto receive = [&]() {
          const uint32_t xa = xch(i, w) + lane * 16;
          mbar_wait(bar(B_XCH), i);
          lds16(xa, Kp[0], Kp[1], Kp[2], Kp[3]); lds16(xa + 512, Kp[4], Kp[5], Kp[6], Kp[7]);
          lds16(xa + 1024, Vp[0], Vp[1], Vp[2], Vp[3]); lds16(xa + 1536, Vp[4], Vp[5], Vp[6], Vp[7]);
          TL(i == 0 ? 22 : 23, t < 11 ? 3 : 4);
        };
        auto score0 = [&]() {
          float dm0, dm1;
#pragma unroll
          for (int h = 0; h < 2; h++) mma16816(sP[h][0][0], sP[h][0][1], dm0, dm1, Q[0][h * 4], Q[0][h * 4], Q[0][h * 4 + 1], Q[0][h * 4 + 1], Kp[h * 4], Kp[h * 4 + 1], z0, z1, z2, z3);
#pragma unroll
          for (int h = 0; h < 2; h++)
            mma16816(sP[h][0][0], sP[h][0][1], dm0, dm1, Q[0][h * 4 + 2], Q[0][h * 4 + 2], Q[0][h * 4 + 3], Q[0][h * 4 + 3], Kp[h * 4 + 2], Kp[h * 4 + 3], sP[h][0][0], sP[h][0][1], 0.f, 0.f);
        };
        auto softmax = [&](int g) {
          const float rk0 = lds4f(sta + (g * 8 + 2 * q - (up0 ? 8 : 0)) * 8), rk1 = lds4f(sta + (g * 8 + 2 * q + 1 - (up1 ? 8 : 0)) * 8);
          const float f = st[g].x * (0.17677669529663687f * LOG2E), f0 = f * rk0, f1 = f * rk1;
          const bool noprev = g == 0 && (m & 7) == 0 && w == 0;
#pragma unroll
          for (int h = 0; h < 2; h++) {
            float v0 = (up0 ? sP[h][g][0] : sS[h][g][0]) * f0, v1 = (up1 ? sP[h][g][1] : sS[h][g][1]) * f1;
            if (noprev && up0) v0 = -1e9f * LOG2E;
            if (noprev && up1) v1 = -1e9f * LOG2E;
            float mx = fmaxf(v0, v1);
            mx = fmaxf(mx, __shfl_xor_sync(0xffffffffu, mx, 1)); mx = fmaxf(mx, __shfl_xor_sync(0xffffffffu, mx, 2));
            const float e0 = ex2f(v0 - mx), e1 = ex2f(v1 - mx);
            float sum = e0 + e1;
            sum += __shfl_xor_sync(0xffffffffu, sum, 1); sum += __shfl_xor_sync(0xffffffffu, sum, 2);
            const float inv = rcpf(sum);
            const uint32_t pk = pack_bf16_v(e0 * inv * rk0, e1 * inv * rk1);
            PS[h][g] = pk & ~mskP; PP[h][g] = pk & mskP;
          }
        };
        const uint32_t sa = SM_STG + (w * 32 + (lane & 7)) * 128 + (((lane >> 3) ^ (lane & 7)) << 4);
        auto stage = [&](int g) {
#pragma unroll
          for (int h = 0; h < 2; h++)
            stsm4((sa ^ (h * 64)) + g * 1024, pack_bf16(O[h][g][0][0], O[h][g][0][1]), pack_bf16(O[h][g][1][0], O[h][g][1][1]),
                  pack_bf16(O[h][g][2][0], O[h][g][2][1]), pack_bf16(O[h][g][3][0], O[h][g][3][1]));
        };
        char* const go = reinterpret_cast<char*>(g_o + (size_t)(m * 128 + w * 32) * D_ + (8 + c) * 64);
        if (i == 0) { receive(); bar_sync(NB_PX, 256); }
        lds16f(SM_ZERO, z0, z1, z2, z3);
#pragma unroll
        for (int h = 0; h < 2; h++) {
          float dm0, dm1;
          const int j0 = h * 4;
#pragma unroll
          for (int g = 0; g < 3; g++) mma16816(sS[h][g][0], sS[h][g][1], sP[h][g + 1][0], sP[h][g + 1][1], Q[g][j0], Q[g + 1][j0], Q[g][j0 + 1], Q[g + 1][j0 + 1], K[g][j0], K[g][j0 + 1], z0, z1, z2, z3);
          mma16816(sS[h][3][0], sS[h][3][1], dm0, dm1, Q[3][j0], Q[3][j0], Q[3][j0 + 1], Q[3][j0 + 1], K[3][j0], K[3][j0 + 1], z0, z1, z2, z3);
        }
#pragma unroll
        for (int h = 0; h < 2; h++) {
          float dm0, dm1;
          const int j0 = h * 4 + 2;
#pragma unroll
          for (int g = 0; g < 3; g++) mma16816(sS[h][g][0], sS[h][g][1], sP[h][g + 1][0], sP[h][g + 1][1], Q[g][j0], Q[g + 1][j0], Q[g][j0 + 1], Q[g + 1][j0 + 1], K[g][j0], K[g][j0 + 1],
                                               sS[h][g][0], sS[h][g][1], sP[h][g + 1][0], sP[h][g + 1][1]);
          mma16816(sS[h][3][0], sS[h][3][1], dm0, dm1, Q[3][j0], Q[3][j0], Q[3][j0 + 1], Q[3][j0 + 1], K[3][j0], K[3][j0 + 1], sS[h][3][0], sS[h][3][1], 0.f, 0.f);
        }
        if (i == 0) {
          score0();
          bar_arrive(NB_PY + ((__float_as_uint(sP[0][0][0]) | __float_as_uint(sP[1][0][0])) & __float_as_uint(z0)), 256);
          softmax(0);
        } else if (O_W & 1) bar_arrive(NB_OGO + ((__float_as_uint(sS[0][3][0]) | __float_as_uint(sS[1][3][0]) | __float_as_uint(sS[1][2][0])) & __float_as_uint(z0)), 256);
#pragma unroll
        for (int g = 1; g < 4; g++) softmax(g);
        TL(23, i == 0 ? (t < 11 ? 5 : 6) : 7);
        if (i == 0) bar_sync(NB_PX + ((PS[0][1] | PS[0][2] | PS[0][3] | PS[1][1] | PS[1][2] | PS[1][3]) & __float_as_uint(z0)), 256);
        lds16f(SM_ZERO, z0, z1, z2, z3);
#pragma unroll
        for (int x = 0; x < 8; x++) {
          const int h = x >> 2, j = x & 3;
          mma16816(O[h][1][j][0], O[h][1][j][1], O[h][2][j][0], O[h][2][j][1], PS[h][1], PP[h][2], PP[h][1], 0u, V[1][x], V[0][x], z0, z1, z2, z3);
        }
#pragma unroll
        for (int x = 0; x < 8; x++) {
          const int h = x >> 2, j = x & 3;
          mma16816(O[h][3][j][0], O[h][3][j][1], O[h][2][j][0], O[h][2][j][1], PS[h][3], 0u, PP[h][3], PS[h][2], V[3][x], V[2][x], 0.f, 0.f, O[h][2][j][0], O[h][2][j][1]);
        }
        if (i) {
          if (O_W & 2) bar_arrive(NB_OGO + (O_W & 1) + ((__float_as_uint(O[1][3][2][0]) | __float_as_uint(O[1][3][3][0])) & __float_as_uint(z0)), 256);
          if (CPY == 0) { stage(1); stage(2); stage(3); copy_out<6>(SM_STG + w * 4096 + 1024, go + 8 * D_ * 2, D_ * 2, lane); }
          receive(); score0(); softmax(0);
        }
        {
          uint32_t y = 0;
#pragma unroll
          for (int x = 0; x < 8; x++) {
            const int h = x >> 2, j = x & 3;
            float dm0, dm1;
            mma16816(O[h][0][j][0], O[h][0][j][1], dm0, dm1, PS[h][0], 0u, PP[h][0], 0u, V[0][x], Vp[x], z0, z1, z2, z3);
            y |= __float_as_uint(O[h][0][j][0]);
          }
          if (i == 0 || (O_W & 4)) bar_arrive((i ? NB_OGO + O_NW : NB_PY) + (y & __float_as_uint(z0)), 256);
          if (i == 0 || CPY) { stage(1); stage(2); stage(3); }
        }
        stage(0);
        if (CPY == 2 && i) bar_arrive(NB_OGO + O_NW, 256);
        if (i) copy_out<CPY ? 8 : 2>(SM_STG + w * 4096, go, D_ * 2, lane);
        mbar_arrive_warp(bar(B_SIG + 1));
        if (!(O_W & 4) && CPY != 2 && i) bar_arrive(NB_OGO + O_NW, 256);
        TL(t, 6);
      } else if (i > 2 && i < 10) {
        float acc[2][64];
        if (i != 4) mbar_wait(bar(B_TURN) + 8 * wg, (t - 1) >> 1);
        float2 cs[16];
        float c1[4], vr[4];
        uint32_t so, sta;
        mainloop<1>(acc, sig, t, wg, [&]() {
          const int lane = lane_now();
          so = SM_STG + (w * 16 + (lane & 7)) * 128 + (((lane >> 3) ^ (lane & 7)) << 4);
          sta = stat(l * 2 + 1) + (w * 16 + (lane >> 2)) * 8;
          mbar_wait(bar(B_STAT + 1) + l * 16, 0);
          mbar_wait(bar(B_CS - 1) + 8 * i, 0);
#pragma unroll
          for (int j = 0; j < 16; j++) cs[j] = lds8f(SM_CS + i * 512 + (lane & 3) * 8 + j * 32);
#pragma unroll
          for (int j = 0; j < 4; j++) {
            const float r = lds4f(sta + (j >> 1) * 512 + (j & 1) * 64);
            if (TANH) { vr[j] = r; c1[j] = r * 0.5f; }
            else {
              asm volatile("rcp.approx.ftz.f32 %0, %1;" : "=f"(vr[j]) : "f"(r * r));
              c1[j] = r * -LOG2E;
            }
          }
          mbar_wait(bar(B_FREE), l * 9 + i - 2);
        }, []() {});
        TL(t, 3);
        float mn[8];
#pragma unroll
        for (int x = 0; x < GLA; x++) mn[x] = __uint_as_float(lds4(sta + 4 + (x >> 2) * 512 + ((x >> 1) & 1) * 64));
#pragma unroll
        for (int x = 0; x < 8; x++) {
          const int mi = x >> 2, half = (x >> 1) & 1, g = x & 1;
          const float var = vr[x >> 1], cc = c1[x >> 1];
          uint32_t v[4];
#pragma unroll
          for (int j = 0; j < 4; j++) {
            const int jg = g * 4 + j + SWAP * 8, ju = jg ^ 8;
            const float2 cg = cs[jg], cu = cs[ju];
            const float g0 = fmaf(mn[x], cg.x, acc[mi][jg * 4 + half * 2]), g1 = fmaf(mn[x], cg.y, acc[mi][jg * 4 + half * 2 + 1]);
            const float u0 = fmaf(mn[x], cu.x, acc[mi][ju * 4 + half * 2]), u1 = fmaf(mn[x], cu.y, acc[mi][ju * 4 + half * 2 + 1]);
            if (TANH) {
              const float a0 = g0 * cc, a1 = g1 * cc;
              const float s0 = fmaf(a0, tanhf_(a0), a0), s1 = fmaf(a1, tanhf_(a1), a1);
              v[j] = TANH == 2 ? pack_bf16(s0 * u0, s1 * u1) : pack_bf16(s0 * u0 * var, s1 * u1 * var);
            } else {
              const float r0 = rcpf(fmaf(ex2f(g0 * cc), var, var)), r1 = rcpf(fmaf(ex2f(g1 * cc), var, var));
              v[j] = pack_bf16(g0 * u0 * r0, g1 * u1 * r1);
            }
          }
          stsm4((so ^ (g * 64)) + (mi * 64 + half * 8) * 128, v[0], v[1], v[2], v[3]);
          if ((x & 3) == 3) mbar_arrive_warp(bar(B_SIG + mi));
          if (x + GLA < 8) mn[x + GLA] = __uint_as_float(lds4(sta + 4 + ((x + GLA) >> 2) * 512 + (((x + GLA) >> 1) & 1) * 64));
        }
        TL(t, 6);
      } else {
        float acc[2][64], rsc[4];
        {
          const int lane = lane_now();
          const uint32_t e = c_sched.task[t].res;
          const uint32_t ra = SB + (w * 16 + (lane & 7)) * 128 + (((lane >> 3) ^ (lane & 7)) << 4);
          float sd[4];
#pragma unroll
          for (int j = 0; j < 4; j++) {
            rsc[j] = i == 10 ? lds4f(stat(l * 2 + 1) + ((j >> 1) * 64 + w * 16 + (j & 1) * 8 + (lane >> 2)) * 8) : 1.f;
            sd[j] = rcpf(rsc[j]);
          }
          const uint32_t zero = lds4(SM_ZERO);
          mbar_wait(bar(B_RES), i == 10);
          uint32_t dep[16];
#pragma unroll
          for (int x = 0; x < 16; x++) {
            const int mi = x >> 3, half = (x >> 2) & 1, g = x & 3;
            uint32_t v[4];
            ldsm4(((e >> ((g >> 1) * 8)) & 31) * 8192 + ((ra ^ ((g & 1) * 64)) | (RLA && x >= RLA ? dep[x - RLA] : 0)) + (mi * 64 + half * 8) * 128, v[0], v[1], v[2], v[3]);
#pragma unroll
            for (int j = 0; j < 4; j++) {
              asm volatile("shl.b32 %0, %1, 16;" : "=f"(acc[mi][(g * 4 + j) * 4 + half * 2]) : "r"(v[j]));
              asm volatile("and.b32 %0, %1, 0xffff0000;" : "=f"(acc[mi][(g * 4 + j) * 4 + half * 2 + 1]) : "r"(v[j]));
              if (TANH == 2) { acc[mi][(g * 4 + j) * 4 + half * 2] *= sd[mi * 2 + half]; acc[mi][(g * 4 + j) * 4 + half * 2 + 1] *= sd[mi * 2 + half]; }
            }
            asm("and.b32 %0, %1, %2;" : "=r"(dep[x]) : "f"(acc[mi][(g * 4 + 3) * 4 + half * 2 + 1]), "r"(zero));
          }
          mbar_arrive_warp(bar(B_RF));
        }
        mbar_wait(bar(B_TURN) + 8 * wg, (t - 1) >> 1);
        auto stage = [&](int mi, int hi) {
          const int lane = lane_now();
          const uint32_t sw = SB + ((c_sched.task[t].stg >> (8 * hi)) & 31) * 8192 + (mi * 64 + w * 16) * 128, so = sw + (lane & 7) * 128 + (((lane >> 3) ^ (lane & 7)) << 4);
#pragma unroll
          for (int half = 0; half < 2; half++)
#pragma unroll
            for (int g = 0; g < 2; g++) {
              uint32_t v[4];
#pragma unroll
              for (int j = 0; j < 4; j++) {
                if (TANH == 2) { acc[mi][(hi * 8 + g * 4 + j) * 4 + half * 2] *= rsc[mi * 2 + half]; acc[mi][(hi * 8 + g * 4 + j) * 4 + half * 2 + 1] *= rsc[mi * 2 + half]; }
                v[j] = pack_bf16(acc[mi][(hi * 8 + g * 4 + j) * 4 + half * 2], acc[mi][(hi * 8 + g * 4 + j) * 4 + half * 2 + 1]);
              }
              stsm4((so ^ (g * 64)) + half * 1024, v[0], v[1], v[2], v[3]);
            }
          if (mi && !hi) mbar_arrive_warp(bar(B_SIG));
          if (hi == 0 || t == 21) {
            const int r = mi * 64 + w * 16;
            bf16* const g = t == 21 ? P.out + (size_t)((row0 + r) * 2 + par) * D_ : g_y + (size_t)(m * 128 + r) * D_;
            copy_out<4>(sw, reinterpret_cast<char*>(g + (hi * 8 + c) * 64), t == 21 ? D_ * 4 : D_ * 2, lane);
          }
        };
        mainloop<2>(acc, sig, t, wg, []() {}, [&]() { stage(0, 0); if (!SH1 || (SH1 == 2 && t == 21)) stage(0, 1); });
        TL(t, 3);
        stage(1, 0); mbar_arrive_warp(bar(B_SIG + 1));
        TL(t, 6);
        if (SH1 == 1 || (SH1 == 2 && t < 21)) stage(0, 1);
        stage(1, 1); mbar_arrive_warp(bar(B_SIG + 2));
        if (t < 21) {
          const int lane = lane_now(), q = lane & 3;
          float s[4], s2[4];
#pragma unroll
          for (int x = 0; x < 4; x++) {
            float a0 = 0.f, a1 = 0.f, b0 = 0.f, b1 = 0.f;
#pragma unroll
            for (int j = 0; j < 16; j++) {
              const float d0 = acc[x >> 1][j * 4 + (x & 1) * 2], d1 = acc[x >> 1][j * 4 + (x & 1) * 2 + 1];
              a0 += d0; a1 += d1; b0 = fmaf(d0, d0, b0); b1 = fmaf(d1, d1, b1);
            }
            s[x] = a0 + a1; s2[x] = b0 + b1;
          }
#pragma unroll
          for (int x = 0; x < 2; x++) {
            s[x] = (q & 2 ? s[x + 2] : s[x]) + __shfl_xor_sync(0xffffffffu, q & 2 ? s[x] : s[x + 2], 2);
            s2[x] = (q & 2 ? s2[x + 2] : s2[x]) + __shfl_xor_sync(0xffffffffu, q & 2 ? s2[x] : s2[x + 2], 2);
          }
          const float r = (q & 1 ? s[1] : s[0]) + __shfl_xor_sync(0xffffffffu, q & 1 ? s[0] : s[1], 1);
          const float r2 = (q & 1 ? s2[1] : s2[0]) + __shfl_xor_sync(0xffffffffu, q & 1 ? s2[0] : s2[1], 1);
          asm volatile("st.global.v2.f32 [%0], {%1, %2};" ::"l"(&g_stat[i == 10 ? 1 : l * 2][m][c][(q >> 1) * 64 + w * 16 + (q & 1) * 8 + (lane >> 2)]), "f"(r), "f"(r2) : "memory");
          mbar_arrive_warp(bar(B_SIG + 3));
        }
      }
    }
  }
}

typedef CUresult (*PFN_encodeTiled)(CUtensorMap*, CUtensorMapDataType, cuuint32_t, void*, const cuuint64_t*, const cuuint64_t*, const cuuint32_t*,
                                    const cuuint32_t*, CUtensorMapInterleave, CUtensorMapSwizzle, CUtensorMapL2promotion, CUtensorMapFloatOOBfill);

void make_map(PFN_encodeTiled enc, CUtensorMap* mp, const void* ptr, int rank, const cuuint64_t* gd, const cuuint64_t* gs, const cuuint32_t* bd) {
  const cuuint32_t es[4] = {1, 1, 1, 1};
  enc(mp, CU_TENSOR_MAP_DATA_TYPE_BFLOAT16, rank, const_cast<void*>(ptr), gd, gs, bd, es, CU_TENSOR_MAP_INTERLEAVE_NONE, CU_TENSOR_MAP_SWIZZLE_128B,
      CU_TENSOR_MAP_L2_PROMOTION_L2_256B, CU_TENSOR_MAP_FLOAT_OOB_FILL_NONE);
}
void make_map_act(PFN_encodeTiled enc, CUtensorMap* mp, const void* ptr, uint64_t cols, bool natural, uint32_t rows) {
  const cuuint64_t gd[3] = {cols, S_ / 2, 2}, gs[2] = {natural ? 4 * cols : 2 * cols, natural ? 2 * cols : cols * S_};
  const cuuint32_t bd[3] = {64, rows, 1};
  make_map(enc, mp, ptr, 3, gd, gs, bd);
}
void make_map_w(PFN_encodeTiled enc, CUtensorMap* mp, const void* ptr, uint64_t rows, uint64_t cols, uint32_t np, uint64_t sp, uint64_t tiles, uint32_t nt) {
  const cuuint64_t gd[4] = {512, rows, np, tiles}, gs[3] = {cols * 2, sp, 1024};
  const cuuint32_t bd[4] = {64, 64, np, nt};
  make_map(enc, mp, ptr, 4, gd, gs, bd);
}

}

extern "C" void kernel_launch(void* const* d_in, const int* in_sizes, int n_in, void* d_out, int out_size) {
  (void)in_sizes; (void)n_in; (void)out_size;
  static PFN_encodeTiled enc = nullptr;
  static void *p_o, *p_y, *p_h, *p_w;
  static int by_sm = 0;
  if (!enc) {
    void* fn = nullptr; cudaDriverEntryPointQueryResult qr;
    cudaGetDriverEntryPoint("cuTensorMapEncodeTiled", &fn, cudaEnableDefault, &qr);
    enc = (PFN_encodeTiled)fn;
    cudaGetSymbolAddress(&p_o, g_o); cudaGetSymbolAddress(&p_y, g_y); cudaGetSymbolAddress(&p_h, g_h); cudaGetSymbolAddress(&p_w, g_w13);
    cudaFuncSetAttribute(fused_kernel<0>, cudaFuncAttributeMaxDynamicSharedMemorySize, SM_TOTAL);
    cudaFuncSetAttribute(fused_kernel<1>, cudaFuncAttributeMaxDynamicSharedMemorySize, SM_TOTAL);
    int dev = 0, sms = 0;
    cudaGetDevice(&dev);
    cudaDeviceGetAttribute(&sms, cudaDevAttrMultiProcessorCount, dev);
    by_sm = sms == NCTA + NHELP;
    for (int i = 1; i < 4 && by_sm; i++) {
      cudaLaunchConfig_t cfg = {};
      cudaLaunchAttribute at;
      at.id = cudaLaunchAttributeClusterDimension; at.val.clusterDim.x = 1 << i; at.val.clusterDim.y = at.val.clusterDim.z = 1;
      cfg.gridDim = dim3(NCTA); cfg.blockDim = dim3(384); cfg.dynamicSmemBytes = SM_TOTAL; cfg.attrs = &at; cfg.numAttrs = 1;
      int n = 0;
      if (cudaOccupancyMaxActiveClusters(&n, fused_kernel<0>, &cfg) != cudaSuccess) { (void)cudaGetLastError(); n = 0; }
      by_sm = n == (i == 1 ? 66 : i == 2 ? 30 : 15);
    }
  }
  Params P;
  P.x0 = (const bf16*)d_in[0]; P.out = (bf16*)d_out; P.by_sm = by_sm;
  make_map_act(enc, &P.tm[M_X0], d_in[0], D_, true, 128);
  make_map_act(enc, &P.tm[M_O], p_o, D_, false, 128);
  make_map_act(enc, &P.tm[M_Y], p_y, D_, false, 128);
  make_map_act(enc, &P.tm[M_H], p_h, F_, false, 128);
  make_map_act(enc, &P.tm[M_OL], p_o, D_, false, PROWS);
  make_map_act(enc, &P.tm[M_YL], p_y, D_, false, PROWS);
  make_map_act(enc, &P.tm[M_HL], p_h, F_, false, PROWS);
  make_map_w(enc, &P.tm[M_WQKV], d_in[1], D_, 3 * D_, 3, D_ * 2, 2, 1);
  make_map_w(enc, &P.tm[M_WO], d_in[2], D_, D_, 2, 1024, 1, 1);
  make_map_w(enc, &P.tm[M_W2], d_in[6], F_, D_, 2, 1024, 1, 1);
  const char *w1 = (const char*)d_in[4], *w3 = (const char*)d_in[5];
  if ((uint64_t)(w1 < w3 ? w3 - w1 : w1 - w3) >> 39) {
    cudaMemcpyAsync(p_w, w1, (size_t)D_ * F_ * 2, cudaMemcpyDeviceToDevice);
    cudaMemcpyAsync((bf16*)p_w + D_ * F_, w3, (size_t)D_ * F_ * 2, cudaMemcpyDeviceToDevice);
    w1 = (const char*)p_w; w3 = w1 + (size_t)D_ * F_ * 2;
  }
  const bool swap = w3 < w1;
  make_map_w(enc, &P.tm[M_W13], swap ? w3 : w1, D_, F_, 2, swap ? w1 - w3 : w3 - w1, 7, 1);
  make_map_w(enc, &P.tm[M_W13P], swap ? w3 : w1, D_, F_, 2, swap ? w1 - w3 : w3 - w1, 7, 2);
  if (swap) fused_kernel<1><<<NCTA + NHELP, 384, SM_TOTAL>>>(P);
  else fused_kernel<0><<<NCTA + NHELP, 384, SM_TOTAL>>>(P);
}
```

```cpp
#include <cuda_runtime.h>
#include <cuda_bf16.h>
#include <cuda.h>
#include <stdint.h>
#include <stddef.h>

typedef __nv_bfloat16 bf16;
#define GU_E 3
#define G_N1 7
#define G_R1 16
#define Q_P1 4
#define Q_P2 6
#define Q_P0 0
#define ST_ROWS 3500
#define PROWS 16
#define GAP_O 150
#define GAP_Y 100
#define GAP_H 350
#define GAP_H6 1000
#define DEP32 0x84
#define HOLD 17
#define GLA 2
#define RELQ 3
#define RELG 1
#define RELD 3
#define WARM_T 4000
#define RLA 1
#define PXE 1
#define HOLD_O 6
#define SH1 0
#define RES_O 3
#define RES_D 3
#define ST_T1 900
#define ST_D1 500
#define QUIET 1
#define QOWN 1
#define TURN_L 1
#define CNT 1
#define TANH 2
#define TAILQ 1
#define TAIL 2
#define WARM_X 1

namespace {

constexpr int S_ = 2048, D_ = 1024, F_ = 3584;
constexpr int NCTA = 128;
constexpr int NHELP = 4;

constexpr uint32_t SB = 1024;
constexpr int NU = 25;
constexpr uint32_t SM_STG  = SB + NU * 8192;
__host__ __device__ constexpr uint32_t xch(int i, int w) { return i ? SM_STG - 8192 + w * 2048 : SM_STG + w * 4096; }
constexpr uint32_t BARS    = SM_STG + 16384;
constexpr uint32_t SM_STAT = BARS + 896;
__host__ __device__ constexpr uint32_t stat(int set) { return SM_STAT + set * 1088 + 64; }
constexpr uint32_t SM_CS   = SM_STAT + 4352;
constexpr uint32_t SM_END  = SM_CS + 5120;
constexpr int SM_TOTAL = SM_END - SB;
static_assert(BARS % 1024 == 0 && SM_TOTAL <= 232448, "smem");
constexpr int B_FULL = 0, B_EMPTY = 16, B_SIG = 32, B_XCH = 36, B_STAT = 37, B_TURN = 41, B_CS = 43, B_FREE = 52, B_SF = 53, B_QT = 55, B_PASS = 56,
              B_RES = 57, B_RF = 58, B_DEP = 59, B_PUB = 75, B_N = 91;
__host__ __device__ constexpr uint32_t bar(int i) { return BARS + 8 * i; }
constexpr uint32_t SM_TAG = BARS + 8 * B_N, SM_ZERO = BARS + 768;
constexpr int NB_WG = 1, NB_PX = 3, NB_PY = 4, NB_INIT = 5, NB_OGO = 6;

constexpr int E_O0 = 0, E_O1 = 1, E_YA = 2, E_YB = 3, E_H4 = 4, E_XA = 7, E_XB = 8, E_N = 9;

constexpr int M_X0 = 0, M_O = 1, M_Y = 2, M_H = 3;
constexpr int M_WQKV = 4, M_WO = 5, M_W13 = 6, M_W13P = 7, M_W2 = 8;
constexpr int M_OL = 9, M_YL = 10, M_HL = 11, M_O24 = 12, M_N = 13;

constexpr int FIRST = 5;
constexpr int NOPA = 416, NOPB = 416, NSEG = 40;
constexpr uint32_t A_END = 1, A_TURN = 2, A_DRAIN = 4, A_WAIT = 8, A_SYNC = 16,
                   A_MARK = 0;
struct Task { uint32_t stg, res, sig; };
struct Seg { uint32_t i8, end8, a, b; };
constexpr uint32_t LO_A = 0x10000 + SB / 16, LO_B = 0x2000000 + SB / 16;
struct Sched { Seg seg[2 * NSEG]; Task task[22]; };
struct Ops { uint2 a[NOPA + 64], b[NOPB + 64]; };
struct Gen {
  Sched s{}; Ops o{};
  int n[2] = {0, 0}, nseg[2] = {0, NSEG}, cur = -1, pos = 0, err = 0, res = 0, nres = 0;
  int mask[400] = {}, sa[400] = {}, sb[400][2] = {}, own[NU][2] = {}, tok[NU] = {}, known[2][2] = {{-1, -1}, {-1, -1}};
  constexpr void emit(int p, int wait, int par, int dst, int map, int kb8, int arr, int load, int y) {
    if (cur < FIRST) return;
    const uint2 e{(uint32_t)(y >> 10 | (p && load ? map - M_WQKV : map) << 3 | (y & 63) << 6 | load << 12 | dst << 13 | (res ? B_RES : B_FULL + (cur & 15)) << 18 | wait << 24) | (uint32_t)(par & 1) << 31,
                  (uint32_t)(((y >> 6) & 15) | arr << 4 | (!p && arr && mask[cur] != 3 && !res) << 5 | ((cur + 2) & 15) << 9 | kb8 << 13)};
    if (p) o.b[n[1]++] = e; else o.a[n[0]++] = e;
  }
  constexpr bool done(int p, int x) const { return x < 0 || ((!(mask[x] & 1) || known[p][0] >= x) && (!(mask[x] & 2) || known[p][1] >= x)); }
  constexpr void op(int p, int dst, int nu, int map, int kb8, int arr, int y, int xw = -1, int xp = 0) {
    int w[8] = {}, wp[8] = {}, nw = 0;
    if (xw >= 0) { w[nw] = xw; wp[nw++] = xp; }
    for (int u = dst; u < dst + nu; u++) if (tok[u] && (u == dst || tok[u] != tok[u - 1])) { w[nw] = (tok[u] - 1) >> 1; wp[nw++] = tok[u] - 1; }
    for (int x = cur - 1; x >= 0; x--) {
      bool need = x <= cur - 12;
      for (int u = dst; u < dst + nu; u++) need = need || own[u][0] == x + 1 || own[u][1] == x + 1;
      if (!need || done(p, x)) continue;
      if (cur - x >= 16 || !done(p, x - 16)) err |= 1;
      w[nw] = B_EMPTY + ((x + 2) & 15); wp[nw++] = x >> 4;
      for (int g = 0; g < 2; g++) if (((mask[x] >> g) & 1) && known[p][g] < x) known[p][g] = x;
    }
    for (; nw > 1; nw--) emit(p, w[nw - 1], wp[nw - 1], 0, 0, 0, 0, 0, 0);
    emit(p, nw ? w[0] : B_PASS, nw ? wp[0] : 1, dst, map, kb8, arr, nu > 0, y);
    for (int u = dst; u < dst + nu; u++) { own[u][0] = cur + 1; own[u][1] = 0; tok[u] = 0; }
  }
  constexpr int step(int m) { mask[++cur] = m; return cur; }
  constexpr int slot() { int u = (pos + 1) & ~1; if (u >= 24) u = 0; pos = u + 2; return u; }
  constexpr int qslot() { int u = (pos + 4) / 5 * 5; if (u >= NU) u = 0; pos = u + 5; return u; }
  constexpr void stage(int u, int first, int t) {
    if (!(SH1 && t)) first -= TAIL;
    for (int x = u; x < u + 2; x++) { if (own[x][0] > first || own[x][1] > first || tok[x]) err |= 2; own[x][0] = cur + 1; own[x][1] = 0; tok[x] = t; }
  }
  static constexpr int kown(int hi) { return hi * 8 | 1 << 9; }
  static constexpr int kskip(int hi, int j) { return (hi * 8 + j) | (j + 1) << 6; }
  static constexpr int kpos(int p) { return p < 2 ? kown(p) : p < 9 ? kskip(0, p - 2) : kskip(1, p - 9); }
  constexpr void segs(int t, const int* st, const uint32_t* act, int cnt, int tail, int inc0) {
    const int g = t & 1, wrap = inc0 == 5 ? NU : 24;
    int j0 = 0;
    for (int j = 0; j < cnt; j++) {
      const int x = st[j], inc = inc0 ? inc0 : mask[st[j0]] == 3 ? 6 : 4;
      const bool next = j + 1 < cnt && st[j + 1] == x + 1 && mask[x + 1] == mask[x] && sa[x + 1] == (sa[x] + inc) % wrap && sb[x + 1][g] == (sb[x][g] + inc) % wrap;
      if (j >= cnt - tail - 1 && j + 1 < cnt && !next) err |= 4;
      if (j + 1 < cnt && st[j + 1] != x + 1 && !(act[j] & A_DRAIN)) err |= 8;
      if (j >= cnt - tail || (next && !act[j] && j != cnt - tail - 1)) continue;
      if (j == j0 && (j == 0 || (inc0 != 4 && (act[j - 1] & (A_DRAIN | A_SYNC))))) err |= 16;
      const int y = st[j0];
      s.seg[nseg[g]++] = Seg{(uint32_t)y * 8 | (act[j] | (j == cnt - tail - 1 ? A_END : 0)) << 16, (uint32_t)(x + 1) * 8 | inc * 512 << 16, LO_A + sa[y] * 512, LO_B + sb[y][g] * 512};
      j0 = j + 1;
    }
  }
  constexpr void residual(int t, int map, bool q) {
    const int u0 = q ? qslot() : slot(), u1 = q ? u0 + 2 : slot();
    res = 1;
    op(0, u0, 2, map, 4, 1, kown(0)); op(0, u1, 2, map, 0, 0, kown(1));
    res = 0;
    for (int x = 0; x < 4; x++) { const int u = (x < 2 ? u0 : u1) + (x & 1); own[u][0] = 0; tok[u] = 1 + B_RF * 2 + (nres & 1); }
    nres++;
    s.task[t].res = u0 | u1 << 8;
  }
  constexpr Gen() {
    int cs[4] = {};
    for (int t = 0; t < 22; t++) {
      const int i = t % 11, use = i == 0 ? 2 : (i == 2 || i == 10) ? 15 : 3;
      for (int x = 0; x < 4; x++) if ((use >> x) & 1) s.task[t].sig |= (cs[x]++ & 1) << x;
    }
    for (int l = 0; l < 2; l++) {
      const int T = l * 11, dep = B_DEP + l * E_N;
      int st[7][56] = {};
      uint32_t act[7][56] = {};
      if (l == 1) {
        const int first = cur + 1;
        for (int j = 0; j < 4; j++) {
          const int x = st[j >> 1][j & 1] = step(1 << ((T + (j >> 1)) & 1)), u = qslot();
          sb[x][0] = sb[x][1] = u + 2;
          if (j < 2) {
            sa[x] = (u + QOWN * 5) % NU; stage(sa[x], first, j ? 1 + B_SF * 2 + 1 : 0); s.task[10].stg |= sa[x] << (8 * j);
            op(0, 0, 0, 0, 0, 1, 1 << 10, B_SIG + 2 * j, s.task[10].sig >> (2 * j));
          }
          else { sa[x] = sa[x - 2]; own[sa[x]][1] = own[sa[x] + 1][1] = x + 1; op(0, 0, 0, 0, 0, 1, 0); }
          op(1, u + 2, 3, M_WQKV, 3, 1, kown(j & 1) | (j >> 1) << 10);
        }
        act[0][1] = A_DRAIN; act[1][1] = A_DRAIN | A_WAIT;
      }
      for (int i = 0; i < 2; i++) {
        for (int j = 2 * l; j < 16; j++) {
          if (i && j == 16 - RES_O) residual(T + 2, l ? M_Y : M_X0, true);
          const int x = st[i][j] = step(1 << ((T + i) & 1)), u = qslot(), k = l ? kpos(j) : j;
          sa[x] = u; sb[x][0] = sb[x][1] = u + 2;
          op(0, u, 2, l ? M_Y : M_X0, 2, 1, k, l && i == 0 && (j == 2 || j == 9) ? B_DEP + (j == 2 ? E_XA : E_XB) : -1);
          op(1, u + 2, 3, M_WQKV, 3, 1, k | i << 10, (HOLD & 2) && l && i == 0 && j == 2 ? B_PUB + E_XA : (HOLD & 8) && l && i == 0 && j == 3 ? B_DEP + E_XA : -1);
        }
        if (i) act[1][Q_P1 - 1 + (l ? 2 : Q_P0)] = act[1][Q_P2 - 1 + (l ? 2 : Q_P0)] = A_SYNC;
        if (i && own[NU - 1][0] > cur - TAILQ) err |= 256;
        segs(T + i, st[i], act[i], 16, TAILQ, 5);
      }
      if (!RES_O) residual(T + 2, l ? M_Y : M_X0, false);
      for (int j = 0; j < 16; j++) {
        const int x = st[0][j] = step(1 << (T & 1)), k = j < 8 ? j : j == 8 ? kown(1) : kskip(1, j - 9), hold = j == HOLD_O ? B_PUB + l * E_N + E_O1 : -1;
        act[0][j] = j == 8 ? A_MARK : 0;
        if (j != 8) { sa[x] = slot(); op(0, sa[x], 2, M_O, 2, 1, k, j == 0 ? dep + E_O0 : j == 9 ? dep + E_O1 : hold); }
        else { sa[x] = NU; op(0, 0, 0, 0, 0, 1, 1 << 10, B_SIG + 1, s.task[T + 1].sig >> 1); }
        sb[x][0] = sb[x][1] = slot();
        op(1, sb[x][0], 2, M_WO, 2, 1, k, hold);
      }
      segs(T + 2, st[0], act[0], 16, TAIL, 4);
      int beg[8] = {0, G_R1}, end[7] = {16, G_R1 + 16 - G_N1}, cnt[7] = {};
      for (int j = 2; j < 7; j++) { beg[j] = end[j - 2] + GU_E; end[j] = beg[j] + 16; }
      beg[7] = end[6];
      const int first = cur + 1;
      for (int j = 0; j < end[6]; j++) {
        int tl[2] = {-1, -1}, m = 0;
        for (int v = 0; v < 7; v++) if ((j >= beg[v] && j < end[v]) || (v == 1 && j < G_N1)) { const int g = (T + 3 + v) & 1; if (tl[g] >= 0) err |= 32; tl[g] = v; m |= 1 << g; }
        if (!m) err |= 32;
        if (j == end[6] - RES_D) residual(T + 10, M_Y, false);
        const int x = step(m), k = kpos(j < 16 ? j : (j + G_N1) & 15);
        const int v0 = m == 3 ? (tl[0] < tl[1] ? tl[0] : tl[1]) : tl[m >> 1];
        const int ps = (pos + 1) / 2 % 12;
        const bool last = m == 3 && (ps % 3 == 1 || (QUIET && j >= 2 && j < G_N1 && (ps % 3 == 0 || (j == 2 && ps != 11))));
        if (!last) sa[x] = slot();
        const int u = slot();
        if (m == 3 && slot() != u + 2) err |= 32;
        if (last) sa[x] = slot();
        if (j < 2) { stage(sa[x], first, j ? 1 + B_SF * 2 : 0); s.task[T + 2].stg |= sa[x] << (8 * j); op(0, 0, 0, 0, 0, 1, 1 << 10, B_SIG + 2 * j, s.task[T + 2].sig >> (2 * j)); }
        else op(0, sa[x], 2, M_Y, 2, 1, k, j == 2 ? dep + E_YA : j == 9 ? dep + E_YB : -1);
        op(1, u, m == 3 ? 4 : 2, m == 3 ? M_W13P : M_W13, m == 3 ? 4 : 2, 1, k | v0 << 10, (HOLD & 1) && j == 2 + QUIET ? (HOLD & 4 ? B_DEP : B_PUB) + l * E_N + E_YA : -1);
        for (int g = 0; g < 2; g++) {
          const int v = tl[g];
          if (v < 0) continue;
          sb[x][g] = u + (v - v0) * 2;
          act[v][cnt[v]] = j == beg[v + 1] - 1 ? A_TURN : v == 1 && j == G_N1 - 1 ? A_DRAIN | A_WAIT : v == 0 && j == 1 ? A_MARK : 0;
          st[v][cnt[v]++] = x;
        }
      }
      for (int v = 0; v < 7; v++) { if (cnt[v] != 16) err |= 64; segs(T + 3 + v, st[v], act[v], 16, 0, 0); }
      if (!RES_D) residual(T + 10, M_Y, false);
      for (int j = 0; j < 56; j++) {
        const int x = st[0][j] = step(1 << (T & 1));
        act[0][j] = 0;
        sa[x] = slot(); op(0, sa[x], 2, M_H, 2, 1, j, j == 0 ? dep + E_H4 : j == 40 ? dep + E_H4 + 1 : j == 48 ? dep + E_H4 + 2 : -1);
        sb[x][0] = sb[x][1] = slot(); op(1, sb[x][0], 2, M_W2, 2, 1, j);
      }
      segs(T + 10, st[0], act[0], 56, TAIL, 4);
    }
    { const int u0 = slot(), u1 = slot(); stage(u0, cur + 1, 0); stage(u1, cur + 1, 0); s.task[21].stg = u0 | u1 << 8; }
    if (n[0] > NOPA || n[1] > NOPB || nseg[0] >= NSEG || nseg[1] >= 2 * NSEG) err |= 128;
    for (int x = n[0]; x < NOPA + 64; x++) o.a[x] = uint2{B_PASS << 24 | 1u << 31, 0};
    for (int x = n[1]; x < NOPB + 64; x++) o.b[x] = uint2{B_PASS << 24 | 1u << 31, 0};
  }
};
constexpr Gen GEN{};
static_assert(GEN.err == 0, "schedule");
constexpr int NOP0 = (GEN.n[0] + 31) / 32 * 32, NOP1 = (GEN.n[1] + 31) / 32 * 32;

struct __align__(64) Params {
  CUtensorMap tm[M_N];
};

}

__constant__ Sched c_sched = GEN.s;
__device__ const Ops g_ops = GEN.o;
struct __align__(1024) Scratch {
  bf16 o[S_ * D_], y[S_ * D_], h[S_ * F_];
  float2 stat[3][16][8][128];
  uint4 stat0[16][128];
  uint4 halo[4][16][8][6][32];
  uint4 cs[9][8][64];
  uint32_t flags[NCTA][32];
  uint32_t cnt[4][32];
  uint32_t epoch[NCTA + NHELP];
};
__device__ Scratch g_sc;
__device__ __align__(1024) bf16 g_w13[2 * D_ * F_];

#define TL(t, i) do {} while (0)
#define TL1(t, i) do {} while (0)
#define TS(i8, wg) do {} while (0)
#define TLW(t, i) do {} while (0)
#define MB_LIMIT (1 << 16)
#define FL_LIMIT (1 << 21)

namespace {

__device__ __forceinline__ uint32_t smem_u32(const void* p) { return (uint32_t)__cvta_generic_to_shared(p); }
__device__ __forceinline__ void mbar_init(uint32_t br, uint32_t cnt) { asm volatile("mbarrier.init.shared::cta.b64 [%0], %1;" ::"r"(br), "r"(cnt)); }
__device__ __forceinline__ void mbar_expect_tx(uint32_t br, uint32_t bytes) { asm volatile("mbarrier.arrive.expect_tx.shared::cta.b64 _, [%0], %1;" ::"r"(br), "r"(bytes) : "memory"); }
__device__ __forceinline__ void mbar_arrive(uint32_t br) { asm volatile("mbarrier.arrive.shared::cta.b64 _, [%0];" ::"r"(br) : "memory"); }
__device__ __forceinline__ void mbar_arrive_if(uint32_t br, uint32_t p) {
  asm volatile("{\n.reg .pred q;\nsetp.ne.u32 q, %1, 0;\n@q mbarrier.arrive.shared::cta.b64 _, [%0];\n}\n" ::"r"(br), "r"(p) : "memory");
}
__device__ __forceinline__ void mbar_arrive_cnt(uint32_t br, uint32_t cnt) {
  asm volatile("{\n.reg .pred q;\nsetp.ne.u32 q, %1, 0;\n@q mbarrier.arrive.shared::cta.b64 _, [%0], %1;\n}\n" ::"r"(br), "r"(cnt) : "memory");
}
__device__ __forceinline__ void mbar_arrive_warp(uint32_t br) {
  asm volatile("{\n.reg .pred q;\nbar.warp.sync 0xffffffff;\nelect.sync _|q, 0xffffffff;\n@q mbarrier.arrive.shared::cta.b64 _, [%0];\n}\n" ::"r"(br) : "memory");
}
__device__ __forceinline__ bool mbar_try_wait(uint32_t br, uint32_t parity) {
  uint32_t ok;
  asm volatile("{\n.reg .pred p;\nmbarrier.try_wait.parity.shared::cta.b64 p, [%1], %2;\nselp.u32 %0, 1, 0, p;\n}\n" : "=r"(ok) : "r"(br), "r"(parity) : "memory");
  return ok;
}
__device__ __forceinline__ bool mbar_test_wait(uint32_t br, uint32_t parity) {
  uint32_t ok;
  asm volatile("{\n.reg .pred p;\nmbarrier.test_wait.parity.shared::cta.b64 p, [%1], %2;\nselp.u32 %0, 1, 0, p;\n}\n" : "=r"(ok) : "r"(br), "r"(parity) : "memory");
  return ok;
}
__device__ __forceinline__ void mbar_wait(uint32_t br, uint32_t parity) {
#pragma unroll 1
  for (int it = 0; it < MB_LIMIT; ++it) { if (mbar_try_wait(br, parity)) return; }
  __trap();
}
__device__ __forceinline__ bool elect_one() { uint32_t p; asm volatile("{\n.reg .pred P;\nelect.sync _|P, 0xffffffff;\nselp.u32 %0, 1, 0, P;\n}\n" : "=r"(p)); return p; }
__device__ __forceinline__ void fence_proxy_async_smem() { asm volatile("fence.proxy.async.shared::cta;" ::: "memory"); }
__device__ __forceinline__ void tma3d(uint32_t dst, const CUtensorMap* m, int c0, int c1, int c2, uint32_t br) {
  asm volatile("cp.async.bulk.tensor.3d.shared::cluster.global.mbarrier::complete_tx::bytes [%0], [%1, {%3, %4, %5}], [%2];" ::"r"(dst), "l"(m), "r"(br), "r"(c0), "r"(c1), "r"(c2) : "memory");
}
__device__ __forceinline__ void tma4d(uint32_t dst, const CUtensorMap* m, int c0, int c1, int c3, uint32_t br) {
  asm volatile("cp.async.bulk.tensor.4d.shared::cluster.global.mbarrier::complete_tx::bytes [%0], [%1, {%3, %4, %6, %5}], [%2];" ::"r"(dst), "l"(m), "r"(br), "r"(c0), "r"(c1), "r"(c3), "r"(0) : "memory");
}
__device__ __forceinline__ void tma3d_store(const CUtensorMap* m, uint32_t src, int c0, int c1, int c2) {
  asm volatile("{\n.reg .pred p;\nelect.sync _|p, 0xffffffff;\n@p cp.async.bulk.tensor.3d.global.shared::cta.bulk_group [%0, {%2, %3, %4}], [%1];\n}\n" ::"l"(m), "r"(src), "r"(c0), "r"(c1), "r"(c2) : "memory");
}
__device__ __forceinline__ void stsm4(uint32_t a, uint32_t x, uint32_t y, uint32_t z, uint32_t w) {
  asm volatile("stmatrix.sync.aligned.m8n8.x4.shared.b16 [%0], {%1,%2,%3,%4};" ::"r"(a), "r"(x), "r"(y), "r"(z), "r"(w) : "memory");
}
__device__ __forceinline__ void ldsm4(uint32_t a, uint32_t& x, uint32_t& y, uint32_t& z, uint32_t& w) {
  asm volatile("ldmatrix.sync.aligned.m8n8.x4.shared.b16 {%0,%1,%2,%3}, [%4];" : "=r"(x), "=r"(y), "=r"(z), "=r"(w) : "r"(a) : "memory");
}
__device__ __forceinline__ void st_tag(uint4* p, uint32_t a, uint32_t b, uint32_t c, uint32_t tag) {
  asm volatile("{\n.reg .b64 x, y;\n.reg .b128 z;\nmov.b64 x, {%1, %2};\nmov.b64 y, {%3, %4};\nmov.b128 z, {x, y};\nst.relaxed.gpu.global.b128 [%0], z;\n}\n" ::"l"(p), "r"(a), "r"(b), "r"(c), "r"(tag) : "memory");
}
__device__ __forceinline__ uint4 ld_tag(const uint4* p) {
  uint4 v;
  asm volatile("{\n.reg .b64 x, y;\n.reg .b128 z;\nld.relaxed.gpu.global.b128 z, [%4];\nmov.b128 {x, y}, z;\nmov.b64 {%0, %1}, x;\nmov.b64 {%2, %3}, y;\n}\n" : "=r"(v.x), "=r"(v.y), "=r"(v.z), "=r"(v.w) : "l"(p) : "memory");
  return v;
}
template <int NAP, int N> __device__ __forceinline__ void ld_tag_wait(uint4 (&v)[N], const uint4* p, uint32_t tag) {
#pragma unroll 1
  for (int it = 0; it < FL_LIMIT; ++it) {
    uint32_t bad = 0;
#pragma unroll
    for (int j = 0; j < N; j++) v[j] = ld_tag(p + j * 32);
#pragma unroll
    for (int j = 0; j < N; j++) bad |= v[j].w ^ tag;
    if (__all_sync(0xffffffffu, bad == 0)) return;
    if (NAP) __nanosleep(NAP);
  }
  __trap();
}
__device__ __forceinline__ void prefetch_tmap(const CUtensorMap* m) { asm volatile("prefetch.tensormap [%0];" ::"l"(m) : "memory"); }
__device__ __forceinline__ void wgmma_fence() { asm volatile("wgmma.fence.sync.aligned;" ::: "memory"); }
__device__ __forceinline__ void wgmma_commit() { asm volatile("wgmma.commit_group.sync.aligned;" ::: "memory"); }
template <int N> __device__ __forceinline__ void wgmma_wait() { asm volatile("wgmma.wait_group.sync.aligned %0;" ::"n"(N) : "memory"); }
template <int R> __device__ __forceinline__ void reg_alloc() { asm volatile("setmaxnreg.inc.sync.aligned.u32 %0;" ::"n"(R)); }
template <int R> __device__ __forceinline__ void reg_dealloc() { asm volatile("setmaxnreg.dec.sync.aligned.u32 %0;" ::"n"(R)); }
__device__ __forceinline__ void bar_sync(int id, int n) { asm volatile("bar.sync %0, %1;" ::"r"(id), "r"(n) : "memory"); }
__device__ __forceinline__ void bar_arrive(int id, int n) { asm volatile("bar.arrive %0, %1;" ::"r"(id), "r"(n) : "memory"); }
__device__ __forceinline__ uint32_t ld_acquire(const uint32_t* p) { uint32_t v; asm volatile("ld.acquire.gpu.global.u32 %0, [%1];" : "=r"(v) : "l"(p) : "memory"); return v; }
__device__ __forceinline__ void st_release(uint32_t* p, uint32_t v) { asm volatile("st.release.gpu.global.u32 [%0], %1;" ::"l"(p), "r"(v) : "memory"); }
__device__ __forceinline__ uint4 ldcg16(const void* p) { uint4 v; asm volatile("ld.global.cg.v4.u32 {%0,%1,%2,%3}, [%4];" : "=r"(v.x), "=r"(v.y), "=r"(v.z), "=r"(v.w) : "l"(p) : "memory"); return v; }
__device__ __forceinline__ float ldcgf(const void* p) { float v; asm volatile("ld.global.cg.f32 %0, [%1];" : "=f"(v) : "l"(p) : "memory"); return v; }
__device__ __forceinline__ float2 lds8f(uint32_t a) { float2 v; asm volatile("ld.shared.v2.f32 {%0,%1}, [%2];" : "=f"(v.x), "=f"(v.y) : "r"(a)); return v; }
__device__ __forceinline__ float lds4f(uint32_t a) { float v; asm volatile("ld.shared.f32 %0, [%1];" : "=f"(v) : "r"(a)); return v; }
__device__ __forceinline__ uint32_t lds4(uint32_t a) { uint32_t v; asm volatile("ld.shared.u32 %0, [%1];" : "=r"(v) : "r"(a) : "memory"); return v; }
__device__ __forceinline__ void lds16f(uint32_t a, float& x, float& y, float& z, float& w) { asm volatile("ld.shared.v4.f32 {%0,%1,%2,%3}, [%4];" : "=f"(x), "=f"(y), "=f"(z), "=f"(w) : "r"(a) : "memory"); }
__device__ __forceinline__ void sts8f(uint32_t a, float x, float y) { asm volatile("st.shared.v2.f32 [%0], {%1,%2};" ::"r"(a), "f"(x), "f"(y) : "memory"); }
__device__ __forceinline__ void sts4f(uint32_t a, float x) { asm volatile("st.shared.f32 [%0], %1;" ::"r"(a), "f"(x) : "memory"); }
__device__ __forceinline__ void sts16(uint32_t a, uint32_t x, uint32_t y, uint32_t z, uint32_t w) { asm volatile("st.shared.v4.u32 [%0], {%1,%2,%3,%4};" ::"r"(a), "r"(x), "r"(y), "r"(z), "r"(w) : "memory"); }
__device__ __forceinline__ void lds16(uint32_t a, uint32_t& x, uint32_t& y, uint32_t& z, uint32_t& w) { asm volatile("ld.shared.v4.u32 {%0,%1,%2,%3}, [%4];" : "=r"(x), "=r"(y), "=r"(z), "=r"(w) : "r"(a) : "memory"); }
__device__ __forceinline__ uint32_t pack_bf16(float a, float b) { uint32_t r; asm("cvt.rn.bf16x2.f32 %0, %1, %2;" : "=r"(r) : "f"(b), "f"(a)); return r; }
__device__ __forceinline__ uint32_t pack_bf16_v(float a, float b) { uint32_t r; asm volatile("cvt.rn.bf16x2.f32 %0, %1, %2;" : "=r"(r) : "f"(b), "f"(a)); return r; }
__device__ __forceinline__ float bf_lo(uint32_t v) { return __uint_as_float(v << 16); }
__device__ __forceinline__ float bf_hi(uint32_t v) { return __uint_as_float(v & 0xffff0000u); }
constexpr float LOG2E = 1.4426950408889634f;
__device__ __forceinline__ float ex2f(float x) { float y; asm("ex2.approx.ftz.f32 %0, %1;" : "=f"(y) : "f"(x)); return y; }
__device__ __forceinline__ float tanhf_(float x) { float y; asm("tanh.approx.f32 %0, %1;" : "=f"(y) : "f"(x)); return y; }
__device__ __forceinline__ float rcpf(float x) { float y; asm("rcp.approx.ftz.f32 %0, %1;" : "=f"(y) : "f"(x)); return y; }
__device__ __forceinline__ float bf_round(float a) { return bf_lo(pack_bf16(a, 0.f)); }
__device__ __forceinline__ uint32_t movmat(uint32_t a) { uint32_t d; asm volatile("movmatrix.sync.aligned.m8n8.trans.b16 %0, %1;" : "=r"(d) : "r"(a)); return d; }
__device__ __forceinline__ void mma16816(float& d0, float& d1, float& d2, float& d3, uint32_t a0, uint32_t a1, uint32_t a2, uint32_t a3, uint32_t b0, uint32_t b1,
                                         float c0, float c1, float c2, float c3) {
  asm volatile("mma.sync.aligned.m16n8k16.row.col.f32.bf16.bf16.f32 {%0,%1,%2,%3}, {%4,%5,%6,%7}, {%8,%9}, {%10,%11,%12,%13};"
               : "=f"(d0), "=f"(d1), "=f"(d2), "=f"(d3) : "r"(a0), "r"(a1), "r"(a2), "r"(a3), "r"(b0), "r"(b1), "f"(c0), "f"(c1), "f"(c2), "f"(c3));
}
template <int N> __device__ __forceinline__ void copy_out(uint32_t a, void* base, uint32_t ofs, int pitch, int lane) {
  a += (lane >> 3) * 128 + (((lane ^ (lane >> 3)) & 7) << 4);
  char* const g = static_cast<char*>(base) + (ofs + (lane >> 3) * pitch + (lane & 7) * 16);
  uint32_t v[N][4];
  __syncwarp();
#pragma unroll
  for (int j = 0; j < N; j++) lds16((a ^ ((j & 1) * 64)) + j * 512, v[j][0], v[j][1], v[j][2], v[j][3]);
#pragma unroll
  for (int j = 0; j < N; j++) asm volatile("st.global.v4.u32 [%0], {%1, %2, %3, %4};" ::"l"(g + j * 4 * pitch), "r"(v[j][0]), "r"(v[j][1]), "r"(v[j][2]), "r"(v[j][3]) : "memory");
}
__device__ __forceinline__ int lane_now() { int v; asm volatile("mov.u32 %0, %%laneid;" : "=r"(v)); return v; }
__device__ __forceinline__ uint32_t uni(uint32_t x, int lane) { return __shfl_sync(0xffffffffu, x + lane, 0); }
__device__ __forceinline__ uint64_t dsc(uint32_t hi, uint32_t lo) { return ((uint64_t)hi << 32) | lo; }

#define R8(a, o) "+f"(a[o]), "+f"(a[o + 1]), "+f"(a[o + 2]), "+f"(a[o + 3]), "+f"(a[o + 4]), "+f"(a[o + 5]), "+f"(a[o + 6]), "+f"(a[o + 7])
#define R32(a, o) R8(a, o), R8(a, o + 8), R8(a, o + 16), R8(a, o + 24)
#define REG64 "%0, %1, %2, %3, %4, %5, %6, %7, %8, %9, %10, %11, %12, %13, %14, %15, %16, %17, %18, %19, %20, %21, %22, %23, %24, %25, %26, %27, %28, %29, %30, %31, " \
              "%32, %33, %34, %35, %36, %37, %38, %39, %40, %41, %42, %43, %44, %45, %46, %47, %48, %49, %50, %51, %52, %53, %54, %55, %56, %57, %58, %59, %60, %61, %62, %63"
#define REG96 REG64 ", %64, %65, %66, %67, %68, %69, %70, %71, %72, %73, %74, %75, %76, %77, %78, %79, %80, %81, %82, %83, %84, %85, %86, %87, %88, %89, %90, %91, %92, %93, %94, %95"
__device__ __forceinline__ void wgmma(float (&d)[64], uint64_t da, uint64_t db) {
  asm volatile("wgmma.mma_async.sync.aligned.m64n128k16.f32.bf16.bf16 {" REG64 "}, %64, %65, 1, 1, 1, 0, 1;\n"
               : R32(d, 0), R32(d, 32) : "l"(da), "l"(db));
}
__device__ __forceinline__ void wgmma(float (&d)[96], uint64_t da, uint64_t db) {
  asm volatile("wgmma.mma_async.sync.aligned.m64n192k16.f32.bf16.bf16 {" REG96 "}, %96, %97, 1, 1, 1, 0, 1;\n"
               : R32(d, 0), R32(d, 32), R32(d, 64) : "l"(da), "l"(db));
}
#define W8(a, o) "=f"(a[o]), "=f"(a[o + 1]), "=f"(a[o + 2]), "=f"(a[o + 3]), "=f"(a[o + 4]), "=f"(a[o + 5]), "=f"(a[o + 6]), "=f"(a[o + 7])
#define W32(a, o) W8(a, o), W8(a, o + 8), W8(a, o + 16), W8(a, o + 24)
__device__ __forceinline__ void wgmma_z(float (&d)[64], uint64_t da, uint64_t db) {
  asm volatile("wgmma.mma_async.sync.aligned.m64n128k16.f32.bf16.bf16 {" REG64 "}, %64, %65, 0, 1, 1, 0, 1;\n"
               : W32(d, 0), W32(d, 32) : "l"(da), "l"(db));
}
__device__ __forceinline__ void wgmma_z(float (&d)[96], uint64_t da, uint64_t db) {
  asm volatile("wgmma.mma_async.sync.aligned.m64n192k16.f32.bf16.bf16 {" REG96 "}, %96, %97, 0, 1, 1, 0, 1;\n"
               : W32(d, 0), W32(d, 32), W32(d, 64) : "l"(da), "l"(db));
}

__device__ __forceinline__ void wgmma_cs(float (&d)[4], uint64_t da, uint64_t db) {
  asm volatile("wgmma.mma_async.sync.aligned.m64n8k16.f32.bf16.bf16 {%0, %1, %2, %3}, %4, %5, 1, 1, 1, 1, 0;\n" : "+f"(d[0]), "+f"(d[1]), "+f"(d[2]), "+f"(d[3]) : "l"(da), "l"(db));
}
__device__ __forceinline__ void bulk_commit() { asm volatile("cp.async.bulk.commit_group;" ::: "memory"); }
__device__ __forceinline__ void bulk_wait() { asm volatile("cp.async.bulk.wait_group 0;" ::: "memory"); }
__device__ __forceinline__ void fence_bar_init() { asm volatile("fence.mbarrier_init.release.cluster;" ::: "memory"); }
__device__ __forceinline__ void prefetch_l2(const void* p) { asm volatile("prefetch.global.L2 [%0];" ::"l"(p) : "memory"); }

__device__ __forceinline__ uint32_t clock_now() { uint32_t v; asm volatile("mov.u32 %0, %%clock;" : "=r"(v)); return v; }
__device__ __forceinline__ void delay_until(uint32_t t0, int cycles) {
#pragma unroll 1
  for (int it = 0; it < 1000 && (int)(clock_now() - t0) < cycles; it++) __nanosleep(40);
}
__device__ __forceinline__ uint32_t ld_epoch(const uint32_t* p) { uint32_t v; asm volatile("ld.global.u32 %0, [%1];" : "=r"(v) : "l"(p) : "memory"); return v + 1; }
__device__ __forceinline__ void wait_flags(const uint32_t* f, uint32_t tag) {
#pragma unroll 1
  for (int it = 0; it < FL_LIMIT; ++it) if (__all_sync(0xffffffffu, (int)(ld_acquire(f) - tag) >= 0)) return;
  __trap();
}

__device__ __forceinline__ float2 ln_finish(float sum, float sq) {
  const float mean = sum * (1.f / D_), var = fmaxf(fmaf(-mean, mean, sq * (1.f / D_)), 0.f);
  const float mb = bf_round(mean);
  const float vb = bf_round(var);
  const float sd = bf_round(sqrtf(bf_round(vb + 1e-5f)));
  return make_float2(1.0f / sd, -mb);
}

__device__ __forceinline__ void helper_cta(const Params& P, Scratch* sc, int e, int wg, int w) {
  const int tid = threadIdx.x;
  if (tid == 256) {
#pragma unroll
    for (int i = 0; i < 16; i++) mbar_init(bar(i), 1);
    fence_bar_init();
  }
  if (tid < 64) sts16(SM_STG + tid * 16, 0x3f803f80u, 0x3f803f80u, 0x3f803f80u, 0x3f803f80u);
  fence_proxy_async_smem();
  __syncthreads();
  if (wg == 2) {
    if (w == 0) {
#pragma unroll 1
      for (int n = 0; n < 9 * 32; n++) {
        const int job = n >> 5;
        const uint32_t fb = bar(n & 7), dst = SB + (n & 7) * 24576;
        mbar_wait(bar(8 + (n & 7)), (n >> 3) + 1);
        if (elect_one()) {
          mbar_expect_tx(fb, job < 2 ? 24576 : 16384);
          tma4d(dst, &P.tm[job < 2 ? M_WQKV : M_W13], (e * 2 + (n & 1)) * 64, (n & 30) * 32, job < 2 ? job : job - 2, fb);
        }
        __syncwarp();
      }
    }
  } else {
    const uint32_t tag = ld_epoch(sc->epoch + NCTA + e);
    const int lane = tid & 31;
#pragma unroll 1
    for (int job = 0; job < 9; job++) {
      float s[3][4] = {};
#pragma unroll 1
      for (int n = job * 32 + wg; n < job * 32 + 32; n += 2) {
        mbar_wait(bar(n & 7), n >> 3);
        wgmma_fence();
        const uint32_t a = ((SB + (n & 7) * 24576) >> 4) + 0x2000000;
#pragma unroll
        for (int k = 0; k < 8; k++) wgmma_cs(s[k & 1], dsc(0x40000040u, a + (k & 1) * 512 + (k >> 1) * 128), dsc(0x40000040u, (SM_STG >> 4) + 0x10000));
        if (job < 2) {
          wgmma_fence();
#pragma unroll
          for (int k = 0; k < 4; k++) wgmma_cs(s[2], dsc(0x40000040u, a + 1024 + k * 128), dsc(0x40000040u, (SM_STG >> 4) + 0x10000));
        }
        wgmma_commit();
        wgmma_wait<0>();
        mbar_arrive_if(bar(8 + (n & 7)), (tid & 127) == 0);
      }
      if (!(lane & 2))
        st_tag(&sc->cs[job][e * 2 + wg][w * 16 + (lane & 1) * 8 + (lane >> 2)], __float_as_uint(lane & 1 ? s[0][2] : s[0][0]), __float_as_uint(lane & 1 ? s[1][2] : s[1][0]),
               __float_as_uint(lane & 1 ? s[2][2] : s[2][0]), tag);
      __syncwarp();
    }
    bar_sync(NB_INIT, 256);
    if (tid == 0) sc->epoch[NCTA + e] = tag;
  }
}

template <bool WEIGHTS>
__device__ __forceinline__ void producer(const Params& P, const uint2* tab, int nop, int lane, int c, int row, int par, uint32_t t_entry) {
  uint64_t pol;
  asm volatile("createpolicy.fractional.L2::evict_first.b64 %0, 1.0;" : "=l"(pol));
  __syncthreads();
  uint2 nx = __ldg(tab + lane), n2 = __ldg(tab + 32 + lane);
#pragma unroll 1
  for (int j = 1; j < FIRST; j++) {
    delay_until(t_entry, ST_T1 + (j - 1) * ST_D1);
    if (elect_one()) {
      mbar_expect_tx(bar(B_FULL) + 8 * j, WEIGHTS ? 24576 : 16384);
      if (WEIGHTS) tma4d(SB + j * 40960 + 16384, &P.tm[M_WQKV], c * 64, j * 64, 0, bar(B_FULL) + 8 * j);
      else tma3d(SB + j * 40960, &P.tm[M_X0], j * 64, row, par, bar(B_FULL) + 8 * j);
    }
    __syncwarp();
  }
  if (!WEIGHTS && lane == 0) {
#pragma unroll
    for (int j = 0; j < FIRST; j++) mbar_arrive(bar(B_EMPTY + 2 + j));
  }
  __syncwarp();
  auto word = [&](uint2 e) { return e.x + (((int)(e.y & 7) > c) + (e.y & 8 ? c : 0)) * 64; };
  uint32_t xn = __shfl_sync(0xffffffffu, word(nx), 0);
  const uint64_t maps = reinterpret_cast<uint64_t>(&P.tm[WEIGHTS ? M_WQKV : 0]);
  if ((uint32_t)maps > 0xfffff000u) __trap();
  const uint32_t sb = uni(SB, lane), bars = uni(BARS, lane), zero = uni(0, lane), mlo = uni((uint32_t)maps, lane), mhi = uni(maps >> 32, lane);
#pragma unroll 1
  for (int base = 0; base < nop; base += 32) {
    const uint2 e = nx;
    nx = n2;
    n2 = __ldg(tab + base + 64 + lane);
    const uint32_t xw = word(lane ? e : nx), bytes = e.y & 0xe000, eb = (e.y >> 6) & 0x78;
    const int arr = e.y & 16 ? lane + 1 : 0, solo = e.y & 32 ? lane + 1 : 0;
#pragma unroll 1
    for (int j = 1; j <= 32; j++) {
      const uint32_t x = xn;
      xn = __shfl_sync(0xffffffffu, xw, j);
#define OP_WAIT(X) "{\n.reg .pred pe, pa, pn, ps, pw;\n.reg .u32 it;\n" \
                "elect.sync _|pe, 0xffffffff;\nsetp.eq.u32 pa, %0, %1;\nsetp.ne.and.u32 pn, %2, 0, pe;\n" X \
                "mov.u32 it, 0;\n" \
                "WAIT_%=:\n" \
                "mbarrier.try_wait.parity.shared::cta.b64 pw, [%3 + %9], %4;\n" \
                "@pw bra.uni GO_%=;\n" \
                "add.u32 it, it, 1;\nsetp.lt.u32 pw, it, 0x10000;\n" \
                "@pw bra.uni WAIT_%=;\n" \
                "trap;\n" \
                "GO_%=:\n"
#define OP_ARGS "r"(arr), "r"(j), "r"(x & (1 << 12)), "r"((x >> 21) & 0x3f8), "r"(x >> 31), "r"(((x >> 15) & 0x1f8) | bars), "r"(bytes), "r"((x & 0x3e000) | sb), \
                "l"(dsc(mhi, mlo + (x & 0x38) * 16)), "n"(BARS), "r"(x & 0xfc0), "r"(x & 7)
      if (WEIGHTS)
        asm volatile(OP_WAIT("")
                     "@pn cp.async.bulk.tensor.4d.shared::cluster.global.mbarrier::complete_tx::bytes.L2::cache_hint [%7], [%8, {%12, %10, %13, %11}], [%5], %14;\n"
                     "@pa mbarrier.arrive.expect_tx.shared::cta.b64 _, [%5], %6;\n"
                     "}\n" ::OP_ARGS, "r"(c * 64), "r"(zero), "l"(pol) : "memory");
      else
        asm volatile(OP_WAIT(".reg .pred pf;\nsetp.ne.u32 pf, %11, 0;\nsetp.eq.u32 ps, %14, %1;\n")
                     "@pn cp.async.bulk.tensor.3d.shared::cluster.global.mbarrier::complete_tx::bytes [%7], [%8, {%10, %12, %13}], [%5];\n"
                     "@pf fence.proxy.async.shared::cta;\n"
                     "@pa mbarrier.arrive.expect_tx.shared::cta.b64 _, [%5], %6;\n"
                     "@ps mbarrier.arrive.shared::cta.b64 _, [%15 + %16];\n"
                     "}\n" ::OP_ARGS, "r"(row), "r"(par), "r"(solo), "r"(eb), "n"(bar(B_EMPTY)) : "memory");
    }
  }
}

template <int N, uint32_t LO> __device__ __forceinline__ void advance(uint32_t& x, uint32_t inc) {
  constexpr uint32_t LEN = (N == 192 ? NU : 24) * 512;
  x += inc; if (x >= LO + LEN) x -= LEN;
}
__device__ __forceinline__ bool full_test(uint32_t i8) {
  uint32_t ok;
  asm volatile("{\n.reg .pred p;\nmbarrier.test_wait.parity.shared::cta.b64 p, [%1 + %3], %2;\nselp.u32 %0, 1, 0, p;\n}\n" : "=r"(ok) : "r"(i8 & 0x78), "r"(i8 >> 7), "n"(bar(B_FULL)) : "memory");
  return ok;
}
__device__ __forceinline__ void full_wait(uint32_t i8) { mbar_wait(bar(B_FULL) + (i8 & 0x78), i8 >> 7); }
__device__ __forceinline__ void release(uint32_t i8, uint32_t p) {
  asm volatile("{\n.reg .pred q;\nsetp.ne.u32 q, %1, 0;\n@q mbarrier.arrive.shared::cta.b64 _, [%0 + %2];\n}\n" ::"r"(i8 & 0x78), "r"(p), "n"(bar(B_EMPTY)) : "memory");
}
template <int N, int RELK, int FIRSTK>
__device__ __forceinline__ bool kstep(float (&acc)[2][N / 2], uint32_t hiA, uint32_t hiB, uint32_t& a, uint32_t& b, uint32_t inc, uint32_t& i8, uint32_t x) {
  constexpr uint32_t MI = N == 192 ? 64 : 512;
  wgmma_fence();
  if (FIRSTK == 2) { wgmma_z(acc[0], dsc(hiA, a), dsc(hiB, b)); wgmma_z(acc[1], dsc(hiA, a + MI), dsc(hiB, b)); }
  else { wgmma(acc[0], dsc(hiA, a), dsc(hiB, b)); wgmma(acc[1], dsc(hiA, a + MI), dsc(hiB, b)); }
  i8 += 8;
  const bool ok = full_test(i8);
#pragma unroll
  for (int k = 1; k < 4; k++) {
    wgmma(acc[0], dsc(hiA, a + 2 * k), dsc(hiB, b + 128 * k)); wgmma(acc[1], dsc(hiA, a + MI + 2 * k), dsc(hiB, b + 128 * k));
    if (k == RELK || k == 3) wgmma_commit();
    if (k == 3) { advance<N, LO_A>(a, inc); advance<N, LO_B>(b, inc); }
    if (!FIRSTK && k == RELK) {
      wgmma_wait<1>();
      release(i8, x);
    }
  }
  return ok;
}
template <int MODE, int N, class F, class G>
__device__ __forceinline__ void mainloop(float (&acc)[2][N], uint32_t sig, int t, int wg, uint32_t& sp, F&& prepare, G&& first_half) {
  const uint32_t turn = bar(B_TURN) + 8 * (wg ^ 1);
  constexpr uint32_t hiA = MODE == 0 ? 0x40000080u : 0x40000040u, hiB = 0x40000040u;
  constexpr Seg S0 = GEN.s.seg[0];
  uint32_t i8 = S0.i8 & 0xffff, nxt = S0.end8 & 0xffff, a = S0.a, b = S0.b, inc = S0.end8 >> 16;
  if (MODE != 0 || t != 0) {
    if (MODE == 2 || (MODE == 0 ? t != 12 : t != 4 && t != 15)) mbar_wait(bar(B_TURN) + 8 * wg, (t - 1) >> 1);
    i8 = c_sched.seg[sp].i8 & 0xffff; nxt = c_sched.seg[sp].end8 & 0xffff; a = c_sched.seg[sp].a; b = c_sched.seg[sp].b; inc = c_sched.seg[sp].end8 >> 16;
  }
  uint32_t hiA_ = hiA, hiB_ = hiB;
  if (MODE == 2) { hiA_ = uni(hiA, lane_now()); hiB_ = uni(hiB, lane_now() * 2); }
  full_wait(i8);
  TL(t, 2);
  TS(i8, wg);
  bool ok = kstep<N * 2, 3, MODE == 2 ? 1 : 2>(acc, hiA_, hiB_, a, b, inc, i8, 0);
  if (MODE == 2 && (t == 2 || t == 13)) bar_sync(NB_OGO, 256);
#pragma unroll 1
  while (true) {
    uint32_t act;
    if (MODE != 2) { hiA_ = uni(hiA, lane_now()); hiB_ = uni(hiB, lane_now() * 2); }
#pragma unroll 1
    while (true) {
      if (!ok) full_wait(i8);
      TS(i8, wg);
      ok = kstep<N * 2, MODE == 0 ? RELQ : MODE == 1 ? RELG : RELD, 0>(acc, hiA_, hiB_, a, b, inc, i8, sig);
      if (__builtin_expect(i8 == nxt, 0)) {
        act = c_sched.seg[sp++].i8 >> 16;
        if (MODE == 1) mbar_arrive_if(turn, sig & (act >> 1));
        if (act & (MODE == 0 ? A_END | A_DRAIN | A_SYNC : MODE == 1 ? A_END | A_DRAIN : A_END)) break;
        nxt = c_sched.seg[sp].end8 & 0xffff; a = c_sched.seg[sp].a; b = c_sched.seg[sp].b;
        if (MODE == 1) inc = c_sched.seg[sp].end8 >> 16;
      }
    }
    if (MODE == 2 || (act & A_END)) break;
    nxt = c_sched.seg[sp].end8 & 0xffff; a = c_sched.seg[sp].a; b = c_sched.seg[sp].b;
    if (MODE == 1) inc = c_sched.seg[sp].end8 >> 16;
    if (PXE && MODE == 0 && (act & A_SYNC)) bar_arrive(NB_PX, 256);
    wgmma_wait<0>();
    if (!PXE && MODE == 0 && (act & A_SYNC)) bar_arrive(NB_PX, 256);
    release(i8 + 8, sig);
    i8 = c_sched.seg[sp].i8 & 0xffff;
    if (MODE == 1 || (act & A_WAIT)) mbar_wait(bar(B_TURN) + 8 * wg, (t - 1) >> 1);
    full_wait(i8);
    if (MODE == 0 && (act & A_SYNC)) bar_sync(NB_PY, 256);
    TS(i8, wg);
    ok = kstep<N * 2, 3, 1>(acc, hiA, hiB, a, b, inc, i8, 0);
  }
  if (MODE != 1) {
    constexpr int TL_ = MODE == 0 ? TAILQ : TAIL;
    uint32_t ta[TL_], tb[TL_];
#pragma unroll
    for (int x = 0; x < TL_; x++) {
      full_wait(i8 + 8 * x);
      TS(i8 + 8 * x, wg);
      ta[x] = a; tb[x] = b;
      advance<N * 2, LO_A>(a, inc); advance<N * 2, LO_B>(b, inc);
    }
    if (TURN_L == 0) mbar_arrive_if(turn, sig);
#pragma unroll
    for (int h = 0; h < 2; h++) {
      const int mi = MODE == 0 ? 1 - h : h;
      wgmma_fence();
#pragma unroll
      for (int x = 0; x < TL_; x++)
#pragma unroll
        for (int k = 0; k < 4; k++) wgmma(acc[mi], dsc(hiA, ta[x] + mi * (MODE == 0 ? 64 : 512) + 2 * k), dsc(hiB, tb[x] + 128 * k));
      wgmma_commit();
      if (TL_ > 1 && h == 0) { wgmma_wait<1>(); release(i8 + 8, sig); prepare(); }
    }
    if (TURN_L == 1) mbar_arrive_if(turn, sig);
    if (TL_ == 1) { wgmma_wait<2>(); release(i8 + 8, sig); prepare(); }
    wgmma_wait<1>();
    first_half();
    wgmma_wait<0>();
#pragma unroll
    for (int x = 0; x < TL_; x++) release(i8 + 16 + 8 * x, sig);
  } else {
    prepare();
    wgmma_wait<0>();
    release(i8 + 8, sig);
  }
}

template <int SWAP, int BY_SM>
__global__ void __launch_bounds__(384, 1) fused_kernel(Scratch* sc, const Ops* ops, const bf16* x0, bf16* out, const __grid_constant__ Params P) {
  extern __shared__ __align__(1024) uint8_t smem_raw[];
  const int tid = threadIdx.x;
  if (tid == 0) prefetch_tmap(&P.tm[M_X0]);
  if (tid == 128) prefetch_tmap(&P.tm[M_WQKV]);
  if (tid == 256) { mbar_init(bar(B_FULL), 2); fence_bar_init(); fence_proxy_async_smem(); }
  const int wg = __shfl_sync(0xffffffffu, tid >> 7, 0);
  const int w = __shfl_sync(0xffffffffu, (tid >> 5) & 3, 0);
  const int lane = tid & 31;
  const uint32_t t_entry = clock_now();
  int b = blockIdx.x, c = ((b >> 2) & 7) ^ (((b >> 5) & 1) * 7), mr = b & 3;
  if (BY_SM) {
    uint32_t smid; asm volatile("mov.u32 %0, %%smid;" : "=r"(smid));
    const int tp = smid >> 1;
    const int q7 = (tp - 32) * 37 >> 8;
    const int v0 = (tp & 7) * 8 + (tp >> 3), v1 = tp * 8 - 244 - q7 * 55, v2 = tp < 62 ? tp + 4 : tp - 58;
    b = (tp < 32 ? v0 : tp < 60 ? v1 : v2) * 2 + (smid & 1);
    c = (b & 1) | ((b >> 1) & 2) | ((b >> 2) & 4); mr = ((b >> 1) & 1) | ((b >> 2) & 2);
  }
  const int mg = (b >> 5) & 3, m = mg * 4 + mr;
  const int row0 = (m & 7) * 128, par = m >> 3;
  if (__builtin_expect(b >= NCTA, 0)) { helper_cta(P, sc, b - NCTA, wg, w); return; }
  if (wg == 2 && w == 0) {
    if (elect_one()) {
      tma3d(SB, &P.tm[M_X0], 0, row0, par, bar(B_FULL));
      tma4d(SB + 16384, &P.tm[M_WQKV], c * 64, 0, 0, bar(B_FULL));
      mbar_expect_tx(bar(B_FULL), 40960);
      mbar_arrive(bar(B_FULL));
    }
    __syncwarp();
    TLW(0, 1);
  }
  if (__builtin_expect(wg == 2, 0)) {
    reg_dealloc<40>();
    if (w < 2) {
      if (w == 0) producer<false>(P, ops->a, NOP0, lane, c, row0, par, t_entry);
      else producer<true>(P, ops->b, NOP1, lane, c, row0, par, t_entry);
    } else if (w == 2) {
      if (smem_u32(smem_raw) != SB) __trap();
      if (lane == 0) {
#pragma unroll
        for (int x = 1; x < B_CS; x++) mbar_init(bar(x), x < B_SIG ? 2 : x <= B_STAT ? 4 : 1);
        fence_bar_init();
        fence_proxy_async_smem();
      }
      __syncthreads();
      const uint32_t tag = ld_epoch(sc->epoch + b);
      uint32_t* const flag = sc->flags[m * 8 + c];
      if (lane < 4) asm volatile("st.relaxed.gpu.global.v4.u32 [%0], {%1, %1, %1, %1};" ::"l"(flag + lane * 4), "r"(tag * 32 - 1) : "memory");
      __syncwarp();
      int ev = 0;
      uint32_t t_st = t_entry;
#pragma unroll 1
      for (int t = 0; t < 21; t++) {
        const int i = t >= 11 ? t - 11 : t;
        const bool od = i == 2 || i == 10;
        const uint32_t sig = c_sched.task[t].sig;
        const uint32_t pf = i == 0 ? 1 << M_OL | 1 << M_O | 1 << M_WO : i == 1 ? 1 << M_O24 | 1 << M_W13 | 1 << M_W13P | 1 << M_YL | 1 << M_Y : i == 3 ? 1 << M_HL :
                            i == 7 ? 1 << M_H | 1 << M_W2 : i == 10 ? 1 << M_WQKV | 1 << M_YL | 1 << M_Y : 0;
        if ((pf >> lane) & 1) prefetch_tmap(&P.tm[lane]);
        __syncwarp();
#pragma unroll 1
        for (int x = i == 1 || od ? 0 : 1; x < (i == 1 ? 1 : 2); x++) {
          if (x == 0) {
            if (i == 1) {
              mbar_wait(bar(B_SIG), sig);
              fence_proxy_async_smem();
#pragma unroll 1
              for (int r = 8; r < 128; r += 32) tma3d_store(&P.tm[M_O24], SM_STG + r * 128, (8 + c) * 64, row0 + r, par);
            }
            mbar_wait(bar(B_SIG + 1), sig >> 1);
          } else {
            const CUtensorMap* mp = &P.tm[i == 0 ? M_OL : od ? M_YL : M_HL];
            const uint32_t src = od ? SB + ((c_sched.task[t].stg >> 8) & 31) * 8192 : SM_STG;
            const int col = ((od ? 1 : i ? i - 3 : 0) * 8 + c) * 64, gap = i == 0 ? GAP_O : od ? GAP_Y : i == 9 ? GAP_H6 : GAP_H;
            const int nr = i && !od ? 64 : 128;
#pragma unroll 1
            for (int r0 = 0; r0 < 128; r0 += nr) {
              const int s = od ? 3 : i ? r0 >> 6 : 1;
              mbar_wait(bar(B_SIG) + 8 * s, sig >> s);
              if ((HOLD & 16) && od) mbar_wait(bar(B_DEP - 1) + 8 * ev, 0);
              fence_proxy_async_smem();
              const uint32_t now = clock_now();
              if ((int)(now - t_st) > 0) t_st = now;
#pragma unroll 1
              for (int r = r0; r < r0 + nr; r += PROWS) {
                delay_until(t_st, 0);
                t_st += gap;
                tma3d_store(mp, src + r * 128, col, row0 + r, par);
              }
            }
          }
          if (elect_one()) {
            if (x || (i == 1)) { bulk_commit(); bulk_wait(); }
            if (x || !od) mbar_arrive(od ? bar(B_SF) : bar(B_FREE));
            if (i < 3 || i > 6) {
              asm volatile("fence.proxy.async.global;" ::: "memory");
              if (CNT && od && x == 0) asm volatile("red.release.gpu.global.add.u32 [%0], 1;" ::"l"(&sc->cnt[mg][ev]) : "memory");
              else st_release(flag, tag * 32 + ev);
              mbar_arrive(bar(B_PUB) + 8 * ev);
            }
          }
          __syncwarp();
          if (i < 3 || i > 6) ev++;
          if (x == 0 || !od) TLW(t, 4);
        }
      }
      if (lane == 0) sc->epoch[b] = tag;
    } else {
      if (lane == 0) {
#pragma unroll
        for (int x = B_CS; x < B_N; x++) mbar_init(bar(x), x == B_RF ? 4 : 1);
        fence_bar_init();
      }
      __syncthreads();
      const uint32_t tag = ld_epoch(sc->epoch + b);
      delay_until(t_entry, WARM_T);
      asm volatile("st.shared.u32 [%0], %1;" ::"r"(SM_TAG + 4), "r"(reinterpret_cast<const uint32_t*>(&c_sched)[min(lane * 16, (int)sizeof(Sched) / 4 - 1)]) : "memory");
      int ncs = 0;
#pragma unroll 1
      for (int it = 0; it < 20; it++) {
        const int l = it >= 11, i = it - l * 11, e = i < 2 ? 0 : i - 2, ev = l * E_N + e;
#pragma unroll 1
        for (; ncs < (it < 2 ? it + 1 : it < 6 ? 2 : 9); ncs++) {
          uint4 v[2];
          ld_tag_wait<200>(v, &sc->cs[ncs][c][lane], tag);
          const uint32_t a = SM_CS + (ncs < 2 ? ncs * 768 : 512 + ncs * 512) + ((lane & 17) | (lane & 6) << 1 | (lane & 8) >> 2) * 4;
#pragma unroll
          for (int j = 0; j < 2; j++) {
            sts4f(a + j * 128, __uint_as_float(v[j].x)); sts4f(a + j * 128 + 256, __uint_as_float(v[j].y));
            if (ncs < 2) sts4f(a + j * 128 + 512, __uint_as_float(v[j].z));
          }
          mbar_arrive_warp(bar(B_CS) + 8 * ncs);
        }
        if (i == 0 || i == 2) {
          const int u = l * 2 + (i >> 1);
          uint4 v[6] = {};
          mbar_wait(bar(B_QT), u);
          if (m & 7) ld_tag_wait<0>(v, &sc->halo[u][m - 1][c][0][lane], tag);
          const uint32_t xa = xch(i, 0) + lane * 16;
          sts16(xa, v[0].x, v[0].y, v[0].z, v[1].x); sts16(xa + 512, v[1].y, v[1].z, v[2].x, v[2].y);
          sts16(xa + 1024, v[2].z, v[3].x, v[3].y, v[3].z); sts16(xa + 1536, v[4].x, v[4].y, v[4].z, v[5].x);
          if (lane < 4) sts16(stat(l * 2) - 64 + lane * 16, v[5].y, 0, v[5].z, 0);
          mbar_arrive_warp(bar(B_XCH));
          continue;
        }
        mbar_wait(bar(B_PUB) + 8 * ev, 0);
        if (CNT) {
          const bool all = e == E_YA || e == E_XA;
          wait_flags(all ? &sc->cnt[mg][ev] : sc->flags[m * 8 + (lane & 7)], tag * 32 + (all ? 0 : ev));
        } else wait_flags(sc->flags[(DEP32 >> e) & 1 ? mg * 32 + lane : m * 8 + (lane & 7)], tag * 32 + ev);
        mbar_arrive_warp(bar(B_DEP) + 8 * ev);
        if (e == E_YB || e == E_XB) {
          const int p = e == E_XB ? 1 : l * 2;
          if (elect_one()) {
            mbar_expect_tx(bar(B_SF + 1), 8192);
            asm volatile("cp.async.bulk.shared::cluster.global.mbarrier::complete_tx::bytes [%0], [%1], 8192, [%2];" ::"r"(SM_STG), "l"(&sc->stat[p][m][0][0]), "r"(bar(B_SF + 1)) : "memory");
          }
          __syncwarp();
          mbar_wait(bar(B_SF + 1), p);
#pragma unroll 1
          for (int h = 0; h < 2; h++) {
            float s0 = 0.f, q0 = 0.f, s1 = 0.f, q1 = 0.f;
#pragma unroll 4
            for (int j = 0; j < 8; j++) {
              float x0, x1, x2, x3;
              lds16f(SM_STG + j * 1024 + h * 512 + lane * 16, x0, x1, x2, x3);
              s0 += x0; q0 += x1; s1 += x2; q1 += x3;
            }
            const float2 r0 = ln_finish(s0, q0), r1 = ln_finish(s1, q1);
            sts16(stat(p + 1) + (h * 64 + lane * 2) * 8, __float_as_uint(r0.x), __float_as_uint(r0.y), __float_as_uint(r1.x), __float_as_uint(r1.y));
          }
          mbar_arrive_warp(bar(B_STAT) + 8 * (p + 1));
        }
      }
    }
  } else {
    const int tw = tid & 127;
    reg_alloc<232>();
    uint32_t sig;
    asm volatile("mov.u32 %0, %1;" : "=r"(sig) : "r"((uint32_t)(tw == 0)));
    __syncthreads();

    if (wg == 1) {
      const uint32_t tag = ld_epoch(sc->epoch + b);
      uint4* const mine = &sc->stat0[m][c * 16 + w * 4 + (lane >> 3)];
      if (WARM_X && (lane & 7) == 0) st_tag(mine, 0, 0, 0, 0);
      __syncwarp();
      delay_until(t_entry, ST_ROWS);
      const bf16* xr = x0 + (size_t)((row0 + c * 16 + w * 4 + (lane >> 3)) * 2 + par) * D_ + (lane & 7) * 8;
      float sum = 0.f, sq = 0.f;
#pragma unroll 1
      for (int j0 = 0; j0 < 16; j0 += 4) {
        uint4 xv[4];
#pragma unroll
        for (int j = 0; j < 4; j++) xv[j] = ldcg16(xr + (j0 + j) * 64);
#pragma unroll
        for (int j = 0; j < 4; j++) {
          const uint32_t x[4] = {xv[j].x, xv[j].y, xv[j].z, xv[j].w};
#pragma unroll
          for (int e = 0; e < 8; e++) { const float d = e & 1 ? bf_hi(x[e >> 1]) : bf_lo(x[e >> 1]); sum += d; sq = fmaf(d, d, sq); }
        }
      }
#pragma unroll
      for (int o = 4; o > 0; o >>= 1) { sum += __shfl_xor_sync(0xffffffffu, sum, o); sq += __shfl_xor_sync(0xffffffffu, sq, o); }
      const float2 fin = ln_finish(sum, sq);
      if ((lane & 7) == 0) st_tag(mine, __float_as_uint(fin.x), __float_as_uint(fin.y), 0, tag);
      __syncwarp();
      TL(22, 5);
      uint4 v[1];
      ld_tag_wait<200>(v, &sc->stat0[m][tw], tag);
      sts8f(stat(0) + tw * 8, __uint_as_float(v[0].x), __uint_as_float(v[0].y));
      if (tw == 0) { asm volatile("st.shared.u32 [%0], %1;" ::"r"(SM_TAG), "r"(tag) : "memory"); sts16(SM_ZERO, 0, 0, 0, 0); }
      mbar_arrive_warp(bar(B_STAT));
      TL(22, 6);
    }

    uint32_t sp = wg * NSEG;
#pragma unroll 1
    for (int t = wg; t < 22; t += 2) {
      const int l = t >= 11, i = t - l * 11;
      if (t == 0) TL(t, 0);
      if (i < 2) {
        float acc[2][96];
        if (WARM_X && w == 3 && (m & 7) < 7) {
#pragma unroll
          for (int j = 0; j < 6; j++) st_tag(&sc->halo[l * 2 + i][m][c][j][lane_now()], 0, 0, 0, 0);
        }
        uint32_t Q[4][8], K[4][8], V[4][8], sta, csa;
        float2 st[4];
        auto fix = [&](int g, int j, float2 cs) {
          const int mi = g & 1, half = g >> 1;
          return pack_bf16_v(fmaf(st[g].y, cs.x, acc[mi][j * 4 + half * 2]), fmaf(st[g].y, cs.y, acc[mi][j * 4 + half * 2 + 1]));
        };
        mainloop<0>(acc, sig, t, wg, sp, [&]() {
          const int lane = lane_now();
          mbar_wait(bar(B_FREE), l * 9 + i - 1);
          mbar_wait(bar(B_STAT) + l * 16, 0);
          mbar_wait(bar(B_CS) + i * 8, 0);
          sta = stat(l * 2) + w * 256;
          csa = SM_CS + i * 768 + (lane & 3) * 16;
          st[1] = lds8f(sta + (8 + (lane >> 2)) * 8); st[3] = lds8f(sta + (24 + (lane >> 2)) * 8);
        }, [&]() {
          const int lane = lane_now();
          mbar_arrive_if(bar(B_QT), sig);
#pragma unroll
          for (int j = 0; j < 8; j += 2) {
            float2 c0, c1;
            lds16f(csa + (16 + j) * 32, c0.x, c0.y, c1.x, c1.y);
            V[3][j] = movmat(fix(3, 16 + j, c0)); V[3][j + 1] = movmat(fix(3, 17 + j, c1));
            lds16f(csa + (8 + j) * 32, c0.x, c0.y, c1.x, c1.y);
            K[3][j] = fix(3, 8 + j, c0); K[3][j + 1] = fix(3, 9 + j, c1);
          }
          if (w < 3) {
            const uint32_t xa = xch(i, w + 1) + lane * 16;
            sts16(xa, K[3][0], K[3][1], K[3][2], K[3][3]); sts16(xa + 512, K[3][4], K[3][5], K[3][6], K[3][7]);
            sts16(xa + 1024, V[3][0], V[3][1], V[3][2], V[3][3]); sts16(xa + 1536, V[3][4], V[3][5], V[3][6], V[3][7]);
            mbar_arrive_warp(bar(B_XCH));
          } else if ((m & 7) < 7) {
            const uint32_t tag = lds4(SM_TAG), r0 = lds4(sta + (24 + 2 * (lane & 3)) * 8), r1 = lds4(sta + (25 + 2 * (lane & 3)) * 8);
            uint4* const p = &sc->halo[l * 2 + i][m][c][0][lane];
            st_tag(p, K[3][0], K[3][1], K[3][2], tag); st_tag(p + 32, K[3][3], K[3][4], K[3][5], tag); st_tag(p + 64, K[3][6], K[3][7], V[3][0], tag);
            st_tag(p + 96, V[3][1], V[3][2], V[3][3], tag); st_tag(p + 128, V[3][4], V[3][5], V[3][6], tag); st_tag(p + 160, V[3][7], r0, r1, tag);
          }
        });
        TL(t, 3);
        const int lane = lane_now(), q = lane & 3, r8 = lane >> 2;
        st[0] = lds8f(sta + r8 * 8); st[2] = lds8f(sta + (16 + r8) * 8);
#pragma unroll
        for (int j0 = 22; j0 >= 0; j0 -= 2) {
          float2 cs[2];
          lds16f(csa + j0 * 32, cs[0].x, cs[0].y, cs[1].x, cs[1].y);
#pragma unroll
          for (int j = j0; j < j0 + 2; j++)
#pragma unroll
            for (int g = 0; g < (j < 8 ? 4 : 3); g++) {
              const uint32_t pk = fix(g, j, cs[j - j0]);
              if (j < 8) Q[g][j] = pk; else if (j < 16) K[g][j - 8] = pk; else V[g][j - 16] = movmat(pk);
            }
        }
        const bool up0 = (2 * q) > r8, up1 = (2 * q + 1) > r8;
        const uint32_t mskP = (up0 ? 0xffffu : 0u) | (up1 ? 0xffff0000u : 0u);
        TL(t, 5);
        uint32_t Kp[8] = {}, Vp[8] = {}, PS[2][4] = {}, PP[2][4] = {};
        float sS[2][4][2], sP[2][4][2], O[2][4][4][2], z0, z1, z2, z3;
        auto receive = [&]() {
          const uint32_t xa = xch(i, w) + lane * 16;
          mbar_wait(bar(B_XCH), i);
          lds16(xa, Kp[0], Kp[1], Kp[2], Kp[3]); lds16(xa + 512, Kp[4], Kp[5], Kp[6], Kp[7]);
          lds16(xa + 1024, Vp[0], Vp[1], Vp[2], Vp[3]); lds16(xa + 1536, Vp[4], Vp[5], Vp[6], Vp[7]);
          TL(i == 0 ? 22 : 23, t < 11 ? 3 : 4);
        };
        auto score0 = [&]() {
          float dm0, dm1;
#pragma unroll
          for (int h = 0; h < 2; h++) mma16816(sP[h][0][0], sP[h][0][1], dm0, dm1, Q[0][h * 4], Q[0][h * 4], Q[0][h * 4 + 1], Q[0][h * 4 + 1], Kp[h * 4], Kp[h * 4 + 1], z0, z1, z2, z3);
#pragma unroll
          for (int h = 0; h < 2; h++)
            mma16816(sP[h][0][0], sP[h][0][1], dm0, dm1, Q[0][h * 4 + 2], Q[0][h * 4 + 2], Q[0][h * 4 + 3], Q[0][h * 4 + 3], Kp[h * 4 + 2], Kp[h * 4 + 3], sP[h][0][0], sP[h][0][1], 0.f, 0.f);
        };
        auto softmax = [&](int g) {
          const float rk0 = lds4f(sta + (g * 8 + 2 * q - (up0 ? 8 : 0)) * 8), rk1 = lds4f(sta + (g * 8 + 2 * q + 1 - (up1 ? 8 : 0)) * 8);
          const float f = st[g].x * (0.17677669529663687f * LOG2E), f0 = f * rk0, f1 = f * rk1;
          const bool noprev = g == 0 && (m & 7) == 0 && w == 0;
#pragma unroll
          for (int h = 0; h < 2; h++) {
            float v0 = (up0 ? sP[h][g][0] : sS[h][g][0]) * f0, v1 = (up1 ? sP[h][g][1] : sS[h][g][1]) * f1;
            if (noprev && up0) v0 = -1e9f * LOG2E;
            if (noprev && up1) v1 = -1e9f * LOG2E;
            float mx = fmaxf(v0, v1);
            mx = fmaxf(mx, __shfl_xor_sync(0xffffffffu, mx, 1)); mx = fmaxf(mx, __shfl_xor_sync(0xffffffffu, mx, 2));
            const float e0 = ex2f(v0 - mx), e1 = ex2f(v1 - mx);
            float sum = e0 + e1;
            sum += __shfl_xor_sync(0xffffffffu, sum, 1); sum += __shfl_xor_sync(0xffffffffu, sum, 2);
            const float inv = rcpf(sum);
            const uint32_t pk = pack_bf16_v(e0 * inv * rk0, e1 * inv * rk1);
            PS[h][g] = pk & ~mskP; PP[h][g] = pk & mskP;
          }
        };
        const uint32_t sa = SM_STG + (w * 32 + (lane & 7)) * 128 + (((lane >> 3) ^ (lane & 7)) << 4);
        auto stage = [&](int g) {
#pragma unroll
          for (int h = 0; h < 2; h++)
            stsm4((sa ^ (h * 64)) + g * 1024, pack_bf16(O[h][g][0][0], O[h][g][0][1]), pack_bf16(O[h][g][1][0], O[h][g][1][1]),
                  pack_bf16(O[h][g][2][0], O[h][g][2][1]), pack_bf16(O[h][g][3][0], O[h][g][3][1]));
        };
        if (i == 0) { receive(); bar_sync(NB_PX, 256); }
        lds16f(SM_ZERO, z0, z1, z2, z3);
#pragma unroll
        for (int h = 0; h < 2; h++) {
          float dm0, dm1;
          const int j0 = h * 4;
#pragma unroll
          for (int g = 0; g < 3; g++) mma16816(sS[h][g][0], sS[h][g][1], sP[h][g + 1][0], sP[h][g + 1][1], Q[g][j0], Q[g + 1][j0], Q[g][j0 + 1], Q[g + 1][j0 + 1], K[g][j0], K[g][j0 + 1], z0, z1, z2, z3);
          mma16816(sS[h][3][0], sS[h][3][1], dm0, dm1, Q[3][j0], Q[3][j0], Q[3][j0 + 1], Q[3][j0 + 1], K[3][j0], K[3][j0 + 1], z0, z1, z2, z3);
        }
#pragma unroll
        for (int h = 0; h < 2; h++) {
          float dm0, dm1;
          const int j0 = h * 4 + 2;
#pragma unroll
          for (int g = 0; g < 3; g++) mma16816(sS[h][g][0], sS[h][g][1], sP[h][g + 1][0], sP[h][g + 1][1], Q[g][j0], Q[g + 1][j0], Q[g][j0 + 1], Q[g + 1][j0 + 1], K[g][j0], K[g][j0 + 1],
                                               sS[h][g][0], sS[h][g][1], sP[h][g + 1][0], sP[h][g + 1][1]);
          mma16816(sS[h][3][0], sS[h][3][1], dm0, dm1, Q[3][j0], Q[3][j0], Q[3][j0 + 1], Q[3][j0 + 1], K[3][j0], K[3][j0 + 1], sS[h][3][0], sS[h][3][1], 0.f, 0.f);
        }
        if (i == 0) {
          score0();
          bar_arrive(NB_PY + ((__float_as_uint(sP[0][0][0]) | __float_as_uint(sP[1][0][0])) & __float_as_uint(z0)), 256);
          softmax(0);
        }
#pragma unroll
        for (int g = 1; g < 4; g++) softmax(g);
        TL(23, i == 0 ? (t < 11 ? 5 : 6) : 7);
        if (i == 0) bar_sync(NB_PX + ((PS[0][1] | PS[0][2] | PS[0][3] | PS[1][1] | PS[1][2] | PS[1][3]) & __float_as_uint(z0)), 256);
        lds16f(SM_ZERO, z0, z1, z2, z3);
#pragma unroll
        for (int x = 0; x < 8; x++) {
          const int h = x >> 2, j = x & 3;
          mma16816(O[h][1][j][0], O[h][1][j][1], O[h][2][j][0], O[h][2][j][1], PS[h][1], PP[h][2], PP[h][1], 0u, V[1][x], V[0][x], z0, z1, z2, z3);
        }
#pragma unroll
        for (int x = 0; x < 8; x++) {
          const int h = x >> 2, j = x & 3;
          mma16816(O[h][3][j][0], O[h][3][j][1], O[h][2][j][0], O[h][2][j][1], PS[h][3], 0u, PP[h][3], PS[h][2], V[3][x], V[2][x], 0.f, 0.f, O[h][2][j][0], O[h][2][j][1]);
        }
        if (i) {
          stage(1); stage(2); stage(3);
          mbar_arrive_warp(bar(B_SIG));
          receive(); score0(); softmax(0);
        }
        {
          uint32_t y = 0;
#pragma unroll
          for (int x = 0; x < 8; x++) {
            const int h = x >> 2, j = x & 3;
            float dm0, dm1;
            mma16816(O[h][0][j][0], O[h][0][j][1], dm0, dm1, PS[h][0], 0u, PP[h][0], 0u, V[0][x], Vp[x], z0, z1, z2, z3);
            y |= __float_as_uint(O[h][0][j][0]);
          }
          if (i == 0) { bar_arrive(NB_PY + (y & __float_as_uint(z0)), 256); stage(1); stage(2); stage(3); }
        }
        stage(0);
        if (i) copy_out<2>(SM_STG + w * 4096, sc->o, ((m * 128 + w * 32) * D_ + (8 + c) * 64) * 2, D_ * 2, lane);
        mbar_arrive_warp(bar(B_SIG + 1));
        if (i) bar_arrive(NB_OGO, 256);
        TL(t, 6);
      } else if (i > 2 && i < 10) {
        float acc[2][64];
        float2 cs[16];
        float c1[4], vr[4];
        uint32_t so, sta;
        mainloop<1>(acc, sig, t, wg, sp, [&]() {
          const int lane = lane_now();
          so = SM_STG + (w * 16 + (lane & 7)) * 128 + (((lane >> 3) ^ (lane & 7)) << 4);
          sta = stat(l * 2 + 1) + (w * 16 + (lane >> 2)) * 8;
          mbar_wait(bar(B_STAT + 1) + l * 16, 0);
          mbar_wait(bar(B_CS - 1) + 8 * i, 0);
#pragma unroll
          for (int j = 0; j < 16; j += 2) lds16f(SM_CS + i * 512 + (lane & 3) * 16 + j * 32, cs[j].x, cs[j].y, cs[j + 1].x, cs[j + 1].y);
#pragma unroll
          for (int j = 0; j < 4; j++) {
            const float r = lds4f(sta + (j >> 1) * 512 + (j & 1) * 64);
            if (TANH) { vr[j] = r; c1[j] = r * 0.5f; }
            else {
              asm volatile("rcp.approx.ftz.f32 %0, %1;" : "=f"(vr[j]) : "f"(r * r));
              c1[j] = r * -LOG2E;
            }
          }
          mbar_wait(bar(B_FREE), l * 9 + i - 2);
        }, []() {});
        TL(t, 3);
        float mn[8];
#pragma unroll
        for (int x = 0; x < GLA; x++) mn[x] = __uint_as_float(lds4(sta + 4 + (x >> 2) * 512 + ((x >> 1) & 1) * 64));
#pragma unroll
        for (int x = 0; x < 8; x++) {
          const int mi = x >> 2, half = (x >> 1) & 1, g = x & 1;
          const float var = vr[x >> 1], cc = c1[x >> 1];
          uint32_t v[4];
#pragma unroll
          for (int j = 0; j < 4; j++) {
            const int jg = g * 4 + j + SWAP * 8, ju = jg ^ 8;
            const float2 cg = cs[jg], cu = cs[ju];
            const float g0 = fmaf(mn[x], cg.x, acc[mi][jg * 4 + half * 2]), g1 = fmaf(mn[x], cg.y, acc[mi][jg * 4 + half * 2 + 1]);
            const float u0 = fmaf(mn[x], cu.x, acc[mi][ju * 4 + half * 2]), u1 = fmaf(mn[x], cu.y, acc[mi][ju * 4 + half * 2 + 1]);
            if (TANH) {
              const float a0 = g0 * cc, a1 = g1 * cc;
              const float s0 = fmaf(a0, tanhf_(a0), a0), s1 = fmaf(a1, tanhf_(a1), a1);
              v[j] = TANH == 2 ? pack_bf16(s0 * u0, s1 * u1) : pack_bf16(s0 * u0 * var, s1 * u1 * var);
            } else {
              const float r0 = rcpf(fmaf(ex2f(g0 * cc), var, var)), r1 = rcpf(fmaf(ex2f(g1 * cc), var, var));
              v[j] = pack_bf16(g0 * u0 * r0, g1 * u1 * r1);
            }
          }
          stsm4((so ^ (g * 64)) + (mi * 64 + half * 8) * 128, v[0], v[1], v[2], v[3]);
          if ((x & 3) == 3) mbar_arrive_warp(bar(B_SIG + mi));
          if (x + GLA < 8) mn[x + GLA] = __uint_as_float(lds4(sta + 4 + ((x + GLA) >> 2) * 512 + (((x + GLA) >> 1) & 1) * 64));
        }
        TL(t, 6);
      } else {
        float acc[2][64], rsc[4];
        {
          const int lane = lane_now();
          const uint32_t e = c_sched.task[t].res;
          const uint32_t ra = SB + (w * 16 + (lane & 7)) * 128 + (((lane >> 3) ^ (lane & 7)) << 4);
          float sd[4];
#pragma unroll
          for (int j = 0; j < 4; j++) {
            rsc[j] = i == 10 ? lds4f(stat(l * 2 + 1) + ((j >> 1) * 64 + w * 16 + (j & 1) * 8 + (lane >> 2)) * 8) : 1.f;
            sd[j] = rcpf(rsc[j]);
          }
          const uint32_t zero = lds4(SM_ZERO);
          mbar_wait(bar(B_RES), i == 10);
          uint32_t dep[16];
#pragma unroll
          for (int x = 0; x < 16; x++) {
            const int mi = x >> 3, half = (x >> 2) & 1, g = x & 3;
            uint32_t v[4];
            ldsm4(((e >> ((g >> 1) * 8)) & 31) * 8192 + ((ra ^ ((g & 1) * 64)) | (RLA && x >= RLA ? dep[x - RLA] : 0)) + (mi * 64 + half * 8) * 128, v[0], v[1], v[2], v[3]);
#pragma unroll
            for (int j = 0; j < 4; j++) {
              asm volatile("shl.b32 %0, %1, 16;" : "=f"(acc[mi][(g * 4 + j) * 4 + half * 2]) : "r"(v[j]));
              asm volatile("and.b32 %0, %1, 0xffff0000;" : "=f"(acc[mi][(g * 4 + j) * 4 + half * 2 + 1]) : "r"(v[j]));
              if (TANH == 2) { acc[mi][(g * 4 + j) * 4 + half * 2] *= sd[mi * 2 + half]; acc[mi][(g * 4 + j) * 4 + half * 2 + 1] *= sd[mi * 2 + half]; }
            }
            asm("and.b32 %0, %1, %2;" : "=r"(dep[x]) : "f"(acc[mi][(g * 4 + 3) * 4 + half * 2 + 1]), "r"(zero));
          }
          mbar_arrive_warp(bar(B_RF));
        }
        auto stage = [&](int mi, int hi) {
          const int lane = lane_now();
          const uint32_t sw = SB + ((c_sched.task[t].stg >> (8 * hi)) & 31) * 8192 + (mi * 64 + w * 16) * 128, so = sw + (lane & 7) * 128 + (((lane >> 3) ^ (lane & 7)) << 4);
#pragma unroll
          for (int half = 0; half < 2; half++)
#pragma unroll
            for (int g = 0; g < 2; g++) {
              uint32_t v[4];
#pragma unroll
              for (int j = 0; j < 4; j++) {
                if (TANH == 2) { acc[mi][(hi * 8 + g * 4 + j) * 4 + half * 2] *= rsc[mi * 2 + half]; acc[mi][(hi * 8 + g * 4 + j) * 4 + half * 2 + 1] *= rsc[mi * 2 + half]; }
                v[j] = pack_bf16(acc[mi][(hi * 8 + g * 4 + j) * 4 + half * 2], acc[mi][(hi * 8 + g * 4 + j) * 4 + half * 2 + 1]);
              }
              stsm4((so ^ (g * 64)) + half * 1024, v[0], v[1], v[2], v[3]);
            }
          if (mi && !hi) mbar_arrive_warp(bar(B_SIG));
          if (hi == 0 || t == 21) {
            const int r = mi * 64 + w * 16;
            copy_out<4>(sw, t == 21 ? out : sc->y, ((t == 21 ? (row0 + r) * 2 + par : m * 128 + r) * D_ + (hi * 8 + c) * 64) * 2, t == 21 ? D_ * 4 : D_ * 2, lane);
          }
        };
        mainloop<2>(acc, sig, t, wg, sp, []() {}, [&]() { stage(0, 0); if (!SH1 || (SH1 == 2 && t == 21)) stage(0, 1); });
        TL(t, 3);
        stage(1, 0); mbar_arrive_warp(bar(B_SIG + 1));
        TL(t, 6);
        if (SH1 == 1 || (SH1 == 2 && t < 21)) stage(0, 1);
        stage(1, 1); mbar_arrive_warp(bar(B_SIG + 2));
        if (t < 21) {
          const int lane = lane_now(), q = lane & 3;
          float s[4], s2[4];
#pragma unroll
          for (int x = 0; x < 4; x++) {
            float a0 = 0.f, a1 = 0.f, b0 = 0.f, b1 = 0.f;
#pragma unroll
            for (int j = 0; j < 16; j++) {
              const float d0 = acc[x >> 1][j * 4 + (x & 1) * 2], d1 = acc[x >> 1][j * 4 + (x & 1) * 2 + 1];
              a0 += d0; a1 += d1; b0 = fmaf(d0, d0, b0); b1 = fmaf(d1, d1, b1);
            }
            s[x] = a0 + a1; s2[x] = b0 + b1;
          }
#pragma unroll
          for (int x = 0; x < 2; x++) {
            s[x] = (q & 2 ? s[x + 2] : s[x]) + __shfl_xor_sync(0xffffffffu, q & 2 ? s[x] : s[x + 2], 2);
            s2[x] = (q & 2 ? s2[x + 2] : s2[x]) + __shfl_xor_sync(0xffffffffu, q & 2 ? s2[x] : s2[x + 2], 2);
          }
          const float r = (q & 1 ? s[1] : s[0]) + __shfl_xor_sync(0xffffffffu, q & 1 ? s[0] : s[1], 1);
          const float r2 = (q & 1 ? s2[1] : s2[0]) + __shfl_xor_sync(0xffffffffu, q & 1 ? s2[0] : s2[1], 1);
          asm volatile("st.global.v2.f32 [%0], {%1, %2};" ::"l"(&sc->stat[i == 10 ? 1 : l * 2][m][c][(q >> 1) * 64 + w * 16 + (q & 1) * 8 + (lane >> 2)]), "f"(r), "f"(r2) : "memory");
          mbar_arrive_warp(bar(B_SIG + 3));
        }
      }
    }
  }
}

typedef CUresult (*PFN_encodeTiled)(CUtensorMap*, CUtensorMapDataType, cuuint32_t, void*, const cuuint64_t*, const cuuint64_t*, const cuuint32_t*,
                                    const cuuint32_t*, CUtensorMapInterleave, CUtensorMapSwizzle, CUtensorMapL2promotion, CUtensorMapFloatOOBfill);

void make_map(PFN_encodeTiled enc, CUtensorMap* mp, const void* ptr, int rank, const cuuint64_t* gd, const cuuint64_t* gs, const cuuint32_t* bd) {
  const cuuint32_t es[4] = {1, 1, 1, 1};
  enc(mp, CU_TENSOR_MAP_DATA_TYPE_BFLOAT16, rank, const_cast<void*>(ptr), gd, gs, bd, es, CU_TENSOR_MAP_INTERLEAVE_NONE, CU_TENSOR_MAP_SWIZZLE_128B,
      CU_TENSOR_MAP_L2_PROMOTION_L2_256B, CU_TENSOR_MAP_FLOAT_OOB_FILL_NONE);
}
void make_map_act(PFN_encodeTiled enc, CUtensorMap* mp, const void* ptr, uint64_t cols, bool natural, uint32_t rows) {
  const cuuint64_t gd[3] = {cols, S_ / 2, 2}, gs[2] = {natural ? 4 * cols : 2 * cols, natural ? 2 * cols : cols * S_};
  const cuuint32_t bd[3] = {64, rows, 1};
  make_map(enc, mp, ptr, 3, gd, gs, bd);
}
void make_map_w(PFN_encodeTiled enc, CUtensorMap* mp, const void* ptr, uint64_t rows, uint64_t cols, uint32_t np, uint64_t sp, uint64_t tiles, uint32_t nt) {
  const cuuint64_t gd[4] = {512, rows, np, tiles}, gs[3] = {cols * 2, sp, 1024};
  const cuuint32_t bd[4] = {64, 64, np, nt};
  make_map(enc, mp, ptr, 4, gd, gs, bd);
}

}

extern "C" void kernel_launch(void* const* d_in, const int* in_sizes, int n_in, void* d_out, int out_size) {
  (void)in_sizes; (void)n_in; (void)out_size;
  static PFN_encodeTiled enc = nullptr;
  static void *p_sc, *p_ops, *p_w;
  static int by_sm = 0;
  void (*const kernels[4])(Scratch*, const Ops*, const bf16*, bf16*, Params) = {fused_kernel<0, 0>, fused_kernel<1, 0>, fused_kernel<0, 1>, fused_kernel<1, 1>};
  if (!enc) {
    void* fn = nullptr; cudaDriverEntryPointQueryResult qr;
    cudaGetDriverEntryPoint("cuTensorMapEncodeTiled", &fn, cudaEnableDefault, &qr);
    enc = (PFN_encodeTiled)fn;
    cudaGetSymbolAddress(&p_sc, g_sc); cudaGetSymbolAddress(&p_ops, g_ops); cudaGetSymbolAddress(&p_w, g_w13);
    for (int i = 0; i < 4; i++) cudaFuncSetAttribute(kernels[i], cudaFuncAttributeMaxDynamicSharedMemorySize, SM_TOTAL);
    int dev = 0, sms = 0;
    cudaGetDevice(&dev);
    cudaDeviceGetAttribute(&sms, cudaDevAttrMultiProcessorCount, dev);
    by_sm = sms == NCTA + NHELP;
    for (int i = 1; i < 4 && by_sm; i++) {
      cudaLaunchConfig_t cfg = {};
      cudaLaunchAttribute at;
      at.id = cudaLaunchAttributeClusterDimension; at.val.clusterDim.x = 1 << i; at.val.clusterDim.y = at.val.clusterDim.z = 1;
      cfg.gridDim = dim3(NCTA); cfg.blockDim = dim3(384); cfg.dynamicSmemBytes = SM_TOTAL; cfg.attrs = &at; cfg.numAttrs = 1;
      int n = 0;
      if (cudaOccupancyMaxActiveClusters(&n, kernels[0], &cfg) != cudaSuccess) { (void)cudaGetLastError(); n = 0; }
      by_sm = n == (i == 1 ? 66 : i == 2 ? 30 : 15);
    }
  }
  Params P;
  Scratch* const sc = (Scratch*)p_sc;
  make_map_act(enc, &P.tm[M_X0], d_in[0], D_, true, 128);
  make_map_act(enc, &P.tm[M_O], sc->o, D_, false, 128);
  make_map_act(enc, &P.tm[M_Y], sc->y, D_, false, 128);
  make_map_act(enc, &P.tm[M_H], sc->h, F_, false, 128);
  make_map_act(enc, &P.tm[M_OL], sc->o, D_, false, PROWS);
  make_map_act(enc, &P.tm[M_YL], sc->y, D_, false, PROWS);
  make_map_act(enc, &P.tm[M_HL], sc->h, F_, false, PROWS);
  make_map_act(enc, &P.tm[M_O24], sc->o, D_, false, 24);
  make_map_w(enc, &P.tm[M_WQKV], d_in[1], D_, 3 * D_, 3, D_ * 2, 2, 1);
  make_map_w(enc, &P.tm[M_WO], d_in[2], D_, D_, 2, 1024, 1, 1);
  make_map_w(enc, &P.tm[M_W2], d_in[6], F_, D_, 2, 1024, 1, 1);
  const char *w1 = (const char*)d_in[4], *w3 = (const char*)d_in[5];
  if ((uint64_t)(w1 < w3 ? w3 - w1 : w1 - w3) >> 39) {
    cudaMemcpyAsync(p_w, w1, (size_t)D_ * F_ * 2, cudaMemcpyDeviceToDevice);
    cudaMemcpyAsync((bf16*)p_w + D_ * F_, w3, (size_t)D_ * F_ * 2, cudaMemcpyDeviceToDevice);
    w1 = (const char*)p_w; w3 = w1 + (size_t)D_ * F_ * 2;
  }
  const bool swap = w3 < w1;
  make_map_w(enc, &P.tm[M_W13], swap ? w3 : w1, D_, F_, 2, swap ? w1 - w3 : w3 - w1, 7, 1);
  make_map_w(enc, &P.tm[M_W13P], swap ? w3 : w1, D_, F_, 2, swap ? w1 - w3 : w3 - w1, 7, 2);
  kernels[by_sm * 2 + swap]<<<NCTA + NHELP, 384, SM_TOTAL>>>(sc, (const Ops*)p_ops, (const bf16*)d_in[0], (bf16*)d_out, P);
}
```

```cpp
#include <cuda_runtime.h>
#include <cuda_bf16.h>
#include <cuda.h>
#include <stdint.h>
#include <stddef.h>

typedef __nv_bfloat16 bf16;
#define GU_E 3
#define G_N1 7
#define Q_P1 4
#define Q_P2 6
#define Q_P0 1
#define RES_O 3
#define RES_D 3
#define HOLD_O 6
#define PROWS 16
#define GAP_O 150
#define GAP_Y 100
#define GAP_H 350
#define GAP_H6 1000
#define ST_T1 900
#define ST_D1 500
#define ST_ROWS 3500
#define WARM_T 4000
constexpr int TAILQ = 1, TAIL = 2;

namespace {

constexpr int S_ = 2048, D_ = 1024, F_ = 3584;
constexpr int NCTA = 128;
constexpr int NHELP = 4;

constexpr uint32_t SB = 1024;
constexpr int NU = 25;
constexpr uint32_t SM_STG  = SB + NU * 8192;
__host__ __device__ constexpr uint32_t xch(int i, int w) { return i ? SM_STG - 8192 + w * 2048 : SM_STG + w * 4096; }
constexpr uint32_t BARS    = SM_STG + 16384;
constexpr uint32_t SM_STAT = BARS + 896;
__host__ __device__ constexpr uint32_t stat(int set) { return SM_STAT + set * 1088 + 64; }
constexpr uint32_t SM_CS   = SM_STAT + 4352;
constexpr uint32_t SM_END  = SM_CS + 5120;
constexpr int SM_TOTAL = SM_END - SB;
static_assert(BARS % 1024 == 0 && SM_TOTAL <= 232448, "smem");
constexpr int B_FULL = 0, B_EMPTY = 16, B_SIG = 32, B_XCH = 36, B_STAT = 37, B_TURN = 41, B_CS = 43, B_FREE = 52, B_SF = 53, B_QT = 55, B_PASS = 56,
              B_RES = 57, B_RF = 58, B_DEP = 59, B_PUB = 75, B_N = 91;
__host__ __device__ constexpr uint32_t bar(int i) { return BARS + 8 * i; }
constexpr uint32_t SM_TAG = BARS + 8 * B_N, SM_ZERO = BARS + 768;
constexpr int NB_PX = 1, NB_PY = 2, NB_OGO = 3, NB_END = 4;

constexpr int E_O0 = 0, E_O1 = 1, E_YA = 2, E_YB = 3, E_H4 = 4, E_XA = 7, E_XB = 8, E_N = 9;

constexpr int M_X0 = 0, M_O = 1, M_Y = 2, M_H = 3;
constexpr int M_WQKV = 4, M_WO = 5, M_W13 = 6, M_W13P = 7, M_W2 = 8;
constexpr int M_OL = 9, M_YL = 10, M_HL = 11, M_O24 = 12, M_N = 13;

constexpr int FIRST = 5;
constexpr int NOPA = 416, NOPB = 416, NSEG = 40;
constexpr uint32_t A_END = 1, A_TURN = 2, A_DRAIN = 4, A_WAIT = 8, A_SYNC = 16;
constexpr uint32_t A_MARK = 0;
struct Task { uint32_t stg, res, sig; };
struct Seg { uint32_t i8, end8, a, b; };
constexpr uint32_t LO_A = 0x10000 + SB / 16, LO_B = 0x2000000 + SB / 16;
struct Sched { Seg seg[2 * NSEG]; Task task[22]; };
struct Ops { uint2 a[NOPA + 64], b[NOPB + 64]; };
struct Gen {
  Sched s{}; Ops o{};
  int n[2] = {0, 0}, nseg[2] = {0, NSEG}, cur = -1, pos = 0, err = 0, res = 0, nres = 0;
  int mask[400] = {}, sa[400] = {}, sb[400][2] = {}, own[NU][2] = {}, tok[NU] = {}, known[2][2] = {{-1, -1}, {-1, -1}};
  constexpr void emit(int p, int wait, int par, int dst, int map, int kb8, int arr, int load, int y) {
    if (cur < FIRST) return;
    const uint2 e{(uint32_t)(y >> 10 | (p && load ? map - M_WQKV : map) << 3 | (y & 63) << 6 | load << 12 | dst << 13 | (res ? B_RES : B_FULL + (cur & 15)) << 18 | wait << 24) | (uint32_t)(par & 1) << 31,
                  (uint32_t)(((y >> 6) & 15) | arr << 4 | (!p && arr && mask[cur] != 3 && !res) << 5 | ((cur + 2) & 15) << 9 | kb8 << 13)};
    if (p) o.b[n[1]++] = e; else o.a[n[0]++] = e;
  }
  constexpr bool done(int p, int x) const { return x < 0 || ((!(mask[x] & 1) || known[p][0] >= x) && (!(mask[x] & 2) || known[p][1] >= x)); }
  constexpr void op(int p, int dst, int nu, int map, int kb8, int arr, int y, int xw = -1, int xp = 0) {
    int w[8] = {}, wp[8] = {}, nw = 0;
    if (xw >= 0) { w[nw] = xw; wp[nw++] = xp; }
    for (int u = dst; u < dst + nu; u++) if (tok[u] && (u == dst || tok[u] != tok[u - 1])) { w[nw] = (tok[u] - 1) >> 1; wp[nw++] = tok[u] - 1; }
    for (int x = cur - 1; x >= 0; x--) {
      bool need = x <= cur - 12;
      for (int u = dst; u < dst + nu; u++) need = need || own[u][0] == x + 1 || own[u][1] == x + 1;
      if (!need || done(p, x)) continue;
      if (cur - x >= 16 || !done(p, x - 16)) err |= 1;
      w[nw] = B_EMPTY + ((x + 2) & 15); wp[nw++] = x >> 4;
      for (int g = 0; g < 2; g++) if (((mask[x] >> g) & 1) && known[p][g] < x) known[p][g] = x;
    }
    for (; nw > 1; nw--) emit(p, w[nw - 1], wp[nw - 1], 0, 0, 0, 0, 0, 0);
    emit(p, nw ? w[0] : B_PASS, nw ? wp[0] : 1, dst, map, kb8, arr, nu > 0, y);
    for (int u = dst; u < dst + nu; u++) { own[u][0] = cur + 1; own[u][1] = 0; tok[u] = 0; }
  }
  constexpr int step(int m) { mask[++cur] = m; return cur; }
  constexpr int slot() { int u = (pos + 1) & ~1; if (u >= 24) u = 0; pos = u + 2; return u; }
  constexpr int qslot() { int u = (pos + 4) / 5 * 5; if (u >= NU) u = 0; pos = u + 5; return u; }
  constexpr void stage(int u, int first, int t) {
    first -= TAIL;
    for (int x = u; x < u + 2; x++) { if (own[x][0] > first || own[x][1] > first || tok[x]) err |= 2; own[x][0] = cur + 1; own[x][1] = 0; tok[x] = t; }
  }
  static constexpr int kown(int hi) { return hi * 8 | 1 << 9; }
  static constexpr int kskip(int hi, int j) { return (hi * 8 + j) | (j + 1) << 6; }
  static constexpr int kpos(int p) { return p < 2 ? kown(p) : p < 9 ? kskip(0, p - 2) : kskip(1, p - 9); }
  constexpr void segs(int t, const int* st, const uint32_t* act, int cnt, int tail, int inc0) {
    const int g = t & 1, wrap = inc0 == 5 ? NU : 24;
    int j0 = 0;
    for (int j = 0; j < cnt; j++) {
      const int x = st[j], inc = inc0 ? inc0 : mask[st[j0]] == 3 ? 6 : 4;
      const bool next = j + 1 < cnt && st[j + 1] == x + 1 && mask[x + 1] == mask[x] && sa[x + 1] == (sa[x] + inc) % wrap && sb[x + 1][g] == (sb[x][g] + inc) % wrap;
      if (j >= cnt - tail - 1 && j + 1 < cnt && !next) err |= 4;
      if (j + 1 < cnt && st[j + 1] != x + 1 && !(act[j] & A_DRAIN)) err |= 8;
      if (j >= cnt - tail || (next && !act[j] && j != cnt - tail - 1)) continue;
      if (j == j0 && (j == 0 || (inc0 != 4 && (act[j - 1] & (A_DRAIN | A_SYNC))))) err |= 16;
      const int y = st[j0];
      s.seg[nseg[g]++] = Seg{(uint32_t)y * 8 | (act[j] | (j == cnt - tail - 1 ? A_END : 0)) << 16, (uint32_t)(x + 1) * 8 | inc * 512 << 16, LO_A + sa[y] * 512, LO_B + sb[y][g] * 512};
      j0 = j + 1;
    }
  }
  constexpr void residual(int t, int map, bool q) {
    const int u0 = q ? qslot() : slot(), u1 = q ? u0 + 2 : slot();
    res = 1;
    op(0, u0, 2, map, 4, 1, kown(0)); op(0, u1, 2, map, 0, 0, kown(1));
    res = 0;
    for (int x = 0; x < 4; x++) { const int u = (x < 2 ? u0 : u1) + (x & 1); own[u][0] = 0; tok[u] = 1 + B_RF * 2 + (nres & 1); }
    nres++;
    s.task[t].res = u0 | u1 << 8;
  }
  constexpr Gen() {
    int cs[4] = {};
    for (int t = 0; t < 22; t++) {
      const int i = t % 11, use = i == 0 ? 2 : (i == 2 || i == 10) ? 15 : 3;
      for (int x = 0; x < 4; x++) if ((use >> x) & 1) s.task[t].sig |= (cs[x]++ & 1) << x;
    }
    for (int l = 0; l < 2; l++) {
      const int T = l * 11, dep = B_DEP + l * E_N;
      int st[7][56] = {};
      uint32_t act[7][56] = {};
      if (l == 1) {
        const int first = cur + 1;
        for (int j = 0; j < 4; j++) {
          const int x = st[j >> 1][j & 1] = step(1 << ((T + (j >> 1)) & 1)), u = qslot();
          sb[x][0] = sb[x][1] = u + 2;
          if (j < 2) {
            sa[x] = (u + 5) % NU; stage(sa[x], first, j ? 1 + B_SF * 2 + 1 : 0); s.task[10].stg |= sa[x] << (8 * j);
            op(0, 0, 0, 0, 0, 1, 1 << 10, B_SIG + 2 * j, s.task[10].sig >> (2 * j));
          }
          else { sa[x] = sa[x - 2]; own[sa[x]][1] = own[sa[x] + 1][1] = x + 1; op(0, 0, 0, 0, 0, 1, 0); }
          op(1, u + 2, 3, M_WQKV, 3, 1, kown(j & 1) | (j >> 1) << 10);
        }
        act[0][1] = A_DRAIN; act[1][1] = A_DRAIN | A_WAIT;
      }
      for (int i = 0; i < 2; i++) {
        for (int j = 2 * l; j < 16; j++) {
          if (i && j == 16 - RES_O) residual(T + 2, l ? M_Y : M_X0, true);
          const int x = st[i][j] = step(1 << ((T + i) & 1)), u = qslot(), k = l ? kpos(j) : j;
          sa[x] = u; sb[x][0] = sb[x][1] = u + 2;
          op(0, u, 2, l ? M_Y : M_X0, 2, 1, k, l && i == 0 && (j == 2 || j == 9) ? B_DEP + (j == 2 ? E_XA : E_XB) : -1);
          op(1, u + 2, 3, M_WQKV, 3, 1, k | i << 10);
        }
        if (i) act[1][Q_P1 - 1 + (l ? 2 : Q_P0)] = act[1][Q_P2 - 1 + (l ? 2 : Q_P0)] = A_SYNC;
        if (i && own[NU - 1][0] > cur - TAILQ) err |= 256;
        segs(T + i, st[i], act[i], 16, TAILQ, 5);
      }
      for (int j = 0; j < 16; j++) {
        const int x = st[0][j] = step(1 << (T & 1)), k = j < 8 ? j : j == 8 ? kown(1) : kskip(1, j - 9), hold = j == HOLD_O ? B_PUB + l * E_N + E_O1 : -1;
        act[0][j] = j == 8 ? A_MARK : 0;
        if (j != 8) { sa[x] = slot(); op(0, sa[x], 2, M_O, 2, 1, k, j == 0 ? dep + E_O0 : j == 9 ? dep + E_O1 : hold); }
        else { sa[x] = NU; op(0, 0, 0, 0, 0, 1, 1 << 10, B_SIG + 1, s.task[T + 1].sig >> 1); }
        sb[x][0] = sb[x][1] = slot();
        op(1, sb[x][0], 2, M_WO, 2, 1, k, hold);
      }
      segs(T + 2, st[0], act[0], 16, TAIL, 4);
      int beg[8] = {0, 16}, end[7] = {16, 32 - G_N1}, cnt[7] = {};
      for (int j = 2; j < 7; j++) { beg[j] = end[j - 2] + GU_E; end[j] = beg[j] + 16; }
      beg[7] = end[6];
      const int first = cur + 1;
      for (int j = 0; j < end[6]; j++) {
        int tl[2] = {-1, -1}, m = 0;
        for (int v = 0; v < 7; v++) if ((j >= beg[v] && j < end[v]) || (v == 1 && j < G_N1)) { const int g = (T + 3 + v) & 1; if (tl[g] >= 0) err |= 32; tl[g] = v; m |= 1 << g; }
        if (!m) err |= 32;
        if (j == end[6] - RES_D) residual(T + 10, M_Y, false);
        const int x = step(m), k = kpos(j < 16 ? j : (j + G_N1) & 15);
        const int v0 = m == 3 ? (tl[0] < tl[1] ? tl[0] : tl[1]) : tl[m >> 1];
        const int ps = (pos + 1) / 2 % 12;
        const bool last = m == 3 && (ps % 3 == 1 || (j >= 2 && j < G_N1 && (ps % 3 == 0 || (j == 2 && ps != 11))));
        if (!last) sa[x] = slot();
        const int u = slot();
        if (m == 3 && slot() != u + 2) err |= 32;
        if (last) sa[x] = slot();
        if (j < 2) { stage(sa[x], first, j ? 1 + B_SF * 2 : 0); s.task[T + 2].stg |= sa[x] << (8 * j); op(0, 0, 0, 0, 0, 1, 1 << 10, B_SIG + 2 * j, s.task[T + 2].sig >> (2 * j)); }
        else op(0, sa[x], 2, M_Y, 2, 1, k, j == 2 ? dep + E_YA : j == 9 ? dep + E_YB : -1);
        op(1, u, m == 3 ? 4 : 2, m == 3 ? M_W13P : M_W13, m == 3 ? 4 : 2, 1, k | v0 << 10, j == 3 ? B_PUB + l * E_N + E_YA : -1);
        for (int g = 0; g < 2; g++) {
          const int v = tl[g];
          if (v < 0) continue;
          sb[x][g] = u + (v - v0) * 2;
          act[v][cnt[v]] = j == beg[v + 1] - 1 ? A_TURN : v == 1 && j == G_N1 - 1 ? A_DRAIN | A_WAIT : v == 0 && j == 1 ? A_MARK : 0;
          st[v][cnt[v]++] = x;
        }
      }
      for (int v = 0; v < 7; v++) { if (cnt[v] != 16) err |= 64; segs(T + 3 + v, st[v], act[v], 16, 0, 0); }
      for (int j = 0; j < 56; j++) {
        const int x = st[0][j] = step(1 << (T & 1));
        act[0][j] = 0;
        sa[x] = slot(); op(0, sa[x], 2, M_H, 2, 1, j, j == 0 ? dep + E_H4 : j == 40 ? dep + E_H4 + 1 : j == 48 ? dep + E_H4 + 2 : -1);
        sb[x][0] = sb[x][1] = slot(); op(1, sb[x][0], 2, M_W2, 2, 1, j);
      }
      segs(T + 10, st[0], act[0], 56, TAIL, 4);
    }
    { const int u0 = slot(), u1 = slot(); stage(u0, cur + 1, 0); stage(u1, cur + 1, 0); s.task[21].stg = u0 | u1 << 8; }
    if (n[0] > NOPA || n[1] > NOPB || nseg[0] >= NSEG || nseg[1] >= 2 * NSEG) err |= 128;
    for (int x = n[0]; x < NOPA + 64; x++) o.a[x] = uint2{B_PASS << 24 | 1u << 31, 0};
    for (int x = n[1]; x < NOPB + 64; x++) o.b[x] = uint2{B_PASS << 24 | 1u << 31, 0};
  }
};
constexpr Gen GEN{};
static_assert(GEN.err == 0, "schedule");
constexpr int NOP0 = (GEN.n[0] + 31) / 32 * 32, NOP1 = (GEN.n[1] + 31) / 32 * 32;

struct __align__(64) Params {
  CUtensorMap tm[M_N];
};

}

__constant__ Sched c_sched = GEN.s;
__device__ const Ops g_ops = GEN.o;
struct __align__(1024) Scratch {
  bf16 o[S_ * D_], y[S_ * D_], h[S_ * F_];
  float2 stat[3][16][8][128];
  uint4 stat0[16][128];
  uint4 halo[4][16][8][6][32];
  uint4 cs[9][8][64];
  uint32_t flags[NCTA][32];
  uint32_t cnt[4][32];
  uint32_t epoch[NCTA + NHELP];
};
__device__ Scratch g_sc;
__device__ __align__(1024) bf16 g_w13[2 * D_ * F_];

#define TL(t, i) do {} while (0)
#define TS(i8, wg) do {} while (0)
#define TLW(t, i) do {} while (0)
#define MB_LIMIT (1 << 16)
#define FL_LIMIT (1 << 21)

namespace {

__device__ __forceinline__ uint32_t smem_u32(const void* p) { return (uint32_t)__cvta_generic_to_shared(p); }
__device__ __forceinline__ void mbar_init(uint32_t br, uint32_t cnt) { asm volatile("mbarrier.init.shared::cta.b64 [%0], %1;" ::"r"(br), "r"(cnt)); }
__device__ __forceinline__ void mbar_expect_tx(uint32_t br, uint32_t bytes) { asm volatile("mbarrier.arrive.expect_tx.shared::cta.b64 _, [%0], %1;" ::"r"(br), "r"(bytes) : "memory"); }
__device__ __forceinline__ void mbar_arrive(uint32_t br) { asm volatile("mbarrier.arrive.shared::cta.b64 _, [%0];" ::"r"(br) : "memory"); }
__device__ __forceinline__ void mbar_arrive_if(uint32_t br, uint32_t p) {
  asm volatile("{\n.reg .pred q;\nsetp.ne.u32 q, %1, 0;\n@q mbarrier.arrive.shared::cta.b64 _, [%0];\n}\n" ::"r"(br), "r"(p) : "memory");
}
__device__ __forceinline__ void mbar_arrive_warp(uint32_t br) {
  asm volatile("{\n.reg .pred q;\nbar.warp.sync 0xffffffff;\nelect.sync _|q, 0xffffffff;\n@q mbarrier.arrive.shared::cta.b64 _, [%0];\n}\n" ::"r"(br) : "memory");
}
__device__ __forceinline__ bool mbar_try_wait(uint32_t br, uint32_t parity) {
  uint32_t ok;
  asm volatile("{\n.reg .pred p;\nmbarrier.try_wait.parity.shared::cta.b64 p, [%1], %2;\nselp.u32 %0, 1, 0, p;\n}\n" : "=r"(ok) : "r"(br), "r"(parity) : "memory");
  return ok;
}
__device__ __forceinline__ void mbar_wait(uint32_t br, uint32_t parity) {
#pragma unroll 1
  for (int it = 0; it < MB_LIMIT; ++it) { if (mbar_try_wait(br, parity)) return; }
  __trap();
}
__device__ __forceinline__ bool elect_one() { uint32_t p; asm volatile("{\n.reg .pred P;\nelect.sync _|P, 0xffffffff;\nselp.u32 %0, 1, 0, P;\n}\n" : "=r"(p)); return p; }
__device__ __forceinline__ void fence_proxy_async_smem() { asm volatile("fence.proxy.async.shared::cta;" ::: "memory"); }
__device__ __forceinline__ void tma3d(uint32_t dst, const CUtensorMap* m, int c0, int c1, int c2, uint32_t br) {
  asm volatile("cp.async.bulk.tensor.3d.shared::cluster.global.mbarrier::complete_tx::bytes [%0], [%1, {%3, %4, %5}], [%2];" ::"r"(dst), "l"(m), "r"(br), "r"(c0), "r"(c1), "r"(c2) : "memory");
}
__device__ __forceinline__ void tma4d(uint32_t dst, const CUtensorMap* m, int c0, int c1, int c3, uint32_t br) {
  asm volatile("cp.async.bulk.tensor.4d.shared::cluster.global.mbarrier::complete_tx::bytes [%0], [%1, {%3, %4, %6, %5}], [%2];" ::"r"(dst), "l"(m), "r"(br), "r"(c0), "r"(c1), "r"(c3), "r"(0) : "memory");
}
__device__ __forceinline__ void tma3d_store(const CUtensorMap* m, uint32_t src, int c0, int c1, int c2) {
  asm volatile("{\n.reg .pred p;\nelect.sync _|p, 0xffffffff;\n@p cp.async.bulk.tensor.3d.global.shared::cta.bulk_group [%0, {%2, %3, %4}], [%1];\n}\n" ::"l"(m), "r"(src), "r"(c0), "r"(c1), "r"(c2) : "memory");
}
__device__ __forceinline__ void stsm4(uint32_t a, uint32_t x, uint32_t y, uint32_t z, uint32_t w) {
  asm volatile("stmatrix.sync.aligned.m8n8.x4.shared.b16 [%0], {%1,%2,%3,%4};" ::"r"(a), "r"(x), "r"(y), "r"(z), "r"(w) : "memory");
}
__device__ __forceinline__ void ldsm4(uint32_t a, uint32_t& x, uint32_t& y, uint32_t& z, uint32_t& w) {
  asm volatile("ldmatrix.sync.aligned.m8n8.x4.shared.b16 {%0,%1,%2,%3}, [%4];" : "=r"(x), "=r"(y), "=r"(z), "=r"(w) : "r"(a) : "memory");
}
__device__ __forceinline__ void st_tag(uint4* p, uint32_t a, uint32_t b, uint32_t c, uint32_t tag) {
  asm volatile("{\n.reg .b64 x, y;\n.reg .b128 z;\nmov.b64 x, {%1, %2};\nmov.b64 y, {%3, %4};\nmov.b128 z, {x, y};\nst.relaxed.gpu.global.b128 [%0], z;\n}\n" ::"l"(p), "r"(a), "r"(b), "r"(c), "r"(tag) : "memory");
}
__device__ __forceinline__ uint4 ld_tag(const uint4* p) {
  uint4 v;
  asm volatile("{\n.reg .b64 x, y;\n.reg .b128 z;\nld.relaxed.gpu.global.b128 z, [%4];\nmov.b128 {x, y}, z;\nmov.b64 {%0, %1}, x;\nmov.b64 {%2, %3}, y;\n}\n" : "=r"(v.x), "=r"(v.y), "=r"(v.z), "=r"(v.w) : "l"(p) : "memory");
  return v;
}
template <int NAP, int N> __device__ __forceinline__ void ld_tag_wait(uint4 (&v)[N], const uint4* p, uint32_t tag) {
#pragma unroll 1
  for (int it = 0; it < FL_LIMIT; ++it) {
    uint32_t bad = 0;
#pragma unroll
    for (int j = 0; j < N; j++) v[j] = ld_tag(p + j * 32);
#pragma unroll
    for (int j = 0; j < N; j++) bad |= v[j].w ^ tag;
    if (__all_sync(0xffffffffu, bad == 0)) return;
    if (NAP) __nanosleep(NAP);
  }
  __trap();
}
__device__ __forceinline__ void prefetch_tmap(const CUtensorMap* m) { asm volatile("prefetch.tensormap [%0];" ::"l"(m) : "memory"); }
__device__ __forceinline__ void wgmma_fence() { asm volatile("wgmma.fence.sync.aligned;" ::: "memory"); }
__device__ __forceinline__ void wgmma_commit() { asm volatile("wgmma.commit_group.sync.aligned;" ::: "memory"); }
template <int N> __device__ __forceinline__ void wgmma_wait() { asm volatile("wgmma.wait_group.sync.aligned %0;" ::"n"(N) : "memory"); }
template <int R> __device__ __forceinline__ void reg_alloc() { asm volatile("setmaxnreg.inc.sync.aligned.u32 %0;" ::"n"(R)); }
template <int R> __device__ __forceinline__ void reg_dealloc() { asm volatile("setmaxnreg.dec.sync.aligned.u32 %0;" ::"n"(R)); }
__device__ __forceinline__ void bar_sync(int id, int n) { asm volatile("bar.sync %0, %1;" ::"r"(id), "r"(n) : "memory"); }
__device__ __forceinline__ void bar_arrive(int id, int n) { asm volatile("bar.arrive %0, %1;" ::"r"(id), "r"(n) : "memory"); }
__device__ __forceinline__ uint32_t ld_acquire(const uint32_t* p) { uint32_t v; asm volatile("ld.acquire.gpu.global.u32 %0, [%1];" : "=r"(v) : "l"(p) : "memory"); return v; }
__device__ __forceinline__ void st_release(uint32_t* p, uint32_t v) { asm volatile("st.release.gpu.global.u32 [%0], %1;" ::"l"(p), "r"(v) : "memory"); }
__device__ __forceinline__ uint4 ldcg16(const void* p) { uint4 v; asm volatile("ld.global.cg.v4.u32 {%0,%1,%2,%3}, [%4];" : "=r"(v.x), "=r"(v.y), "=r"(v.z), "=r"(v.w) : "l"(p) : "memory"); return v; }
__device__ __forceinline__ float2 lds8f(uint32_t a) { float2 v; asm volatile("ld.shared.v2.f32 {%0,%1}, [%2];" : "=f"(v.x), "=f"(v.y) : "r"(a)); return v; }
__device__ __forceinline__ float lds4f(uint32_t a) { float v; asm volatile("ld.shared.f32 %0, [%1];" : "=f"(v) : "r"(a)); return v; }
__device__ __forceinline__ uint32_t lds4(uint32_t a) { uint32_t v; asm volatile("ld.shared.u32 %0, [%1];" : "=r"(v) : "r"(a) : "memory"); return v; }
__device__ __forceinline__ void lds16f(uint32_t a, float& x, float& y, float& z, float& w) { asm volatile("ld.shared.v4.f32 {%0,%1,%2,%3}, [%4];" : "=f"(x), "=f"(y), "=f"(z), "=f"(w) : "r"(a) : "memory"); }
__device__ __forceinline__ void sts8f(uint32_t a, float x, float y) { asm volatile("st.shared.v2.f32 [%0], {%1,%2};" ::"r"(a), "f"(x), "f"(y) : "memory"); }
__device__ __forceinline__ void sts4f(uint32_t a, float x) { asm volatile("st.shared.f32 [%0], %1;" ::"r"(a), "f"(x) : "memory"); }
__device__ __forceinline__ void sts16(uint32_t a, uint32_t x, uint32_t y, uint32_t z, uint32_t w) { asm volatile("st.shared.v4.u32 [%0], {%1,%2,%3,%4};" ::"r"(a), "r"(x), "r"(y), "r"(z), "r"(w) : "memory"); }
__device__ __forceinline__ void lds16(uint32_t a, uint32_t& x, uint32_t& y, uint32_t& z, uint32_t& w) { asm volatile("ld.shared.v4.u32 {%0,%1,%2,%3}, [%4];" : "=r"(x), "=r"(y), "=r"(z), "=r"(w) : "r"(a) : "memory"); }
__device__ __forceinline__ uint32_t pack_bf16(float a, float b) { uint32_t r; asm("cvt.rn.bf16x2.f32 %0, %1, %2;" : "=r"(r) : "f"(b), "f"(a)); return r; }
__device__ __forceinline__ uint32_t pack_bf16_v(float a, float b) { uint32_t r; asm volatile("cvt.rn.bf16x2.f32 %0, %1, %2;" : "=r"(r) : "f"(b), "f"(a)); return r; }
__device__ __forceinline__ float bf_lo(uint32_t v) { return __uint_as_float(v << 16); }
__device__ __forceinline__ float bf_hi(uint32_t v) { return __uint_as_float(v & 0xffff0000u); }
constexpr float LOG2E = 1.4426950408889634f;
__device__ __forceinline__ float ex2f(float x) { float y; asm("ex2.approx.ftz.f32 %0, %1;" : "=f"(y) : "f"(x)); return y; }
__device__ __forceinline__ float tanhf_(float x) { float y; asm("tanh.approx.f32 %0, %1;" : "=f"(y) : "f"(x)); return y; }
__device__ __forceinline__ float rcpf(float x) { float y; asm("rcp.approx.ftz.f32 %0, %1;" : "=f"(y) : "f"(x)); return y; }
__device__ __forceinline__ float bf_round(float a) { return bf_lo(pack_bf16(a, 0.f)); }
__device__ __forceinline__ uint32_t movmat(uint32_t a) { uint32_t d; asm volatile("movmatrix.sync.aligned.m8n8.trans.b16 %0, %1;" : "=r"(d) : "r"(a)); return d; }
__device__ __forceinline__ void mma16816(float& d0, float& d1, float& d2, float& d3, uint32_t a0, uint32_t a1, uint32_t a2, uint32_t a3, uint32_t b0, uint32_t b1,
                                         float c0, float c1, float c2, float c3) {
  asm volatile("mma.sync.aligned.m16n8k16.row.col.f32.bf16.bf16.f32 {%0,%1,%2,%3}, {%4,%5,%6,%7}, {%8,%9}, {%10,%11,%12,%13};"
               : "=f"(d0), "=f"(d1), "=f"(d2), "=f"(d3) : "r"(a0), "r"(a1), "r"(a2), "r"(a3), "r"(b0), "r"(b1), "f"(c0), "f"(c1), "f"(c2), "f"(c3));
}
template <int N> __device__ __forceinline__ void copy_out(uint32_t a, void* base, uint32_t ofs, int pitch, int lane) {
  a += (lane >> 3) * 128 + (((lane ^ (lane >> 3)) & 7) << 4);
  char* const g = static_cast<char*>(base) + (ofs + (lane >> 3) * pitch + (lane & 7) * 16);
  uint32_t v[N][4];
  __syncwarp();
#pragma unroll
  for (int j = 0; j < N; j++) lds16((a ^ ((j & 1) * 64)) + j * 512, v[j][0], v[j][1], v[j][2], v[j][3]);
#pragma unroll
  for (int j = 0; j < N; j++) asm volatile("st.global.v4.u32 [%0], {%1, %2, %3, %4};" ::"l"(g + j * 4 * pitch), "r"(v[j][0]), "r"(v[j][1]), "r"(v[j][2]), "r"(v[j][3]) : "memory");
}
__device__ __forceinline__ int lane_now() { int v; asm volatile("mov.u32 %0, %%laneid;" : "=r"(v)); return v; }
__device__ __forceinline__ uint32_t uni(uint32_t x, int lane) { return __shfl_sync(0xffffffffu, x + lane, 0); }
__device__ __forceinline__ uint64_t dsc(uint32_t hi, uint32_t lo) { return ((uint64_t)hi << 32) | lo; }

#define R8(a, o) "+f"(a[o]), "+f"(a[o + 1]), "+f"(a[o + 2]), "+f"(a[o + 3]), "+f"(a[o + 4]), "+f"(a[o + 5]), "+f"(a[o + 6]), "+f"(a[o + 7])
#define R32(a, o) R8(a, o), R8(a, o + 8), R8(a, o + 16), R8(a, o + 24)
#define REG64 "%0, %1, %2, %3, %4, %5, %6, %7, %8, %9, %10, %11, %12, %13, %14, %15, %16, %17, %18, %19, %20, %21, %22, %23, %24, %25, %26, %27, %28, %29, %30, %31, " \
              "%32, %33, %34, %35, %36, %37, %38, %39, %40, %41, %42, %43, %44, %45, %46, %47, %48, %49, %50, %51, %52, %53, %54, %55, %56, %57, %58, %59, %60, %61, %62, %63"
#define REG96 REG64 ", %64, %65, %66, %67, %68, %69, %70, %71, %72, %73, %74, %75, %76, %77, %78, %79, %80, %81, %82, %83, %84, %85, %86, %87, %88, %89, %90, %91, %92, %93, %94, %95"
__device__ __forceinline__ void wgmma(float (&d)[64], uint64_t da, uint64_t db) {
  asm volatile("wgmma.mma_async.sync.aligned.m64n128k16.f32.bf16.bf16 {" REG64 "}, %64, %65, 1, 1, 1, 0, 1;\n"
               : R32(d, 0), R32(d, 32) : "l"(da), "l"(db));
}
__device__ __forceinline__ void wgmma(float (&d)[96], uint64_t da, uint64_t db) {
  asm volatile("wgmma.mma_async.sync.aligned.m64n192k16.f32.bf16.bf16 {" REG96 "}, %96, %97, 1, 1, 1, 0, 1;\n"
               : R32(d, 0), R32(d, 32), R32(d, 64) : "l"(da), "l"(db));
}
#define W8(a, o) "=f"(a[o]), "=f"(a[o + 1]), "=f"(a[o + 2]), "=f"(a[o + 3]), "=f"(a[o + 4]), "=f"(a[o + 5]), "=f"(a[o + 6]), "=f"(a[o + 7])
#define W32(a, o) W8(a, o), W8(a, o + 8), W8(a, o + 16), W8(a, o + 24)
__device__ __forceinline__ void wgmma_z(float (&d)[64], uint64_t da, uint64_t db) {
  asm volatile("wgmma.mma_async.sync.aligned.m64n128k16.f32.bf16.bf16 {" REG64 "}, %64, %65, 0, 1, 1, 0, 1;\n"
               : W32(d, 0), W32(d, 32) : "l"(da), "l"(db));
}
__device__ __forceinline__ void wgmma_z(float (&d)[96], uint64_t da, uint64_t db) {
  asm volatile("wgmma.mma_async.sync.aligned.m64n192k16.f32.bf16.bf16 {" REG96 "}, %96, %97, 0, 1, 1, 0, 1;\n"
               : W32(d, 0), W32(d, 32), W32(d, 64) : "l"(da), "l"(db));
}

__device__ __forceinline__ void wgmma_cs(float (&d)[4], uint64_t da, uint64_t db) {
  asm volatile("wgmma.mma_async.sync.aligned.m64n8k16.f32.bf16.bf16 {%0, %1, %2, %3}, %4, %5, 1, 1, 1, 1, 0;\n" : "+f"(d[0]), "+f"(d[1]), "+f"(d[2]), "+f"(d[3]) : "l"(da), "l"(db));
}
__device__ __forceinline__ void bulk_commit() { asm volatile("cp.async.bulk.commit_group;" ::: "memory"); }
__device__ __forceinline__ void bulk_wait() { asm volatile("cp.async.bulk.wait_group 0;" ::: "memory"); }
__device__ __forceinline__ void fence_bar_init() { asm volatile("fence.mbarrier_init.release.cluster;" ::: "memory"); }

__device__ __forceinline__ uint32_t clock_now() { uint32_t v; asm volatile("mov.u32 %0, %%clock;" : "=r"(v)); return v; }
__device__ __forceinline__ void delay_until(uint32_t t0, int cycles) {
#pragma unroll 1
  for (int it = 0; it < 1000 && (int)(clock_now() - t0) < cycles; it++) __nanosleep(40);
}
__device__ __forceinline__ uint32_t ld_epoch(const uint32_t* p) { uint32_t v; asm volatile("ld.global.u32 %0, [%1];" : "=r"(v) : "l"(p) : "memory"); return v + 1; }
__device__ __forceinline__ void wait_flags(const uint32_t* f, uint32_t tag) {
#pragma unroll 1
  for (int it = 0; it < FL_LIMIT; ++it) if (__all_sync(0xffffffffu, (int)(ld_acquire(f) - tag) >= 0)) return;
  __trap();
}

__device__ __forceinline__ float2 ln_finish(float sum, float sq) {
  const float mean = sum * (1.f / D_), var = fmaxf(fmaf(-mean, mean, sq * (1.f / D_)), 0.f);
  const float mb = bf_round(mean);
  const float vb = bf_round(var);
  const float sd = bf_round(sqrtf(bf_round(vb + 1e-5f)));
  return make_float2(1.0f / sd, -mb);
}

__device__ __forceinline__ void helper_cta(const Params& P, Scratch* sc, int e, int wg, int w) {
  const int tid = threadIdx.x;
  if (tid == 256) {
#pragma unroll
    for (int i = 0; i < 16; i++) mbar_init(bar(i), 1);
    fence_bar_init();
  }
  if (tid < 64) sts16(SM_STG + tid * 16, 0x3f803f80u, 0x3f803f80u, 0x3f803f80u, 0x3f803f80u);
  fence_proxy_async_smem();
  __syncthreads();
  if (wg == 2) {
    if (w == 0) {
#pragma unroll 1
      for (int n = 0; n < 9 * 32; n++) {
        const int job = n >> 5;
        const uint32_t fb = bar(n & 7), dst = SB + (n & 7) * 24576;
        mbar_wait(bar(8 + (n & 7)), (n >> 3) + 1);
        if (elect_one()) {
          mbar_expect_tx(fb, job < 2 ? 24576 : 16384);
          tma4d(dst, &P.tm[job < 2 ? M_WQKV : M_W13], (e * 2 + (n & 1)) * 64, (n & 30) * 32, job < 2 ? job : job - 2, fb);
        }
        __syncwarp();
      }
    }
  } else {
    const uint32_t tag = ld_epoch(sc->epoch + NCTA + e);
    const int lane = tid & 31;
#pragma unroll 1
    for (int job = 0; job < 9; job++) {
      float s[3][4] = {};
#pragma unroll 1
      for (int n = job * 32 + wg; n < job * 32 + 32; n += 2) {
        mbar_wait(bar(n & 7), n >> 3);
        wgmma_fence();
        const uint32_t a = ((SB + (n & 7) * 24576) >> 4) + 0x2000000;
#pragma unroll
        for (int k = 0; k < 8; k++) wgmma_cs(s[k & 1], dsc(0x40000040u, a + (k & 1) * 512 + (k >> 1) * 128), dsc(0x40000040u, (SM_STG >> 4) + 0x10000));
        if (job < 2) {
          wgmma_fence();
#pragma unroll
          for (int k = 0; k < 4; k++) wgmma_cs(s[2], dsc(0x40000040u, a + 1024 + k * 128), dsc(0x40000040u, (SM_STG >> 4) + 0x10000));
        }
        wgmma_commit();
        wgmma_wait<0>();
        mbar_arrive_if(bar(8 + (n & 7)), (tid & 127) == 0);
      }
      if (!(lane & 2))
        st_tag(&sc->cs[job][e * 2 + wg][w * 16 + (lane & 1) * 8 + (lane >> 2)], __float_as_uint(lane & 1 ? s[0][2] : s[0][0]), __float_as_uint(lane & 1 ? s[1][2] : s[1][0]),
               __float_as_uint(lane & 1 ? s[2][2] : s[2][0]), tag);
      __syncwarp();
    }
    bar_sync(NB_END, 256);
    if (tid == 0) sc->epoch[NCTA + e] = tag;
  }
}

template <bool WEIGHTS>
__device__ __forceinline__ void producer(const Params& P, const uint2* tab, int nop, int lane, int c, int row, int par, uint32_t t_entry) {
  uint64_t pol;
  asm volatile("createpolicy.fractional.L2::evict_first.b64 %0, 1.0;" : "=l"(pol));
  __syncthreads();
  uint2 nx = __ldg(tab + lane), n2 = __ldg(tab + 32 + lane);
#pragma unroll 1
  for (int j = 1; j < FIRST; j++) {
    delay_until(t_entry, ST_T1 + (j - 1) * ST_D1);
    if (elect_one()) {
      mbar_expect_tx(bar(B_FULL) + 8 * j, WEIGHTS ? 24576 : 16384);
      if (WEIGHTS) tma4d(SB + j * 40960 + 16384, &P.tm[M_WQKV], c * 64, j * 64, 0, bar(B_FULL) + 8 * j);
      else tma3d(SB + j * 40960, &P.tm[M_X0], j * 64, row, par, bar(B_FULL) + 8 * j);
    }
    __syncwarp();
  }
  if (!WEIGHTS && lane == 0) {
#pragma unroll
    for (int j = 0; j < FIRST; j++) mbar_arrive(bar(B_EMPTY + 2 + j));
  }
  __syncwarp();
  auto word = [&](uint2 e) { return e.x + (((int)(e.y & 7) > c) + (e.y & 8 ? c : 0)) * 64; };
  uint32_t xn = __shfl_sync(0xffffffffu, word(nx), 0);
  const uint64_t maps = reinterpret_cast<uint64_t>(&P.tm[WEIGHTS ? M_WQKV : 0]);
  if ((uint32_t)maps > 0xfffff000u) __trap();
  const uint32_t sb = uni(SB, lane), bars = uni(BARS, lane), zero = uni(0, lane), mlo = uni((uint32_t)maps, lane), mhi = uni(maps >> 32, lane);
#pragma unroll 1
  for (int base = 0; base < nop; base += 32) {
    const uint2 e = nx;
    nx = n2;
    n2 = __ldg(tab + base + 64 + lane);
    const uint32_t xw = word(lane ? e : nx), bytes = e.y & 0xe000, eb = (e.y >> 6) & 0x78;
    const int arr = e.y & 16 ? lane + 1 : 0, solo = e.y & 32 ? lane + 1 : 0;
#pragma unroll 1
    for (int j = 1; j <= 32; j++) {
      const uint32_t x = xn;
      xn = __shfl_sync(0xffffffffu, xw, j);
#define OP_WAIT(X) "{\n.reg .pred pe, pa, pn, ps, pw;\n.reg .u32 it;\n" \
                "elect.sync _|pe, 0xffffffff;\nsetp.eq.u32 pa, %0, %1;\nsetp.ne.and.u32 pn, %2, 0, pe;\n" X \
                "mov.u32 it, 0;\n" \
                "WAIT_%=:\n" \
                "mbarrier.try_wait.parity.shared::cta.b64 pw, [%3 + %9], %4;\n" \
                "@pw bra.uni GO_%=;\n" \
                "add.u32 it, it, 1;\nsetp.lt.u32 pw, it, 0x10000;\n" \
                "@pw bra.uni WAIT_%=;\n" \
                "trap;\n" \
                "GO_%=:\n"
#define OP_ARGS "r"(arr), "r"(j), "r"(x & (1 << 12)), "r"((x >> 21) & 0x3f8), "r"(x >> 31), "r"(((x >> 15) & 0x1f8) | bars), "r"(bytes), "r"((x & 0x3e000) | sb), \
                "l"(dsc(mhi, mlo + (x & 0x38) * 16)), "n"(BARS), "r"(x & 0xfc0), "r"(x & 7)
      if (WEIGHTS)
        asm volatile(OP_WAIT("")
                     "@pn cp.async.bulk.tensor.4d.shared::cluster.global.mbarrier::complete_tx::bytes.L2::cache_hint [%7], [%8, {%12, %10, %13, %11}], [%5], %14;\n"
                     "@pa mbarrier.arrive.expect_tx.shared::cta.b64 _, [%5], %6;\n"
                     "}\n" ::OP_ARGS, "r"(c * 64), "r"(zero), "l"(pol) : "memory");
      else
        asm volatile(OP_WAIT(".reg .pred pf;\nsetp.ne.u32 pf, %11, 0;\nsetp.eq.u32 ps, %14, %1;\n")
                     "@pn cp.async.bulk.tensor.3d.shared::cluster.global.mbarrier::complete_tx::bytes [%7], [%8, {%10, %12, %13}], [%5];\n"
                     "@pf fence.proxy.async.shared::cta;\n"
                     "@pa mbarrier.arrive.expect_tx.shared::cta.b64 _, [%5], %6;\n"
                     "@ps mbarrier.arrive.shared::cta.b64 _, [%15 + %16];\n"
                     "}\n" ::OP_ARGS, "r"(row), "r"(par), "r"(solo), "r"(eb), "n"(bar(B_EMPTY)) : "memory");
    }
  }
}

template <int N, uint32_t LO> __device__ __forceinline__ void advance(uint32_t& x, uint32_t inc) {
  constexpr uint32_t LEN = (N == 192 ? NU : 24) * 512;
  x += inc; if (x >= LO + LEN) x -= LEN;
}
__device__ __forceinline__ bool full_test(uint32_t i8) {
  uint32_t ok;
  asm volatile("{\n.reg .pred p;\nmbarrier.test_wait.parity.shared::cta.b64 p, [%1 + %3], %2;\nselp.u32 %0, 1, 0, p;\n}\n" : "=r"(ok) : "r"(i8 & 0x78), "r"(i8 >> 7), "n"(bar(B_FULL)) : "memory");
  return ok;
}
__device__ __forceinline__ void full_wait(uint32_t i8) { mbar_wait(bar(B_FULL) + (i8 & 0x78), i8 >> 7); }
__device__ __forceinline__ void release(uint32_t i8, uint32_t p) {
  asm volatile("{\n.reg .pred q;\nsetp.ne.u32 q, %1, 0;\n@q mbarrier.arrive.shared::cta.b64 _, [%0 + %2];\n}\n" ::"r"(i8 & 0x78), "r"(p), "n"(bar(B_EMPTY)) : "memory");
}
template <int N, int RELK, int FIRSTK>
__device__ __forceinline__ bool kstep(float (&acc)[2][N / 2], uint32_t hiA, uint32_t hiB, uint32_t& a, uint32_t& b, uint32_t inc, uint32_t& i8, uint32_t x) {
  constexpr uint32_t MI = N == 192 ? 64 : 512;
  wgmma_fence();
  if (FIRSTK == 2) { wgmma_z(acc[0], dsc(hiA, a), dsc(hiB, b)); wgmma_z(acc[1], dsc(hiA, a + MI), dsc(hiB, b)); }
  else { wgmma(acc[0], dsc(hiA, a), dsc(hiB, b)); wgmma(acc[1], dsc(hiA, a + MI), dsc(hiB, b)); }
  i8 += 8;
  const bool ok = full_test(i8);
#pragma unroll
  for (int k = 1; k < 4; k++) {
    wgmma(acc[0], dsc(hiA, a + 2 * k), dsc(hiB, b + 128 * k)); wgmma(acc[1], dsc(hiA, a + MI + 2 * k), dsc(hiB, b + 128 * k));
    if (k == RELK || k == 3) wgmma_commit();
    if (k == 3) { advance<N, LO_A>(a, inc); advance<N, LO_B>(b, inc); }
    if (!FIRSTK && k == RELK) {
      wgmma_wait<1>();
      release(i8, x);
    }
  }
  return ok;
}
template <int MODE, int N, class F, class G>
__device__ __forceinline__ void mainloop(float (&acc)[2][N], uint32_t sig, int t, int wg, uint32_t& sp, F&& prepare, G&& first_half) {
  const uint32_t turn = bar(B_TURN) + 8 * (wg ^ 1);
  constexpr uint32_t hiA = MODE == 0 ? 0x40000080u : 0x40000040u, hiB = 0x40000040u;
  constexpr Seg S0 = GEN.s.seg[0];
  uint32_t i8 = S0.i8 & 0xffff, nxt = S0.end8 & 0xffff, a = S0.a, b = S0.b, inc = S0.end8 >> 16;
  if (MODE != 0 || t != 0) {
    if (MODE == 2 || (MODE == 0 ? t != 12 : t != 4 && t != 15)) mbar_wait(bar(B_TURN) + 8 * wg, (t - 1) >> 1);
    i8 = c_sched.seg[sp].i8 & 0xffff; nxt = c_sched.seg[sp].end8 & 0xffff; a = c_sched.seg[sp].a; b = c_sched.seg[sp].b; inc = c_sched.seg[sp].end8 >> 16;
  }
  uint32_t hiA_ = hiA, hiB_ = hiB;
  if (MODE == 2) { hiA_ = uni(hiA, lane_now()); hiB_ = uni(hiB, lane_now() * 2); }
  full_wait(i8);
  TL(t, 2);
  TS(i8, wg);
  bool ok = kstep<N * 2, 3, MODE == 2 ? 1 : 2>(acc, hiA_, hiB_, a, b, inc, i8, 0);
  if (MODE == 2 && (t == 2 || t == 13)) bar_sync(NB_OGO, 256);
#pragma unroll 1
  while (true) {
    uint32_t act;
    if (MODE != 2) { hiA_ = uni(hiA, lane_now()); hiB_ = uni(hiB, lane_now() * 2); }
#pragma unroll 1
    while (true) {
      if (!ok) full_wait(i8);
      TS(i8, wg);
      ok = kstep<N * 2, MODE == 1 ? 1 : 3, 0>(acc, hiA_, hiB_, a, b, inc, i8, sig);
      if (__builtin_expect(i8 == nxt, 0)) {
        act = c_sched.seg[sp++].i8 >> 16;
        if (MODE == 1) mbar_arrive_if(turn, sig & (act >> 1));
        if (act & (MODE == 0 ? A_END | A_DRAIN | A_SYNC : MODE == 1 ? A_END | A_DRAIN : A_END)) break;
        nxt = c_sched.seg[sp].end8 & 0xffff; a = c_sched.seg[sp].a; b = c_sched.seg[sp].b;
        if (MODE == 1) inc = c_sched.seg[sp].end8 >> 16;
      }
    }
    if (MODE == 2 || (act & A_END)) break;
    nxt = c_sched.seg[sp].end8 & 0xffff; a = c_sched.seg[sp].a; b = c_sched.seg[sp].b;
    if (MODE == 1) inc = c_sched.seg[sp].end8 >> 16;
    if (MODE == 0 && (act & A_SYNC)) bar_arrive(NB_PX, 256);
    wgmma_wait<0>();
    release(i8 + 8, sig);
    i8 = c_sched.seg[sp].i8 & 0xffff;
    if (MODE == 1 || (act & A_WAIT)) mbar_wait(bar(B_TURN) + 8 * wg, (t - 1) >> 1);
    full_wait(i8);
    if (MODE == 0 && (act & A_SYNC)) bar_sync(NB_PY, 256);
    TS(i8, wg);
    ok = kstep<N * 2, 3, 1>(acc, hiA, hiB, a, b, inc, i8, 0);
  }
  if (MODE != 1) {
    constexpr int TL_ = MODE == 0 ? TAILQ : TAIL;
    uint32_t ta[TL_], tb[TL_];
#pragma unroll
    for (int x = 0; x < TL_; x++) {
      full_wait(i8 + 8 * x);
      TS(i8 + 8 * x, wg);
      ta[x] = a; tb[x] = b;
      advance<N * 2, LO_A>(a, inc); advance<N * 2, LO_B>(b, inc);
    }
#pragma unroll
    for (int h = 0; h < 2; h++) {
      const int mi = MODE == 0 ? 1 - h : h;
      wgmma_fence();
#pragma unroll
      for (int x = 0; x < TL_; x++)
#pragma unroll
        for (int k = 0; k < 4; k++) wgmma(acc[mi], dsc(hiA, ta[x] + mi * (MODE == 0 ? 64 : 512) + 2 * k), dsc(hiB, tb[x] + 128 * k));
      wgmma_commit();
      if (TL_ > 1 && h == 0) { wgmma_wait<1>(); release(i8 + 8, sig); prepare(); }
    }
    mbar_arrive_if(turn, sig);
    if (TL_ == 1) { wgmma_wait<2>(); release(i8 + 8, sig); prepare(); }
    wgmma_wait<1>();
    first_half();
    wgmma_wait<0>();
#pragma unroll
    for (int x = 0; x < TL_; x++) release(i8 + 16 + 8 * x, sig);
  } else {
    prepare();
    wgmma_wait<0>();
    release(i8 + 8, sig);
  }
}

template <int SWAP, int BY_SM>
__global__ void __launch_bounds__(384, 1) fused_kernel(Scratch* sc, const Ops* ops, const bf16* x0, bf16* out, const __grid_constant__ Params P) {
  extern __shared__ __align__(1024) uint8_t smem_raw[];
  const int tid = threadIdx.x;
  if (tid == 0) prefetch_tmap(&P.tm[M_X0]);
  if (tid == 128) prefetch_tmap(&P.tm[M_WQKV]);
  if (tid == 256) { mbar_init(bar(B_FULL), 2); fence_bar_init(); fence_proxy_async_smem(); }
  const int wg = __shfl_sync(0xffffffffu, tid >> 7, 0);
  const int w = __shfl_sync(0xffffffffu, (tid >> 5) & 3, 0);
  const int lane = tid & 31;
  const uint32_t t_entry = clock_now();
  int b = blockIdx.x, c = ((b >> 2) & 7) ^ (((b >> 5) & 1) * 7), mr = b & 3;
  if (BY_SM) {
    uint32_t smid; asm volatile("mov.u32 %0, %%smid;" : "=r"(smid));
    const int tp = smid >> 1;
    const int q7 = (tp - 32) * 37 >> 8;
    const int v0 = (tp & 7) * 8 + (tp >> 3), v1 = tp * 8 - 244 - q7 * 55, v2 = tp < 62 ? tp + 4 : tp - 58;
    b = (tp < 32 ? v0 : tp < 60 ? v1 : v2) * 2 + (smid & 1);
    c = (b & 1) | ((b >> 1) & 2) | ((b >> 2) & 4); mr = ((b >> 1) & 1) | ((b >> 2) & 2);
  }
  const int mg = (b >> 5) & 3, m = mg * 4 + mr;
  const int row0 = (m & 7) * 128, par = m >> 3;
  if (__builtin_expect(b >= NCTA, 0)) { helper_cta(P, sc, b - NCTA, wg, w); return; }
  if (wg == 2 && w == 0) {
    if (elect_one()) {
      tma3d(SB, &P.tm[M_X0], 0, row0, par, bar(B_FULL));
      tma4d(SB + 16384, &P.tm[M_WQKV], c * 64, 0, 0, bar(B_FULL));
      mbar_expect_tx(bar(B_FULL), 40960);
      mbar_arrive(bar(B_FULL));
    }
    __syncwarp();
    TLW(0, 1);
  }
  if (__builtin_expect(wg == 2, 0)) {
    reg_dealloc<40>();
    if (w < 2) {
      if (w == 0) producer<false>(P, ops->a, NOP0, lane, c, row0, par, t_entry);
      else producer<true>(P, ops->b, NOP1, lane, c, row0, par, t_entry);
    } else if (w == 2) {
      if (smem_u32(smem_raw) != SB) __trap();
      if (lane == 0) {
#pragma unroll
        for (int x = 1; x < B_CS; x++) mbar_init(bar(x), x < B_SIG ? 2 : x <= B_STAT ? 4 : 1);
        fence_bar_init();
        fence_proxy_async_smem();
      }
      __syncthreads();
      const uint32_t tag = ld_epoch(sc->epoch + b);
      uint32_t* const flag = sc->flags[m * 8 + c];
      if (lane < 4) asm volatile("st.relaxed.gpu.global.v4.u32 [%0], {%1, %1, %1, %1};" ::"l"(flag + lane * 4), "r"(tag * 32 - 1) : "memory");
      __syncwarp();
      int ev = 0;
      uint32_t t_st = t_entry;
#pragma unroll 1
      for (int t = 0; t < 21; t++) {
        const int i = t >= 11 ? t - 11 : t;
        const bool od = i == 2 || i == 10;
        const uint32_t sig = c_sched.task[t].sig;
        const uint32_t pf = i == 0 ? 1 << M_OL | 1 << M_O | 1 << M_WO : i == 1 ? 1 << M_O24 | 1 << M_W13 | 1 << M_W13P | 1 << M_YL | 1 << M_Y : i == 3 ? 1 << M_HL :
                            i == 7 ? 1 << M_H | 1 << M_W2 : i == 10 ? 1 << M_WQKV | 1 << M_YL | 1 << M_Y : 0;
        if ((pf >> lane) & 1) prefetch_tmap(&P.tm[lane]);
        __syncwarp();
#pragma unroll 1
        for (int x = i == 1 || od ? 0 : 1; x < (i == 1 ? 1 : 2); x++) {
          if (x == 0) {
            if (i == 1) {
              mbar_wait(bar(B_SIG), sig);
              fence_proxy_async_smem();
#pragma unroll 1
              for (int r = 8; r < 128; r += 32) tma3d_store(&P.tm[M_O24], SM_STG + r * 128, (8 + c) * 64, row0 + r, par);
            }
            mbar_wait(bar(B_SIG + 1), sig >> 1);
          } else {
            const CUtensorMap* mp = &P.tm[i == 0 ? M_OL : od ? M_YL : M_HL];
            const uint32_t src = od ? SB + ((c_sched.task[t].stg >> 8) & 31) * 8192 : SM_STG;
            const int col = ((od ? 1 : i ? i - 3 : 0) * 8 + c) * 64, gap = i == 0 ? GAP_O : od ? GAP_Y : i == 9 ? GAP_H6 : GAP_H;
            const int nr = i && !od ? 64 : 128;
#pragma unroll 1
            for (int r0 = 0; r0 < 128; r0 += nr) {
              const int s = od ? 3 : i ? r0 >> 6 : 1;
              mbar_wait(bar(B_SIG) + 8 * s, sig >> s);
              if (od) mbar_wait(bar(B_DEP - 1) + 8 * ev, 0);
              fence_proxy_async_smem();
              const uint32_t now = clock_now();
              if ((int)(now - t_st) > 0) t_st = now;
#pragma unroll 1
              for (int r = r0; r < r0 + nr; r += PROWS) {
                delay_until(t_st, 0);
                t_st += gap;
                tma3d_store(mp, src + r * 128, col, row0 + r, par);
              }
            }
          }
          if (elect_one()) {
            if (x || (i == 1)) { bulk_commit(); bulk_wait(); }
            if (x || !od) mbar_arrive(od ? bar(B_SF) : bar(B_FREE));
            if (i < 3 || i > 6) {
              asm volatile("fence.proxy.async.global;" ::: "memory");
              if (od && x == 0) asm volatile("red.release.gpu.global.add.u32 [%0], 1;" ::"l"(&sc->cnt[mg][ev]) : "memory");
              else st_release(flag, tag * 32 + ev);
              mbar_arrive(bar(B_PUB) + 8 * ev);
            }
          }
          __syncwarp();
          if (i < 3 || i > 6) ev++;
          if (x == 0 || !od) TLW(t, 4);
        }
      }
      if (lane == 0) sc->epoch[b] = tag;
    } else {
      if (lane == 0) {
#pragma unroll
        for (int x = B_CS; x < B_N; x++) mbar_init(bar(x), x == B_RF ? 4 : 1);
        fence_bar_init();
      }
      __syncthreads();
      const uint32_t tag = ld_epoch(sc->epoch + b);
      delay_until(t_entry, WARM_T);
      asm volatile("st.shared.u32 [%0], %1;" ::"r"(SM_TAG + 4), "r"(reinterpret_cast<const uint32_t*>(&c_sched)[min(lane * 16, (int)sizeof(Sched) / 4 - 1)]) : "memory");
      int ncs = 0;
#pragma unroll 1
      for (int it = 0; it < 20; it++) {
        const int l = it >= 11, i = it - l * 11, e = i < 2 ? 0 : i - 2, ev = l * E_N + e;
#pragma unroll 1
        for (; ncs < (it < 2 ? it + 1 : it < 6 ? 2 : 9); ncs++) {
          uint4 v[2];
          ld_tag_wait<200>(v, &sc->cs[ncs][c][lane], tag);
          const uint32_t a = SM_CS + (ncs < 2 ? ncs * 768 : 512 + ncs * 512) + ((lane & 17) | (lane & 6) << 1 | (lane & 8) >> 2) * 4;
#pragma unroll
          for (int j = 0; j < 2; j++) {
            sts4f(a + j * 128, __uint_as_float(v[j].x)); sts4f(a + j * 128 + 256, __uint_as_float(v[j].y));
            if (ncs < 2) sts4f(a + j * 128 + 512, __uint_as_float(v[j].z));
          }
          mbar_arrive_warp(bar(B_CS) + 8 * ncs);
        }
        if (i == 0 || i == 2) {
          const int u = l * 2 + (i >> 1);
          uint4 v[6] = {};
          mbar_wait(bar(B_QT), u);
          if (m & 7) ld_tag_wait<0>(v, &sc->halo[u][m - 1][c][0][lane], tag);
          const uint32_t xa = xch(i, 0) + lane * 16;
          sts16(xa, v[0].x, v[0].y, v[0].z, v[1].x); sts16(xa + 512, v[1].y, v[1].z, v[2].x, v[2].y);
          sts16(xa + 1024, v[2].z, v[3].x, v[3].y, v[3].z); sts16(xa + 1536, v[4].x, v[4].y, v[4].z, v[5].x);
          if (lane < 4) sts16(stat(l * 2) - 64 + lane * 16, v[5].y, 0, v[5].z, 0);
          mbar_arrive_warp(bar(B_XCH));
          continue;
        }
        mbar_wait(bar(B_PUB) + 8 * ev, 0);
        const bool all = e == E_YA || e == E_XA;
        wait_flags(all ? &sc->cnt[mg][ev] : sc->flags[m * 8 + (lane & 7)], tag * 32 + (all ? 0 : ev));
        mbar_arrive_warp(bar(B_DEP) + 8 * ev);
        if (e == E_YB || e == E_XB) {
          const int p = e == E_XB ? 1 : l * 2;
          if (elect_one()) {
            mbar_expect_tx(bar(B_SF + 1), 8192);
            asm volatile("cp.async.bulk.shared::cluster.global.mbarrier::complete_tx::bytes [%0], [%1], 8192, [%2];" ::"r"(SM_STG), "l"(&sc->stat[p][m][0][0]), "r"(bar(B_SF + 1)) : "memory");
          }
          __syncwarp();
          mbar_wait(bar(B_SF + 1), p);
#pragma unroll 1
          for (int h = 0; h < 2; h++) {
            float s0 = 0.f, q0 = 0.f, s1 = 0.f, q1 = 0.f;
#pragma unroll 4
            for (int j = 0; j < 8; j++) {
              float x0, x1, x2, x3;
              lds16f(SM_STG + j * 1024 + h * 512 + lane * 16, x0, x1, x2, x3);
              s0 += x0; q0 += x1; s1 += x2; q1 += x3;
            }
            const float2 r0 = ln_finish(s0, q0), r1 = ln_finish(s1, q1);
            sts16(stat(p + 1) + (h * 64 + lane * 2) * 8, __float_as_uint(r0.x), __float_as_uint(r0.y), __float_as_uint(r1.x), __float_as_uint(r1.y));
          }
          mbar_arrive_warp(bar(B_STAT) + 8 * (p + 1));
        }
      }
    }
  } else {
    const int tw = tid & 127;
    reg_alloc<232>();
    uint32_t sig;
    asm volatile("mov.u32 %0, %1;" : "=r"(sig) : "r"((uint32_t)(tw == 0)));
    __syncthreads();

    if (wg == 1) {
      const uint32_t tag = ld_epoch(sc->epoch + b);
      uint4* const mine = &sc->stat0[m][c * 16 + w * 4 + (lane >> 3)];
      if ((lane & 7) == 0) st_tag(mine, 0, 0, 0, 0);
      __syncwarp();
      delay_until(t_entry, ST_ROWS);
      const bf16* xr = x0 + (size_t)((row0 + c * 16 + w * 4 + (lane >> 3)) * 2 + par) * D_ + (lane & 7) * 8;
      float sum = 0.f, sq = 0.f;
#pragma unroll 1
      for (int j0 = 0; j0 < 16; j0 += 4) {
        uint4 xv[4];
#pragma unroll
        for (int j = 0; j < 4; j++) xv[j] = ldcg16(xr + (j0 + j) * 64);
#pragma unroll
        for (int j = 0; j < 4; j++) {
          const uint32_t x[4] = {xv[j].x, xv[j].y, xv[j].z, xv[j].w};
#pragma unroll
          for (int e = 0; e < 8; e++) { const float d = e & 1 ? bf_hi(x[e >> 1]) : bf_lo(x[e >> 1]); sum += d; sq = fmaf(d, d, sq); }
        }
      }
#pragma unroll
      for (int o = 4; o > 0; o >>= 1) { sum += __shfl_xor_sync(0xffffffffu, sum, o); sq += __shfl_xor_sync(0xffffffffu, sq, o); }
      const float2 fin = ln_finish(sum, sq);
      if ((lane & 7) == 0) st_tag(mine, __float_as_uint(fin.x), __float_as_uint(fin.y), 0, tag);
      __syncwarp();
      TL(22, 5);
      uint4 v[1];
      ld_tag_wait<200>(v, &sc->stat0[m][tw], tag);
      sts8f(stat(0) + tw * 8, __uint_as_float(v[0].x), __uint_as_float(v[0].y));
      if (tw == 0) { asm volatile("st.shared.u32 [%0], %1;" ::"r"(SM_TAG), "r"(tag) : "memory"); sts16(SM_ZERO, 0, 0, 0, 0); }
      mbar_arrive_warp(bar(B_STAT));
      TL(22, 6);
    }

    uint32_t sp = wg * NSEG;
#pragma unroll 1
    for (int t = wg; t < 22; t += 2) {
      const int l = t >= 11, i = t - l * 11;
      if (t == 0) TL(t, 0);
      if (i < 2) {
        float acc[2][96];
        if (w == 3 && (m & 7) < 7) {
#pragma unroll
          for (int j = 0; j < 6; j++) st_tag(&sc->halo[l * 2 + i][m][c][j][lane_now()], 0, 0, 0, 0);
        }
        uint32_t Q[4][8], K[4][8], V[4][8], sta, csa;
        float2 st[4];
        auto fix = [&](int g, int j, float2 cs) {
          const int mi = g & 1, half = g >> 1;
          return pack_bf16_v(fmaf(st[g].y, cs.x, acc[mi][j * 4 + half * 2]), fmaf(st[g].y, cs.y, acc[mi][j * 4 + half * 2 + 1]));
        };
        mainloop<0>(acc, sig, t, wg, sp, [&]() {
          const int lane = lane_now();
          mbar_wait(bar(B_FREE), l * 9 + i - 1);
          mbar_wait(bar(B_STAT) + l * 16, 0);
          mbar_wait(bar(B_CS) + i * 8, 0);
          sta = stat(l * 2) + w * 256;
          csa = SM_CS + i * 768 + (lane & 3) * 16;
          st[1] = lds8f(sta + (8 + (lane >> 2)) * 8); st[3] = lds8f(sta + (24 + (lane >> 2)) * 8);
        }, [&]() {
          const int lane = lane_now();
          mbar_arrive_if(bar(B_QT), sig);
#pragma unroll
          for (int j = 0; j < 8; j += 2) {
            float2 c0, c1;
            lds16f(csa + (16 + j) * 32, c0.x, c0.y, c1.x, c1.y);
            V[3][j] = movmat(fix(3, 16 + j, c0)); V[3][j + 1] = movmat(fix(3, 17 + j, c1));
            lds16f(csa + (8 + j) * 32, c0.x, c0.y, c1.x, c1.y);
            K[3][j] = fix(3, 8 + j, c0); K[3][j + 1] = fix(3, 9 + j, c1);
          }
          if (w < 3) {
            const uint32_t xa = xch(i, w + 1) + lane * 16;
            sts16(xa, K[3][0], K[3][1], K[3][2], K[3][3]); sts16(xa + 512, K[3][4], K[3][5], K[3][6], K[3][7]);
            sts16(xa + 1024, V[3][0], V[3][1], V[3][2], V[3][3]); sts16(xa + 1536, V[3][4], V[3][5], V[3][6], V[3][7]);
            mbar_arrive_warp(bar(B_XCH));
          } else if ((m & 7) < 7) {
            const uint32_t tag = lds4(SM_TAG), r0 = lds4(sta + (24 + 2 * (lane & 3)) * 8), r1 = lds4(sta + (25 + 2 * (lane & 3)) * 8);
            uint4* const p = &sc->halo[l * 2 + i][m][c][0][lane];
            st_tag(p, K[3][0], K[3][1], K[3][2], tag); st_tag(p + 32, K[3][3], K[3][4], K[3][5], tag); st_tag(p + 64, K[3][6], K[3][7], V[3][0], tag);
            st_tag(p + 96, V[3][1], V[3][2], V[3][3], tag); st_tag(p + 128, V[3][4], V[3][5], V[3][6], tag); st_tag(p + 160, V[3][7], r0, r1, tag);
          }
        });
        TL(t, 3);
        const int lane = lane_now(), q = lane & 3, r8 = lane >> 2;
        st[0] = lds8f(sta + r8 * 8); st[2] = lds8f(sta + (16 + r8) * 8);
#pragma unroll
        for (int j0 = 22; j0 >= 0; j0 -= 2) {
          float2 cs[2];
          lds16f(csa + j0 * 32, cs[0].x, cs[0].y, cs[1].x, cs[1].y);
#pragma unroll
          for (int j = j0; j < j0 + 2; j++)
#pragma unroll
            for (int g = 0; g < (j < 8 ? 4 : 3); g++) {
              const uint32_t pk = fix(g, j, cs[j - j0]);
              if (j < 8) Q[g][j] = pk; else if (j < 16) K[g][j - 8] = pk; else V[g][j - 16] = movmat(pk);
            }
        }
        const bool up0 = (2 * q) > r8, up1 = (2 * q + 1) > r8;
        const uint32_t mskP = (up0 ? 0xffffu : 0u) | (up1 ? 0xffff0000u : 0u);
        TL(t, 5);
        uint32_t Kp[8] = {}, Vp[8] = {}, PS[2][4] = {}, PP[2][4] = {};
        float sS[2][4][2], sP[2][4][2] = {}, O[2][4][4][2], z0, z1, z2, z3;
        auto receive = [&]() {
          const uint32_t xa = xch(i, w) + lane * 16;
          mbar_wait(bar(B_XCH), i);
          lds16(xa, Kp[0], Kp[1], Kp[2], Kp[3]); lds16(xa + 512, Kp[4], Kp[5], Kp[6], Kp[7]);
          lds16(xa + 1024, Vp[0], Vp[1], Vp[2], Vp[3]); lds16(xa + 1536, Vp[4], Vp[5], Vp[6], Vp[7]);
          TL(i == 0 ? 22 : 23, t < 11 ? 3 : 4);
        };
        auto score0 = [&]() {
          float dm0, dm1;
#pragma unroll
          for (int h = 0; h < 2; h++) mma16816(sP[h][0][0], sP[h][0][1], dm0, dm1, Q[0][h * 4], Q[0][h * 4], Q[0][h * 4 + 1], Q[0][h * 4 + 1], Kp[h * 4], Kp[h * 4 + 1], z0, z1, z2, z3);
#pragma unroll
          for (int h = 0; h < 2; h++)
            mma16816(sP[h][0][0], sP[h][0][1], dm0, dm1, Q[0][h * 4 + 2], Q[0][h * 4 + 2], Q[0][h * 4 + 3], Q[0][h * 4 + 3], Kp[h * 4 + 2], Kp[h * 4 + 3], sP[h][0][0], sP[h][0][1], 0.f, 0.f);
        };
        auto softmax = [&](int g) {
          const float rk0 = lds4f(sta + (g * 8 + 2 * q - (up0 ? 8 : 0)) * 8), rk1 = lds4f(sta + (g * 8 + 2 * q + 1 - (up1 ? 8 : 0)) * 8);
          const float f = st[g].x * (0.17677669529663687f * LOG2E), f0 = f * rk0, f1 = f * rk1;
          const bool noprev = g == 0 && (m & 7) == 0 && w == 0;
#pragma unroll
          for (int h = 0; h < 2; h++) {
            float v0 = (up0 ? sP[h][g][0] : sS[h][g][0]) * f0, v1 = (up1 ? sP[h][g][1] : sS[h][g][1]) * f1;
            if (noprev && up0) v0 = -1e9f * LOG2E;
            if (noprev && up1) v1 = -1e9f * LOG2E;
            float mx = fmaxf(v0, v1);
            mx = fmaxf(mx, __shfl_xor_sync(0xffffffffu, mx, 1)); mx = fmaxf(mx, __shfl_xor_sync(0xffffffffu, mx, 2));
            const float e0 = ex2f(v0 - mx), e1 = ex2f(v1 - mx);
            float sum = e0 + e1;
            sum += __shfl_xor_sync(0xffffffffu, sum, 1); sum += __shfl_xor_sync(0xffffffffu, sum, 2);
            const float inv = rcpf(sum);
            const uint32_t pk = pack_bf16_v(e0 * inv * rk0, e1 * inv * rk1);
            PS[h][g] = pk & ~mskP; PP[h][g] = pk & mskP;
          }
        };
        const uint32_t sa = SM_STG + (w * 32 + (lane & 7)) * 128 + (((lane >> 3) ^ (lane & 7)) << 4);
        auto stage = [&](int g) {
#pragma unroll
          for (int h = 0; h < 2; h++)
            stsm4((sa ^ (h * 64)) + g * 1024, pack_bf16_v(O[h][g][0][0], O[h][g][0][1]), pack_bf16_v(O[h][g][1][0], O[h][g][1][1]),
                  pack_bf16_v(O[h][g][2][0], O[h][g][2][1]), pack_bf16_v(O[h][g][3][0], O[h][g][3][1]));
        };
        if (i == 0) { receive(); bar_sync(NB_PX, 256); }
        lds16f(SM_ZERO, z0, z1, z2, z3);
        if (i == 0) score0();
#pragma unroll
        for (int h = 0; h < 2; h++) {
          float dm0, dm1;
          const int j0 = h * 4;
#pragma unroll
          for (int g = 0; g < 3; g++) mma16816(sS[h][g][0], sS[h][g][1], sP[h][g + 1][0], sP[h][g + 1][1], Q[g][j0], Q[g + 1][j0], Q[g][j0 + 1], Q[g + 1][j0 + 1], K[g][j0], K[g][j0 + 1], z0, z1, z2, z3);
          mma16816(sS[h][3][0], sS[h][3][1], dm0, dm1, Q[3][j0], Q[3][j0], Q[3][j0 + 1], Q[3][j0 + 1], K[3][j0], K[3][j0 + 1], z0, z1, z2, z3);
        }
#pragma unroll
        for (int h = 0; h < 2; h++) {
          float dm0, dm1;
          const int j0 = h * 4 + 2;
#pragma unroll
          for (int g = 0; g < 3; g++) mma16816(sS[h][g][0], sS[h][g][1], sP[h][g + 1][0], sP[h][g + 1][1], Q[g][j0], Q[g + 1][j0], Q[g][j0 + 1], Q[g + 1][j0 + 1], K[g][j0], K[g][j0 + 1],
                                               sS[h][g][0], sS[h][g][1], sP[h][g + 1][0], sP[h][g + 1][1]);
          mma16816(sS[h][3][0], sS[h][3][1], dm0, dm1, Q[3][j0], Q[3][j0], Q[3][j0 + 1], Q[3][j0 + 1], K[3][j0], K[3][j0 + 1], sS[h][3][0], sS[h][3][1], 0.f, 0.f);
        }
        if (i == 0) { bar_arrive(NB_PY, 256); softmax(0); }
#pragma unroll
        for (int g = 1; g < 4; g++) softmax(g);
        TL(23, i == 0 ? (t < 11 ? 5 : 6) : 7);
        if (i == 0) bar_sync(NB_PX + ((PS[0][1] | PS[0][2] | PS[0][3] | PS[1][1] | PS[1][2] | PS[1][3]) & __float_as_uint(z0)), 256);
        lds16f(SM_ZERO, z0, z1, z2, z3);
        auto pv0 = [&]() {
#pragma unroll
          for (int x = 0; x < 8; x++) {
            float dm0, dm1;
            mma16816(O[x >> 2][0][x & 3][0], O[x >> 2][0][x & 3][1], dm0, dm1, PS[x >> 2][0], 0u, PP[x >> 2][0], 0u, V[0][x], Vp[x], z0, z1, z2, z3);
          }
        };
#pragma unroll
        for (int x = 0; x < 8; x++) {
          const int h = x >> 2, j = x & 3;
          mma16816(O[h][1][j][0], O[h][1][j][1], O[h][2][j][0], O[h][2][j][1], PS[h][1], PP[h][2], PP[h][1], 0u, V[1][x], V[0][x], z0, z1, z2, z3);
        }
#pragma unroll
        for (int x = 0; x < 8; x++) {
          const int h = x >> 2, j = x & 3;
          mma16816(O[h][3][j][0], O[h][3][j][1], O[h][2][j][0], O[h][2][j][1], PS[h][3], 0u, PP[h][3], PS[h][2], V[3][x], V[2][x], 0.f, 0.f, O[h][2][j][0], O[h][2][j][1]);
        }
        if (i) {
          stage(1); stage(2); stage(3);
          mbar_arrive_warp(bar(B_SIG));
          receive(); score0(); softmax(0);
        }
        pv0();
        if (i == 0) { bar_arrive(NB_PY, 256); stage(1); stage(2); stage(3); stage(0); }
        else { stage(0); copy_out<2>(SM_STG + w * 4096, sc->o, ((m * 128 + w * 32) * D_ + (8 + c) * 64) * 2, D_ * 2, lane); }
        mbar_arrive_warp(bar(B_SIG + 1));
        if (i) bar_arrive(NB_OGO, 256);
        TL(t, 6);
      } else if (i > 2 && i < 10) {
        float acc[2][64];
        float2 cs[16];
        float hr[4];
        uint32_t so, sta;
        mainloop<1>(acc, sig, t, wg, sp, [&]() {
          const int lane = lane_now();
          so = SM_STG + (w * 16 + (lane & 7)) * 128 + (((lane >> 3) ^ (lane & 7)) << 4);
          sta = stat(l * 2 + 1) + (w * 16 + (lane >> 2)) * 8;
          mbar_wait(bar(B_STAT + 1) + l * 16, 0);
          mbar_wait(bar(B_CS - 1) + 8 * i, 0);
#pragma unroll
          for (int j = 0; j < 16; j += 2) lds16f(SM_CS + i * 512 + (lane & 3) * 16 + j * 32, cs[j].x, cs[j].y, cs[j + 1].x, cs[j + 1].y);
#pragma unroll
          for (int j = 0; j < 4; j++) hr[j] = 0.5f * lds4f(sta + (j >> 1) * 512 + (j & 1) * 64);
          mbar_wait(bar(B_FREE), l * 9 + i - 2);
        }, []() {});
        TL(t, 3);
        float mn[8];
#pragma unroll
        for (int x = 0; x < 2; x++) mn[x] = __uint_as_float(lds4(sta + 4 + (x >> 2) * 512 + ((x >> 1) & 1) * 64));
#pragma unroll
        for (int x = 0; x < 8; x++) {
          const int mi = x >> 2, half = (x >> 1) & 1, g = x & 1;
          uint32_t v[4];
#pragma unroll
          for (int j = 0; j < 4; j++) {
            const int jg = g * 4 + j + SWAP * 8, ju = jg ^ 8;
            const float2 cg = cs[jg], cu = cs[ju];
            const float g0 = fmaf(mn[x], cg.x, acc[mi][jg * 4 + half * 2]), g1 = fmaf(mn[x], cg.y, acc[mi][jg * 4 + half * 2 + 1]);
            const float u0 = fmaf(mn[x], cu.x, acc[mi][ju * 4 + half * 2]), u1 = fmaf(mn[x], cu.y, acc[mi][ju * 4 + half * 2 + 1]);
            const float a0 = g0 * hr[x >> 1], a1 = g1 * hr[x >> 1];
            v[j] = pack_bf16(fmaf(a0, tanhf_(a0), a0) * u0, fmaf(a1, tanhf_(a1), a1) * u1);
          }
          stsm4((so ^ (g * 64)) + (mi * 64 + half * 8) * 128, v[0], v[1], v[2], v[3]);
          if ((x & 3) == 3) mbar_arrive_warp(bar(B_SIG + mi));
          if (x + 2 < 8) mn[x + 2] = __uint_as_float(lds4(sta + 4 + ((x + 2) >> 2) * 512 + (((x + 2) >> 1) & 1) * 64));
        }
        TL(t, 6);
      } else {
        float acc[2][64], rsc[4];
        {
          const int lane = lane_now();
          const uint32_t e = c_sched.task[t].res;
          const uint32_t ra = SB + (w * 16 + (lane & 7)) * 128 + (((lane >> 3) ^ (lane & 7)) << 4);
          float sd[4];
#pragma unroll
          for (int j = 0; j < 4; j++) {
            rsc[j] = i == 10 ? lds4f(stat(l * 2 + 1) + ((j >> 1) * 64 + w * 16 + (j & 1) * 8 + (lane >> 2)) * 8) : 1.f;
            sd[j] = rcpf(rsc[j]);
          }
          const uint32_t zero = lds4(SM_ZERO);
          mbar_wait(bar(B_RES), i == 10);
          uint32_t dep[16];
#pragma unroll
          for (int x = 0; x < 16; x++) {
            const int mi = x >> 3, half = (x >> 2) & 1, g = x & 3;
            uint32_t v[4];
            ldsm4(((e >> ((g >> 1) * 8)) & 31) * 8192 + ((ra ^ ((g & 1) * 64)) | (x ? dep[x - 1] : 0)) + (mi * 64 + half * 8) * 128, v[0], v[1], v[2], v[3]);
#pragma unroll
            for (int j = 0; j < 4; j++) {
              asm volatile("shl.b32 %0, %1, 16;" : "=f"(acc[mi][(g * 4 + j) * 4 + half * 2]) : "r"(v[j]));
              asm volatile("and.b32 %0, %1, 0xffff0000;" : "=f"(acc[mi][(g * 4 + j) * 4 + half * 2 + 1]) : "r"(v[j]));
              { acc[mi][(g * 4 + j) * 4 + half * 2] *= sd[mi * 2 + half]; acc[mi][(g * 4 + j) * 4 + half * 2 + 1] *= sd[mi * 2 + half]; }
            }
            asm("and.b32 %0, %1, %2;" : "=r"(dep[x]) : "f"(acc[mi][(g * 4 + 3) * 4 + half * 2 + 1]), "r"(zero));
          }
          mbar_arrive_warp(bar(B_RF));
        }
        auto stage = [&](int mi, int hi) {
          const int lane = lane_now();
          const uint32_t sw = SB + ((c_sched.task[t].stg >> (8 * hi)) & 31) * 8192 + (mi * 64 + w * 16) * 128, so = sw + (lane & 7) * 128 + (((lane >> 3) ^ (lane & 7)) << 4);
#pragma unroll
          for (int half = 0; half < 2; half++)
#pragma unroll
            for (int g = 0; g < 2; g++) {
              uint32_t v[4];
#pragma unroll
              for (int j = 0; j < 4; j++) {
                { acc[mi][(hi * 8 + g * 4 + j) * 4 + half * 2] *= rsc[mi * 2 + half]; acc[mi][(hi * 8 + g * 4 + j) * 4 + half * 2 + 1] *= rsc[mi * 2 + half]; }
                v[j] = pack_bf16(acc[mi][(hi * 8 + g * 4 + j) * 4 + half * 2], acc[mi][(hi * 8 + g * 4 + j) * 4 + half * 2 + 1]);
              }
              stsm4((so ^ (g * 64)) + half * 1024, v[0], v[1], v[2], v[3]);
            }
          if (mi && !hi) mbar_arrive_warp(bar(B_SIG));
          if (hi == 0 || t == 21) {
            const int r = mi * 64 + w * 16;
            copy_out<4>(sw, t == 21 ? out : sc->y, ((t == 21 ? (row0 + r) * 2 + par : m * 128 + r) * D_ + (hi * 8 + c) * 64) * 2, t == 21 ? D_ * 4 : D_ * 2, lane);
          }
        };
        mainloop<2>(acc, sig, t, wg, sp, []() {}, [&]() { stage(0, 0); stage(0, 1); });
        TL(t, 3);
        stage(1, 0); mbar_arrive_warp(bar(B_SIG + 1));
        TL(t, 6);
        stage(1, 1); mbar_arrive_warp(bar(B_SIG + 2));
        if (t < 21) {
          const int lane = lane_now(), q = lane & 3;
          float s[4], s2[4];
#pragma unroll
          for (int x = 0; x < 4; x++) {
            float a0 = 0.f, a1 = 0.f, b0 = 0.f, b1 = 0.f;
#pragma unroll
            for (int j = 0; j < 16; j++) {
              const float d0 = acc[x >> 1][j * 4 + (x & 1) * 2], d1 = acc[x >> 1][j * 4 + (x & 1) * 2 + 1];
              a0 += d0; a1 += d1; b0 = fmaf(d0, d0, b0); b1 = fmaf(d1, d1, b1);
            }
            s[x] = a0 + a1; s2[x] = b0 + b1;
          }
#pragma unroll
          for (int x = 0; x < 2; x++) {
            s[x] = (q & 2 ? s[x + 2] : s[x]) + __shfl_xor_sync(0xffffffffu, q & 2 ? s[x] : s[x + 2], 2);
            s2[x] = (q & 2 ? s2[x + 2] : s2[x]) + __shfl_xor_sync(0xffffffffu, q & 2 ? s2[x] : s2[x + 2], 2);
          }
          const float r = (q & 1 ? s[1] : s[0]) + __shfl_xor_sync(0xffffffffu, q & 1 ? s[0] : s[1], 1);
          const float r2 = (q & 1 ? s2[1] : s2[0]) + __shfl_xor_sync(0xffffffffu, q & 1 ? s2[0] : s2[1], 1);
          asm volatile("st.global.v2.f32 [%0], {%1, %2};" ::"l"(&sc->stat[i == 10 ? 1 : l * 2][m][c][(q >> 1) * 64 + w * 16 + (q & 1) * 8 + (lane >> 2)]), "f"(r), "f"(r2) : "memory");
          mbar_arrive_warp(bar(B_SIG + 3));
        }
      }
    }
  }
}

typedef CUresult (*PFN_encodeTiled)(CUtensorMap*, CUtensorMapDataType, cuuint32_t, void*, const cuuint64_t*, const cuuint64_t*, const cuuint32_t*,
                                    const cuuint32_t*, CUtensorMapInterleave, CUtensorMapSwizzle, CUtensorMapL2promotion, CUtensorMapFloatOOBfill);

void make_map(PFN_encodeTiled enc, CUtensorMap* mp, const void* ptr, int rank, const cuuint64_t* gd, const cuuint64_t* gs, const cuuint32_t* bd) {
  const cuuint32_t es[4] = {1, 1, 1, 1};
  enc(mp, CU_TENSOR_MAP_DATA_TYPE_BFLOAT16, rank, const_cast<void*>(ptr), gd, gs, bd, es, CU_TENSOR_MAP_INTERLEAVE_NONE, CU_TENSOR_MAP_SWIZZLE_128B,
      CU_TENSOR_MAP_L2_PROMOTION_L2_128B, CU_TENSOR_MAP_FLOAT_OOB_FILL_NONE);
}
void make_map_act(PFN_encodeTiled enc, CUtensorMap* mp, const void* ptr, uint64_t cols, bool natural, uint32_t rows) {
  const cuuint64_t gd[3] = {cols, S_ / 2, 2}, gs[2] = {natural ? 4 * cols : 2 * cols, natural ? 2 * cols : cols * S_};
  const cuuint32_t bd[3] = {64, rows, 1};
  make_map(enc, mp, ptr, 3, gd, gs, bd);
}
void make_map_w(PFN_encodeTiled enc, CUtensorMap* mp, const void* ptr, uint64_t rows, uint64_t cols, uint32_t np, uint64_t sp, uint64_t tiles, uint32_t nt) {
  const cuuint64_t gd[4] = {512, rows, np, tiles}, gs[3] = {cols * 2, sp, 1024};
  const cuuint32_t bd[4] = {64, 64, np, nt};
  make_map(enc, mp, ptr, 4, gd, gs, bd);
}

}

extern "C" void kernel_launch(void* const* d_in, const int* in_sizes, int n_in, void* d_out, int out_size) {
  (void)in_sizes; (void)n_in; (void)out_size;
  static PFN_encodeTiled enc = nullptr;
  static void *p_sc, *p_ops, *p_w;
  static int by_sm = 0;
  void (*const kernels[4])(Scratch*, const Ops*, const bf16*, bf16*, Params) = {fused_kernel<0, 0>, fused_kernel<1, 0>, fused_kernel<0, 1>, fused_kernel<1, 1>};
  if (!enc) {
    void* fn = nullptr; cudaDriverEntryPointQueryResult qr;
    cudaGetDriverEntryPoint("cuTensorMapEncodeTiled", &fn, cudaEnableDefault, &qr);
    enc = (PFN_encodeTiled)fn;
    cudaGetSymbolAddress(&p_sc, g_sc); cudaGetSymbolAddress(&p_ops, g_ops); cudaGetSymbolAddress(&p_w, g_w13);
    for (int i = 0; i < 4; i++) cudaFuncSetAttribute(kernels[i], cudaFuncAttributeMaxDynamicSharedMemorySize, SM_TOTAL);
    int dev = 0, sms = 0;
    cudaGetDevice(&dev);
    cudaDeviceGetAttribute(&sms, cudaDevAttrMultiProcessorCount, dev);
    by_sm = sms == NCTA + NHELP;
    for (int i = 1; i < 4 && by_sm; i++) {
      cudaLaunchConfig_t cfg = {};
      cudaLaunchAttribute at;
      at.id = cudaLaunchAttributeClusterDimension; at.val.clusterDim.x = 1 << i; at.val.clusterDim.y = at.val.clusterDim.z = 1;
      cfg.gridDim = dim3(NCTA); cfg.blockDim = dim3(384); cfg.dynamicSmemBytes = SM_TOTAL; cfg.attrs = &at; cfg.numAttrs = 1;
      int n = 0;
      if (cudaOccupancyMaxActiveClusters(&n, kernels[0], &cfg) != cudaSuccess) { (void)cudaGetLastError(); n = 0; }
      by_sm = n == (i == 1 ? 66 : i == 2 ? 30 : 15);
    }
  }
  Params P;
  Scratch* const sc = (Scratch*)p_sc;
  make_map_act(enc, &P.tm[M_X0], d_in[0], D_, true, 128);
  make_map_act(enc, &P.tm[M_O], sc->o, D_, false, 128);
  make_map_act(enc, &P.tm[M_Y], sc->y, D_, false, 128);
  make_map_act(enc, &P.tm[M_H], sc->h, F_, false, 128);
  make_map_act(enc, &P.tm[M_OL], sc->o, D_, false, PROWS);
  make_map_act(enc, &P.tm[M_YL], sc->y, D_, false, PROWS);
  make_map_act(enc, &P.tm[M_HL], sc->h, F_, false, PROWS);
  make_map_act(enc, &P.tm[M_O24], sc->o, D_, false, 24);
  make_map_w(enc, &P.tm[M_WQKV], d_in[1], D_, 3 * D_, 3, D_ * 2, 2, 1);
  make_map_w(enc, &P.tm[M_WO], d_in[2], D_, D_, 2, 1024, 1, 1);
  make_map_w(enc, &P.tm[M_W2], d_in[6], F_, D_, 2, 1024, 1, 1);
  const char *w1 = (const char*)d_in[4], *w3 = (const char*)d_in[5];
  if ((uint64_t)(w1 < w3 ? w3 - w1 : w1 - w3) >> 39) {
    cudaMemcpyAsync(p_w, w1, (size_t)D_ * F_ * 2, cudaMemcpyDeviceToDevice);
    cudaMemcpyAsync((bf16*)p_w + D_ * F_, w3, (size_t)D_ * F_ * 2, cudaMemcpyDeviceToDevice);
    w1 = (const char*)p_w; w3 = w1 + (size_t)D_ * F_ * 2;
  }
  const bool swap = w3 < w1;
  make_map_w(enc, &P.tm[M_W13], swap ? w3 : w1, D_, F_, 2, swap ? w1 - w3 : w3 - w1, 7, 1);
  make_map_w(enc, &P.tm[M_W13P], swap ? w3 : w1, D_, F_, 2, swap ? w1 - w3 : w3 - w1, 7, 2);
  kernels[by_sm * 2 + swap]<<<NCTA + NHELP, 384, SM_TOTAL>>>(sc, (const Ops*)p_ops, (const bf16*)d_in[0], (bf16*)d_out, P);
}
```

```cpp
#include <cuda_runtime.h>
#include <cuda_bf16.h>
#include <cuda.h>
#include <stdint.h>
#include <stddef.h>

typedef __nv_bfloat16 bf16;
#define GU_E 3
#define G_N1 7
#define Q_P1 4
#define Q_P2 6
#define Q_P0 1
#define RES_O 3
#define RES_D 3
#define HOLD_O 6
#define PROWS 16
#define GAP_O 150
#define GAP_Y 100
#define GAP_H 350
#define GAP_H6 1000
#define ST_T1 600
#define ST_D1 700
#define ST_ROWS 3500
#define WARM_T 4000
constexpr int TAILQ = 1, TAIL = 2;

namespace {

constexpr int S_ = 2048, D_ = 1024, F_ = 3584;
constexpr int PANEL = S_ / 2 * 128;
constexpr int NCTA = 128;
constexpr int NHELP = 4;

constexpr uint32_t SB = 1024;
constexpr int NU = 25;
constexpr uint32_t SM_STG  = SB + NU * 8192;
__host__ __device__ constexpr uint32_t xch(int i, int w) { return i ? SM_STG - 8192 + w * 2048 : SM_STG + w * 4096; }
constexpr uint32_t BARS    = SM_STG + 16384;
constexpr uint32_t SM_STAT = BARS + 896;
__host__ __device__ constexpr uint32_t stat(int set) { return SM_STAT + set * 1088 + 64; }
constexpr uint32_t SM_CS   = SM_STAT + 4352;
constexpr uint32_t SM_END  = SM_CS + 5120;
constexpr int SM_TOTAL = SM_END - SB;
static_assert(BARS % 1024 == 0 && SM_TOTAL <= 232448, "smem");
constexpr int B_FULL = 0, B_EMPTY = 16, B_SIG = 37, B_XCH = 41, B_RF = 42, B_STAT = 45, B_TURN = 49, B_RES = 51, B_FREE = 52, B_SF = 53, B_QT = 55, B_PASS = 56,
              B_CS = 57, B_DEP = 66, B_PUB = 82, B_N = 100;
__host__ __device__ constexpr uint32_t bar(int i) { return BARS + 8 * i; }
constexpr uint32_t SM_TAG = BARS + 8 * B_N, SM_ZERO = SM_TAG + 16;
constexpr int NB_PX = 1, NB_PY = 2, NB_OGO = 3, NB_END = 4;

constexpr int E_O0 = 0, E_O1 = 1, E_YA = 2, E_YB = 3, E_H4 = 4, E_XA = 7, E_XB = 8, E_N = 9;

constexpr int M_X0 = 0, M_O = 1, M_Y = 2, M_H = 3;
constexpr int M_WQKV = 4, M_WO = 5, M_W13 = 6, M_W13P = 7, M_W2 = 8;
constexpr int M_OL = 9, M_YL = 10, M_HL = 11, M_O24 = 12, M_N = 13;

constexpr int FIRST = 5;
constexpr int NOPA = 416, NOPB = 416, NSEG = 40;
constexpr uint32_t A_END = 1, A_TURN = 2, A_DRAIN = 4, A_WAIT = 8, A_SYNC = 16;
constexpr uint32_t A_MARK = 0;
struct Task { uint32_t stg, res, sig; };
struct Seg { uint32_t i8, end8, a, b; };
constexpr uint32_t LO_A = 0x10000 + SB / 16, LO_B = 0x2000000 + SB / 16;
struct Sched { Seg seg[2 * NSEG]; Task task[22]; };
struct Ops { uint2 a[NOPA + 64], b[NOPB + 64]; };
struct Gen {
  Sched s{}; Ops o{};
  int n[2] = {0, 0}, nseg[2] = {0, NSEG}, cur = -1, pos = 0, err = 0, res = 0, nres = 0;
  int mask[400] = {}, sa[400] = {}, sb[400][2] = {}, own[NU][2] = {}, tok[NU] = {}, known[2][2] = {{-1, -1}, {-1, -1}};
  constexpr void emit(int p, int wait, int par, int dst, int map, int kb8, int arr, int load, int y) {
    if (cur < FIRST) return;
    const uint2 e{(uint32_t)((p ? y >> 10 | (load ? map - M_WQKV : 0) << 3 | (y & 63) << 6 : (y & 63) | (y >> 10) << 6 | map << 7) | load << 12 | dst << 13 | (res ? B_RES : B_FULL + (cur & 15)) << 18 | wait << 24) | (uint32_t)(par & 1) << 31,
                  (uint32_t)(((y >> 6) & 15) | arr << 4 | (!p && arr && mask[cur] != 3 && !res) << 5 | ((cur + 2) & 15) << 9 | kb8 << 13)};
    if (p) o.b[n[1]++] = e; else o.a[n[0]++] = e;
  }
  constexpr bool done(int p, int x) const { return x < 0 || ((!(mask[x] & 1) || known[p][0] >= x) && (!(mask[x] & 2) || known[p][1] >= x)); }
  constexpr void op(int p, int dst, int nu, int map, int kb8, int arr, int y, int xw = -1, int xp = 0) {
    int w[8] = {}, wp[8] = {}, nw = 0;
    if (xw >= 0) { w[nw] = xw; wp[nw++] = xp; }
    for (int u = dst; u < dst + nu; u++) if (tok[u] && (u == dst || tok[u] != tok[u - 1])) { w[nw] = (tok[u] - 1) >> 1; wp[nw++] = tok[u] - 1; }
    for (int x = cur - 1; x >= 0; x--) {
      bool need = x <= cur - 12;
      for (int u = dst; u < dst + nu; u++) need = need || own[u][0] == x + 1 || own[u][1] == x + 1;
      if (!need || done(p, x)) continue;
      if (cur - x >= 16 || !done(p, x - 16)) err |= 1;
      w[nw] = B_EMPTY + ((x + 2) & 15); wp[nw++] = x >> 4;
      for (int g = 0; g < 2; g++) if (((mask[x] >> g) & 1) && known[p][g] < x) known[p][g] = x;
    }
    for (; nw > 1; nw--) emit(p, w[nw - 1], wp[nw - 1], 0, 0, 0, 0, 0, 0);
    emit(p, nw ? w[0] : B_PASS, nw ? wp[0] : 1, dst, map, kb8, arr, nu > 0, y);
    for (int u = dst; u < dst + nu; u++) { own[u][0] = cur + 1; own[u][1] = 0; tok[u] = 0; }
  }
  constexpr int step(int m) { mask[++cur] = m; return cur; }
  constexpr int slot() { int u = (pos + 1) & ~1; if (u >= 24) u = 0; pos = u + 2; return u; }
  constexpr int qslot() { int u = (pos + 4) / 5 * 5; if (u >= NU) u = 0; pos = u + 5; return u; }
  constexpr void stage(int u, int first, int t) {
    first -= TAIL;
    for (int x = u; x < u + 2; x++) { if (own[x][0] > first || own[x][1] > first || tok[x]) err |= 2; own[x][0] = cur + 1; own[x][1] = 0; tok[x] = t; }
  }
  static constexpr int kown(int hi) { return hi * 8 | 1 << 9; }
  static constexpr int kskip(int hi, int j) { return (hi * 8 + j) | (j + 1) << 6; }
  static constexpr int kpos(int p) { return p < 2 ? kown(p) : p < 9 ? kskip(0, p - 2) : kskip(1, p - 9); }
  constexpr void segs(int t, const int* st, const uint32_t* act, int cnt, int tail, int inc0) {
    const int g = t & 1, wrap = inc0 == 5 ? NU : 24;
    int j0 = 0;
    for (int j = 0; j < cnt; j++) {
      const int x = st[j], inc = inc0 ? inc0 : mask[st[j0]] == 3 ? 6 : 4;
      const bool next = j + 1 < cnt && st[j + 1] == x + 1 && mask[x + 1] == mask[x] && sa[x + 1] == (sa[x] + inc) % wrap && sb[x + 1][g] == (sb[x][g] + inc) % wrap;
      if (j >= cnt - tail - 1 && j + 1 < cnt && !next) err |= 4;
      if (j + 1 < cnt && st[j + 1] != x + 1 && !(act[j] & A_DRAIN)) err |= 8;
      if (j >= cnt - tail || (next && !act[j] && j != cnt - tail - 1)) continue;
      if (j == j0 && (j == 0 || (inc0 != 4 && (act[j - 1] & (A_DRAIN | A_SYNC))))) err |= 16;
      const int y = st[j0];
      s.seg[nseg[g]++] = Seg{(uint32_t)y * 8 | (act[j] | (j == cnt - tail - 1 ? A_END : 0)) << 16, (uint32_t)(x + 1) * 8 | inc * 512 << 16, LO_A + sa[y] * 512, LO_B + sb[y][g] * 512};
      j0 = j + 1;
    }
  }
  constexpr void residual(int t, int map, bool q) {
    const int u0 = q ? qslot() : slot(), u1 = q ? u0 + 2 : slot();
    res = 1;
    op(0, u0, 2, map, 4, 1, kown(0)); op(0, u1, 2, map, 0, 0, kown(1));
    res = 0;
    for (int x = 0; x < 4; x++) { const int u = (x < 2 ? u0 : u1) + (x & 1); own[u][0] = 0; tok[u] = 1 + B_RF * 2 + (nres & 1); }
    nres++;
    s.task[t].res = u0 | u1 << 8;
  }
  constexpr Gen() {
    int cs[4] = {};
    for (int t = 0; t < 22; t++) {
      const int i = t % 11, use = i == 0 ? 2 : (i == 2 || i == 10) ? 15 : 3;
      for (int x = 0; x < 4; x++) if ((use >> x) & 1) s.task[t].sig |= (cs[x]++ & 1) << x;
    }
    for (int l = 0; l < 2; l++) {
      const int T = l * 11, dep = B_DEP + l * E_N;
      int st[7][56] = {};
      uint32_t act[7][56] = {};
      if (l == 1) {
        const int first = cur + 1;
        for (int j = 0; j < 4; j++) {
          const int x = st[j >> 1][j & 1] = step(1 << ((T + (j >> 1)) & 1)), u = qslot();
          sb[x][0] = sb[x][1] = u + 2;
          if (j < 2) {
            sa[x] = (u + 5) % NU; stage(sa[x], first, j ? 1 + B_SF * 2 + 1 : 0); s.task[10].stg |= sa[x] << (8 * j);
            op(0, 0, 0, 0, 0, 1, 1 << 10, B_SIG + 2 * j, s.task[10].sig >> (2 * j));
          }
          else { sa[x] = sa[x - 2]; own[sa[x]][1] = own[sa[x] + 1][1] = x + 1; op(0, 0, 0, 0, 0, 1, 0); }
          op(1, u + 2, 3, M_WQKV, 3, 1, kown(j & 1) | (j >> 1) << 10);
        }
        act[0][1] = A_DRAIN; act[1][1] = A_DRAIN | A_WAIT;
      }
      for (int i = 0; i < 2; i++) {
        for (int j = 2 * l; j < 16; j++) {
          if (i && j == 16 - RES_O) residual(T + 2, l ? M_Y : M_X0, true);
          const int x = st[i][j] = step(1 << ((T + i) & 1)), u = qslot(), k = l ? kpos(j) : j;
          sa[x] = u; sb[x][0] = sb[x][1] = u + 2;
          op(0, u, 2, l ? M_Y : M_X0, 2, 1, k, l && i == 0 && (j == 2 || j == 9) ? B_DEP + (j == 2 ? E_XA : E_XB) : -1);
          op(1, u + 2, 3, M_WQKV, 3, 1, k | i << 10);
        }
        if (i) act[1][Q_P1 - 1 + (l ? 2 : Q_P0)] = act[1][Q_P2 - 1 + (l ? 2 : Q_P0)] = A_SYNC;
        if (i && own[NU - 1][0] > cur - TAILQ) err |= 256;
        segs(T + i, st[i], act[i], 16, TAILQ, 5);
      }
      for (int j = 0; j < 16; j++) {
        const int x = st[0][j] = step(1 << (T & 1)), k = j < 8 ? j : j == 8 ? kown(1) : kskip(1, j - 9), hold = j == HOLD_O ? B_PUB + l * E_N + E_O1 : -1;
        act[0][j] = j == 8 ? A_MARK : 0;
        if (j != 8) { sa[x] = slot(); op(0, sa[x], 2, M_O, 2, 1, k, j == 0 ? dep + E_O0 : j == 9 ? dep + E_O1 : hold); }
        else { sa[x] = NU; op(0, 0, 0, 0, 0, 1, 1 << 10, B_SIG + 1, s.task[T + 1].sig >> 1); }
        sb[x][0] = sb[x][1] = slot();
        op(1, sb[x][0], 2, M_WO, 2, 1, k, hold);
      }
      segs(T + 2, st[0], act[0], 16, TAIL, 4);
      int beg[8] = {0, 16}, end[7] = {16, 32 - G_N1}, cnt[7] = {};
      for (int j = 2; j < 7; j++) { beg[j] = end[j - 2] + GU_E; end[j] = beg[j] + 16; }
      beg[7] = end[6];
      const int first = cur + 1;
      for (int j = 0; j < end[6]; j++) {
        int tl[2] = {-1, -1}, m = 0;
        for (int v = 0; v < 7; v++) if ((j >= beg[v] && j < end[v]) || (v == 1 && j < G_N1)) { const int g = (T + 3 + v) & 1; if (tl[g] >= 0) err |= 32; tl[g] = v; m |= 1 << g; }
        if (!m) err |= 32;
        if (j == end[6] - RES_D) residual(T + 10, M_Y, false);
        const int x = step(m), k = kpos(j < 16 ? j : (j + G_N1) & 15);
        const int v0 = m == 3 ? (tl[0] < tl[1] ? tl[0] : tl[1]) : tl[m >> 1];
        const int ps = (pos + 1) / 2 % 12;
        const bool last = m == 3 && (ps % 3 == 1 || (j >= 2 && j < G_N1 && (ps % 3 == 0 || (j == 2 && ps != 11))));
        if (!last) sa[x] = slot();
        const int u = slot();
        if (m == 3 && slot() != u + 2) err |= 32;
        if (last) sa[x] = slot();
        if (j < 2) { stage(sa[x], first, j ? 1 + B_SF * 2 : 0); s.task[T + 2].stg |= sa[x] << (8 * j); op(0, 0, 0, 0, 0, 1, 1 << 10, B_SIG + 2 * j, s.task[T + 2].sig >> (2 * j)); }
        else op(0, sa[x], 2, M_Y, 2, 1, k, j == 2 ? dep + E_YA : j == 9 ? dep + E_YB : -1);
        op(1, u, m == 3 ? 4 : 2, m == 3 ? M_W13P : M_W13, m == 3 ? 4 : 2, 1, k | v0 << 10, j == 3 ? B_PUB + l * E_N + E_YA : -1);
        for (int g = 0; g < 2; g++) {
          const int v = tl[g];
          if (v < 0) continue;
          sb[x][g] = u + (v - v0) * 2;
          act[v][cnt[v]] = j == beg[v + 1] - 1 ? A_TURN : v == 1 && j == G_N1 - 1 ? A_DRAIN | A_WAIT : v == 0 && j == 1 ? A_MARK : 0;
          st[v][cnt[v]++] = x;
        }
      }
      for (int v = 0; v < 7; v++) { if (cnt[v] != 16) err |= 64; segs(T + 3 + v, st[v], act[v], 16, 0, 0); }
      for (int j = 0; j < 56; j++) {
        const int x = st[0][j] = step(1 << (T & 1));
        act[0][j] = 0;
        sa[x] = slot(); op(0, sa[x], 2, M_H, 2, 1, j, j == 0 ? dep + E_H4 : j == 40 ? dep + E_H4 + 1 : j == 48 ? dep + E_H4 + 2 : -1);
        sb[x][0] = sb[x][1] = slot(); op(1, sb[x][0], 2, M_W2, 2, 1, j);
      }
      segs(T + 10, st[0], act[0], 56, TAIL, 4);
    }
    { const int u0 = slot(), u1 = slot(); stage(u0, cur + 1, 0); stage(u1, cur + 1, 0); s.task[21].stg = u0 | u1 << 8; }
    if (n[0] > NOPA || n[1] > NOPB || nseg[0] >= NSEG || nseg[1] >= 2 * NSEG) err |= 128;
    for (int x = n[0]; x < NOPA + 64; x++) o.a[x] = uint2{B_PASS << 24 | 1u << 31, 0};
    for (int x = n[1]; x < NOPB + 64; x++) o.b[x] = uint2{B_PASS << 24 | 1u << 31, 0};
  }
};
constexpr Gen GEN{};
static_assert(GEN.err == 0, "schedule");
constexpr int NOP0 = (GEN.n[0] + 31) / 32 * 32, NOP1 = (GEN.n[1] + 31) / 32 * 32;

struct __align__(64) Params {
  CUtensorMap tm[M_N];
};

}

__constant__ Sched c_sched = GEN.s;
__device__ const Ops g_ops = GEN.o;
struct __align__(1024) Scratch {
  float2 stat[3][16][8][128];
  uint4 stat0[16][128];
  uint4 halo[4][16][8][6][32];
  uint4 cs[9][8][64];
  uint32_t flags[NCTA][32];
  uint32_t cnt[4][32];
  uint32_t epoch[NCTA + NHELP];
  __align__(1024) bf16 o[S_ * D_];
  bf16 y[S_ * D_], h[S_ * F_];
};
__device__ Scratch g_sc;
__device__ __align__(1024) bf16 g_w13[2 * D_ * F_];

#define TL(t, i) do {} while (0)
#define TS(i8, wg) do {} while (0)
#define TLW(t, i) do {} while (0)
#define MB_LIMIT (1 << 16)
#define FL_LIMIT (1 << 21)

namespace {

__device__ __forceinline__ uint32_t smem_u32(const void* p) { return (uint32_t)__cvta_generic_to_shared(p); }
__device__ __forceinline__ void mbar_init(uint32_t br, uint32_t cnt) { asm volatile("mbarrier.init.shared::cta.b64 [%0], %1;" ::"r"(br), "r"(cnt)); }
__device__ __forceinline__ void mbar_expect_tx(uint32_t br, uint32_t bytes) { asm volatile("mbarrier.arrive.expect_tx.shared::cta.b64 _, [%0], %1;" ::"r"(br), "r"(bytes) : "memory"); }
__device__ __forceinline__ void mbar_arrive(uint32_t br) { asm volatile("mbarrier.arrive.shared::cta.b64 _, [%0];" ::"r"(br) : "memory"); }
__device__ __forceinline__ void mbar_arrive_if(uint32_t br, uint32_t p) {
  asm volatile("{\n.reg .pred q;\nsetp.ne.u32 q, %1, 0;\n@q mbarrier.arrive.shared::cta.b64 _, [%0];\n}\n" ::"r"(br), "r"(p) : "memory");
}
__device__ __forceinline__ void mbar_arrive_warp(uint32_t br) {
  asm volatile("{\n.reg .pred q;\nbar.warp.sync 0xffffffff;\nelect.sync _|q, 0xffffffff;\n@q mbarrier.arrive.shared::cta.b64 _, [%0];\n}\n" ::"r"(br) : "memory");
}
__device__ __forceinline__ bool mbar_try_wait(uint32_t br, uint32_t parity) {
  uint32_t ok;
  asm volatile("{\n.reg .pred p;\nmbarrier.try_wait.parity.shared::cta.b64 p, [%1], %2;\nselp.u32 %0, 1, 0, p;\n}\n" : "=r"(ok) : "r"(br), "r"(parity) : "memory");
  return ok;
}
__device__ __forceinline__ void mbar_wait(uint32_t br, uint32_t parity) {
#pragma unroll 1
  for (int it = 0; it < MB_LIMIT; ++it) { if (mbar_try_wait(br, parity)) return; }
  __trap();
}
__device__ __forceinline__ bool elect_one() { uint32_t p; asm volatile("{\n.reg .pred P;\nelect.sync _|P, 0xffffffff;\nselp.u32 %0, 1, 0, P;\n}\n" : "=r"(p)); return p; }
__device__ __forceinline__ void fence_proxy_async_smem() { asm volatile("fence.proxy.async.shared::cta;" ::: "memory"); }
__device__ __forceinline__ void tma4d(uint32_t dst, const CUtensorMap* m, int c0, int c1, int c2, int c3, uint32_t br) {
  asm volatile("cp.async.bulk.tensor.4d.shared::cluster.global.mbarrier::complete_tx::bytes [%0], [%1, {%3, %4, %5, %6}], [%2];" ::"r"(dst), "l"(m), "r"(br), "r"(c0), "r"(c1), "r"(c2), "r"(c3) : "memory");
}
__device__ __forceinline__ void tma4d_store(const CUtensorMap* m, uint32_t src, int c1, int c2, int c3) {
  asm volatile("{\n.reg .pred p;\nelect.sync _|p, 0xffffffff;\n@p cp.async.bulk.tensor.4d.global.shared::cta.bulk_group [%0, {%5, %2, %3, %4}], [%1];\n}\n" ::"l"(m), "r"(src), "r"(c1), "r"(c2), "r"(c3), "r"(0) : "memory");
}
__device__ __forceinline__ void stsm4(uint32_t a, uint32_t x, uint32_t y, uint32_t z, uint32_t w) {
  asm volatile("stmatrix.sync.aligned.m8n8.x4.shared.b16 [%0], {%1,%2,%3,%4};" ::"r"(a), "r"(x), "r"(y), "r"(z), "r"(w) : "memory");
}
__device__ __forceinline__ void ldsm4(uint32_t a, uint32_t& x, uint32_t& y, uint32_t& z, uint32_t& w) {
  asm volatile("ldmatrix.sync.aligned.m8n8.x4.shared.b16 {%0,%1,%2,%3}, [%4];" : "=r"(x), "=r"(y), "=r"(z), "=r"(w) : "r"(a) : "memory");
}
__device__ __forceinline__ void st_tag(uint4* p, uint32_t a, uint32_t b, uint32_t c, uint32_t tag) {
  asm volatile("{\n.reg .b64 x, y;\n.reg .b128 z;\nmov.b64 x, {%1, %2};\nmov.b64 y, {%3, %4};\nmov.b128 z, {x, y};\nst.relaxed.gpu.global.b128 [%0], z;\n}\n" ::"l"(p), "r"(a), "r"(b), "r"(c), "r"(tag) : "memory");
}
__device__ __forceinline__ uint4 ld_tag(const uint4* p) {
  uint4 v;
  asm volatile("{\n.reg .b64 x, y;\n.reg .b128 z;\nld.relaxed.gpu.global.b128 z, [%4];\nmov.b128 {x, y}, z;\nmov.b64 {%0, %1}, x;\nmov.b64 {%2, %3}, y;\n}\n" : "=r"(v.x), "=r"(v.y), "=r"(v.z), "=r"(v.w) : "l"(p) : "memory");
  return v;
}
template <int NAP, int N> __device__ __forceinline__ void ld_tag_wait(uint4 (&v)[N], const uint4* p, uint32_t tag) {
#pragma unroll 1
  for (int it = 0; it < FL_LIMIT; ++it) {
    uint32_t bad = 0;
#pragma unroll
    for (int j = 0; j < N; j++) v[j] = ld_tag(p + j * 32);
#pragma unroll
    for (int j = 0; j < N; j++) bad |= v[j].w ^ tag;
    if (__all_sync(0xffffffffu, bad == 0)) return;
    if (NAP) __nanosleep(NAP);
  }
  __trap();
}
__device__ __forceinline__ void prefetch_tmap(const CUtensorMap* m) { asm volatile("prefetch.tensormap [%0];" ::"l"(m) : "memory"); }
__device__ __forceinline__ void wgmma_fence() { asm volatile("wgmma.fence.sync.aligned;" ::: "memory"); }
__device__ __forceinline__ void wgmma_commit() { asm volatile("wgmma.commit_group.sync.aligned;" ::: "memory"); }
template <int N> __device__ __forceinline__ void wgmma_wait() { asm volatile("wgmma.wait_group.sync.aligned %0;" ::"n"(N) : "memory"); }
template <int R> __device__ __forceinline__ void reg_alloc() { asm volatile("setmaxnreg.inc.sync.aligned.u32 %0;" ::"n"(R)); }
template <int R> __device__ __forceinline__ void reg_dealloc() { asm volatile("setmaxnreg.dec.sync.aligned.u32 %0;" ::"n"(R)); }
__device__ __forceinline__ void bar_sync(int id, int n) { asm volatile("bar.sync %0, %1;" ::"r"(id), "r"(n) : "memory"); }
__device__ __forceinline__ void bar_arrive(int id, int n) { asm volatile("bar.arrive %0, %1;" ::"r"(id), "r"(n) : "memory"); }
__device__ __forceinline__ uint32_t ld_acquire(const uint32_t* p) { uint32_t v; asm volatile("ld.acquire.gpu.global.u32 %0, [%1];" : "=r"(v) : "l"(p) : "memory"); return v; }
__device__ __forceinline__ void st_release(uint32_t* p, uint32_t v) { asm volatile("st.release.gpu.global.u32 [%0], %1;" ::"l"(p), "r"(v) : "memory"); }
__device__ __forceinline__ uint4 ldcg16(const void* p) { uint4 v; asm volatile("ld.global.cg.v4.u32 {%0,%1,%2,%3}, [%4];" : "=r"(v.x), "=r"(v.y), "=r"(v.z), "=r"(v.w) : "l"(p) : "memory"); return v; }
__device__ __forceinline__ float2 lds8f(uint32_t a) { float2 v; asm volatile("ld.shared.v2.f32 {%0,%1}, [%2];" : "=f"(v.x), "=f"(v.y) : "r"(a)); return v; }
__device__ __forceinline__ float lds4f(uint32_t a) { float v; asm volatile("ld.shared.f32 %0, [%1];" : "=f"(v) : "r"(a)); return v; }
__device__ __forceinline__ uint32_t lds4(uint32_t a) { uint32_t v; asm volatile("ld.shared.u32 %0, [%1];" : "=r"(v) : "r"(a) : "memory"); return v; }
__device__ __forceinline__ void lds16f(uint32_t a, float& x, float& y, float& z, float& w) { asm volatile("ld.shared.v4.f32 {%0,%1,%2,%3}, [%4];" : "=f"(x), "=f"(y), "=f"(z), "=f"(w) : "r"(a) : "memory"); }
__device__ __forceinline__ void sts8f(uint32_t a, float x, float y) { asm volatile("st.shared.v2.f32 [%0], {%1,%2};" ::"r"(a), "f"(x), "f"(y) : "memory"); }
__device__ __forceinline__ void sts4f(uint32_t a, float x) { asm volatile("st.shared.f32 [%0], %1;" ::"r"(a), "f"(x) : "memory"); }
__device__ __forceinline__ void sts16(uint32_t a, uint32_t x, uint32_t y, uint32_t z, uint32_t w) { asm volatile("st.shared.v4.u32 [%0], {%1,%2,%3,%4};" ::"r"(a), "r"(x), "r"(y), "r"(z), "r"(w) : "memory"); }
__device__ __forceinline__ void lds16(uint32_t a, uint32_t& x, uint32_t& y, uint32_t& z, uint32_t& w) { asm volatile("ld.shared.v4.u32 {%0,%1,%2,%3}, [%4];" : "=r"(x), "=r"(y), "=r"(z), "=r"(w) : "r"(a) : "memory"); }
__device__ __forceinline__ uint32_t pack_bf16(float a, float b) { uint32_t r; asm("cvt.rn.bf16x2.f32 %0, %1, %2;" : "=r"(r) : "f"(b), "f"(a)); return r; }
__device__ __forceinline__ uint32_t pack_bf16_v(float a, float b) { uint32_t r; asm volatile("cvt.rn.bf16x2.f32 %0, %1, %2;" : "=r"(r) : "f"(b), "f"(a)); return r; }
__device__ __forceinline__ float bf_lo(uint32_t v) { return __uint_as_float(v << 16); }
__device__ __forceinline__ float bf_hi(uint32_t v) { return __uint_as_float(v & 0xffff0000u); }
constexpr float LOG2E = 1.4426950408889634f;
__device__ __forceinline__ float ex2f(float x) { float y; asm("ex2.approx.ftz.f32 %0, %1;" : "=f"(y) : "f"(x)); return y; }
__device__ __forceinline__ float tanhf_(float x) { float y; asm("tanh.approx.f32 %0, %1;" : "=f"(y) : "f"(x)); return y; }
__device__ __forceinline__ float rcpf(float x) { float y; asm("rcp.approx.ftz.f32 %0, %1;" : "=f"(y) : "f"(x)); return y; }
__device__ __forceinline__ float bf_round(float a) { return bf_lo(pack_bf16(a, 0.f)); }
__device__ __forceinline__ uint32_t movmat(uint32_t a) { uint32_t d; asm volatile("movmatrix.sync.aligned.m8n8.trans.b16 %0, %1;" : "=r"(d) : "r"(a)); return d; }
__device__ __forceinline__ void mma16816(float& d0, float& d1, float& d2, float& d3, uint32_t a0, uint32_t a1, uint32_t a2, uint32_t a3, uint32_t b0, uint32_t b1,
                                         float c0, float c1, float c2, float c3) {
  asm volatile("mma.sync.aligned.m16n8k16.row.col.f32.bf16.bf16.f32 {%0,%1,%2,%3}, {%4,%5,%6,%7}, {%8,%9}, {%10,%11,%12,%13};"
               : "=f"(d0), "=f"(d1), "=f"(d2), "=f"(d3) : "r"(a0), "r"(a1), "r"(a2), "r"(a3), "r"(b0), "r"(b1), "f"(c0), "f"(c1), "f"(c2), "f"(c3));
}
template <int N> __device__ __forceinline__ void copy_out(uint32_t a, void* base, uint32_t ofs, int pitch, int lane) {
  a += (lane >> 3) * 128 + (((lane ^ (lane >> 3)) & 7) << 4);
  char* const g = static_cast<char*>(base) + (ofs + (lane >> 3) * pitch + (lane & 7) * 16);
  uint32_t v[N][4];
  __syncwarp();
#pragma unroll
  for (int j = 0; j < N; j++) lds16((a ^ ((j & 1) * 64)) + j * 512, v[j][0], v[j][1], v[j][2], v[j][3]);
#pragma unroll
  for (int j = 0; j < N; j++) asm volatile("st.global.v4.u32 [%0], {%1, %2, %3, %4};" ::"l"(g + j * 4 * pitch), "r"(v[j][0]), "r"(v[j][1]), "r"(v[j][2]), "r"(v[j][3]) : "memory");
}
__device__ __forceinline__ int lane_now() { int v; asm volatile("mov.u32 %0, %%laneid;" : "=r"(v)); return v; }
__device__ __forceinline__ uint32_t uni(uint32_t x, int lane) { return __shfl_sync(0xffffffffu, x + lane, 0); }
__device__ __forceinline__ uint64_t dsc(uint32_t hi, uint32_t lo) { return ((uint64_t)hi << 32) | lo; }

#define R8(a, o) "+f"(a[o]), "+f"(a[o + 1]), "+f"(a[o + 2]), "+f"(a[o + 3]), "+f"(a[o + 4]), "+f"(a[o + 5]), "+f"(a[o + 6]), "+f"(a[o + 7])
#define R32(a, o) R8(a, o), R8(a, o + 8), R8(a, o + 16), R8(a, o + 24)
#define REG64 "%0, %1, %2, %3, %4, %5, %6, %7, %8, %9, %10, %11, %12, %13, %14, %15, %16, %17, %18, %19, %20, %21, %22, %23, %24, %25, %26, %27, %28, %29, %30, %31, " \
              "%32, %33, %34, %35, %36, %37, %38, %39, %40, %41, %42, %43, %44, %45, %46, %47, %48, %49, %50, %51, %52, %53, %54, %55, %56, %57, %58, %59, %60, %61, %62, %63"
#define REG96 REG64 ", %64, %65, %66, %67, %68, %69, %70, %71, %72, %73, %74, %75, %76, %77, %78, %79, %80, %81, %82, %83, %84, %85, %86, %87, %88, %89, %90, %91, %92, %93, %94, %95"
__device__ __forceinline__ void wgmma(float (&d)[64], uint64_t da, uint64_t db) {
  asm volatile("wgmma.mma_async.sync.aligned.m64n128k16.f32.bf16.bf16 {" REG64 "}, %64, %65, 1, 1, 1, 0, 1;\n"
               : R32(d, 0), R32(d, 32) : "l"(da), "l"(db));
}
__device__ __forceinline__ void wgmma(float (&d)[96], uint64_t da, uint64_t db) {
  asm volatile("wgmma.mma_async.sync.aligned.m64n192k16.f32.bf16.bf16 {" REG96 "}, %96, %97, 1, 1, 1, 0, 1;\n"
               : R32(d, 0), R32(d, 32), R32(d, 64) : "l"(da), "l"(db));
}
#define W8(a, o) "=f"(a[o]), "=f"(a[o + 1]), "=f"(a[o + 2]), "=f"(a[o + 3]), "=f"(a[o + 4]), "=f"(a[o + 5]), "=f"(a[o + 6]), "=f"(a[o + 7])
#define W32(a, o) W8(a, o), W8(a, o + 8), W8(a, o + 16), W8(a, o + 24)
__device__ __forceinline__ void wgmma_z(float (&d)[64], uint64_t da, uint64_t db) {
  asm volatile("wgmma.mma_async.sync.aligned.m64n128k16.f32.bf16.bf16 {" REG64 "}, %64, %65, 0, 1, 1, 0, 1;\n"
               : W32(d, 0), W32(d, 32) : "l"(da), "l"(db));
}
__device__ __forceinline__ void wgmma_z(float (&d)[96], uint64_t da, uint64_t db) {
  asm volatile("wgmma.mma_async.sync.aligned.m64n192k16.f32.bf16.bf16 {" REG96 "}, %96, %97, 0, 1, 1, 0, 1;\n"
               : W32(d, 0), W32(d, 32), W32(d, 64) : "l"(da), "l"(db));
}

__device__ __forceinline__ void wgmma_cs(float (&d)[4], uint64_t da, uint64_t db) {
  asm volatile("wgmma.mma_async.sync.aligned.m64n8k16.f32.bf16.bf16 {%0, %1, %2, %3}, %4, %5, 1, 1, 1, 1, 0;\n" : "+f"(d[0]), "+f"(d[1]), "+f"(d[2]), "+f"(d[3]) : "l"(da), "l"(db));
}
__device__ __forceinline__ void bulk_commit() { asm volatile("cp.async.bulk.commit_group;" ::: "memory"); }
__device__ __forceinline__ void bulk_wait() { asm volatile("cp.async.bulk.wait_group 0;" ::: "memory"); }
__device__ __forceinline__ void fence_bar_init() { asm volatile("fence.mbarrier_init.release.cluster;" ::: "memory"); }

__device__ __forceinline__ uint32_t clock_now() { uint32_t v; asm volatile("mov.u32 %0, %%clock;" : "=r"(v)); return v; }
__device__ __forceinline__ void delay_until(uint32_t t0, int cycles) {
#pragma unroll 1
  for (int it = 0; it < 1000 && (int)(clock_now() - t0) < cycles; it++) __nanosleep(40);
}
__device__ __forceinline__ uint32_t ld_epoch(const uint32_t* p) { uint32_t v; asm volatile("ld.global.u32 %0, [%1];" : "=r"(v) : "l"(p) : "memory"); return v + 1; }
__device__ __forceinline__ void wait_flags(const uint32_t* f, uint32_t tag) {
#pragma unroll 1
  for (int it = 0; it < FL_LIMIT; ++it) if (__all_sync(0xffffffffu, (int)(ld_acquire(f) - tag) >= 0)) return;
  __trap();
}

__device__ __forceinline__ float2 ln_finish(float sum, float sq) {
  const float mean = sum * (1.f / D_), var = fmaxf(fmaf(-mean, mean, sq * (1.f / D_)), 0.f);
  const float mb = bf_round(mean);
  const float vb = bf_round(var);
  const float sd = bf_round(sqrtf(bf_round(vb + 1e-5f)));
  return make_float2(1.0f / sd, -mb);
}

__device__ __forceinline__ void helper_cta(const Params& P, Scratch* sc, int e, int wg, int w) {
  const int tid = threadIdx.x;
  if (tid == 256) {
#pragma unroll
    for (int i = 0; i < 16; i++) mbar_init(bar(i), 1);
    fence_bar_init();
  }
  if (tid < 64) sts16(SM_STG + tid * 16, 0x3f803f80u, 0x3f803f80u, 0x3f803f80u, 0x3f803f80u);
  fence_proxy_async_smem();
  __syncthreads();
  if (wg == 2) {
    if (w == 0) {
#pragma unroll 1
      for (int n = 0; n < 9 * 32; n++) {
        const int job = n >> 5;
        const uint32_t fb = bar(n & 7), dst = SB + (n & 7) * 24576;
        mbar_wait(bar(8 + (n & 7)), (n >> 3) + 1);
        if (elect_one()) {
          mbar_expect_tx(fb, job < 2 ? 24576 : 16384);
          tma4d(dst, &P.tm[job < 2 ? M_WQKV : M_W13], (e * 2 + (n & 1)) * 64, (n & 30) * 32, 0, job < 2 ? job : job - 2, fb);
        }
        __syncwarp();
      }
    }
  } else {
    const uint32_t tag = ld_epoch(sc->epoch + NCTA + e);
    const int lane = tid & 31;
#pragma unroll 1
    for (int job = 0; job < 9; job++) {
      float s[3][4] = {};
#pragma unroll 1
      for (int n = job * 32 + wg; n < job * 32 + 32; n += 2) {
        mbar_wait(bar(n & 7), n >> 3);
        wgmma_fence();
        const uint32_t a = ((SB + (n & 7) * 24576) >> 4) + 0x2000000;
#pragma unroll
        for (int k = 0; k < 8; k++) wgmma_cs(s[k & 1], dsc(0x40000040u, a + (k & 1) * 512 + (k >> 1) * 128), dsc(0x40000040u, (SM_STG >> 4) + 0x10000));
        if (job < 2) {
          wgmma_fence();
#pragma unroll
          for (int k = 0; k < 4; k++) wgmma_cs(s[2], dsc(0x40000040u, a + 1024 + k * 128), dsc(0x40000040u, (SM_STG >> 4) + 0x10000));
        }
        wgmma_commit();
        wgmma_wait<0>();
        mbar_arrive_if(bar(8 + (n & 7)), (tid & 127) == 0);
      }
      if (!(lane & 2))
        st_tag(&sc->cs[job][e * 2 + wg][w * 16 + (lane & 1) * 8 + (lane >> 2)], __float_as_uint(lane & 1 ? s[0][2] : s[0][0]), __float_as_uint(lane & 1 ? s[1][2] : s[1][0]),
               __float_as_uint(lane & 1 ? s[2][2] : s[2][0]), tag);
      __syncwarp();
    }
    bar_sync(NB_END, 256);
    if (tid == 0) sc->epoch[NCTA + e] = tag;
  }
}

template <bool WEIGHTS>
__device__ __forceinline__ void producer(const Params& P, const uint2* tab, int nop, int lane, int c, int row, int par, uint32_t t_entry) {
  uint64_t pol;
  asm volatile("createpolicy.fractional.L2::evict_first.b64 %0, 1.0;" : "=l"(pol));
  __syncthreads();
  uint2 nx = __ldg(tab + lane), n2 = __ldg(tab + 32 + lane);
#pragma unroll 1
  for (int j = 1; j < FIRST; j++) {
    delay_until(t_entry, ST_T1 + (j - 1) * ST_D1);
    if (elect_one()) {
      mbar_expect_tx(bar(B_FULL) + 8 * j, WEIGHTS ? 24576 : 16384);
      if (WEIGHTS) tma4d(SB + j * 40960 + 16384, &P.tm[M_WQKV], c * 64, j * 64, 0, 0, bar(B_FULL) + 8 * j);
      else tma4d(SB + j * 40960, &P.tm[M_X0], 0, row, j, par, bar(B_FULL) + 8 * j);
    }
    __syncwarp();
  }
  if (!WEIGHTS && lane == 0) {
#pragma unroll
    for (int j = 0; j < FIRST; j++) mbar_arrive(bar(B_EMPTY + 2 + j));
  }
  __syncwarp();
  auto word = [&](uint2 e) { return e.x + (((int)(e.y & 7) > c) + (e.y & 8 ? c : 0)) * (WEIGHTS ? 64 : 1); };
  uint32_t xn = __shfl_sync(0xffffffffu, word(nx), 0);
  const uint64_t maps = reinterpret_cast<uint64_t>(&P.tm[WEIGHTS ? M_WQKV : 0]);
  if ((uint32_t)maps > 0xfffff000u) __trap();
  const uint32_t sb = uni(SB, lane), bars = uni(BARS, lane), zero = uni(0, lane), mlo = uni((uint32_t)maps, lane), mhi = uni(maps >> 32, lane);
#pragma unroll 1
  for (int base = 0; base < nop; base += 32) {
    const uint2 e = nx;
    nx = n2;
    n2 = __ldg(tab + base + 64 + lane);
    const uint32_t xw = word(lane ? e : nx), bytes = e.y & 0xe000, eb = (e.y >> 6) & 0x78;
    const int arr = e.y & 16 ? lane + 1 : 0, solo = e.y & 32 ? lane + 1 : 0;
#pragma unroll 1
    for (int j = 1; j <= 32; j++) {
      const uint32_t x = xn;
      xn = __shfl_sync(0xffffffffu, xw, j);
#define OP_WAIT(X) "{\n.reg .pred pe, pa, pn, ps, pw;\n.reg .u32 it;\n" \
                "elect.sync _|pe, 0xffffffff;\nsetp.eq.u32 pa, %0, %1;\nsetp.ne.and.u32 pn, %2, 0, pe;\n" X \
                "mov.u32 it, 0;\n" \
                "WAIT_%=:\n" \
                "mbarrier.try_wait.parity.shared::cta.b64 pw, [%3 + %9], %4;\n" \
                "@pw bra.uni GO_%=;\n" \
                "add.u32 it, it, 1;\nsetp.lt.u32 pw, it, 0x10000;\n" \
                "@pw bra.uni WAIT_%=;\n" \
                "trap;\n" \
                "GO_%=:\n"
#define OP_ARGS "r"(arr), "r"(j), "r"(x & (1 << 12)), "r"((x >> 21) & 0x3f8), "r"(x >> 31), "r"(((x >> 15) & 0x1f8) | bars), "r"(bytes), "r"((x & 0x3e000) | sb), \
                "l"(dsc(mhi, mlo + (WEIGHTS ? (x & 0x38) * 16 : x & 0x180))), "n"(BARS), "r"(x & (WEIGHTS ? 0xfc0 : 63)), "r"(x & (WEIGHTS ? 7 : 64))
      if (WEIGHTS)
        asm volatile(OP_WAIT("")
                     "@pn cp.async.bulk.tensor.4d.shared::cluster.global.mbarrier::complete_tx::bytes.L2::cache_hint [%7], [%8, {%12, %10, %13, %11}], [%5], %14;\n"
                     "@pa mbarrier.arrive.expect_tx.shared::cta.b64 _, [%5], %6;\n"
                     "}\n" ::OP_ARGS, "r"(c * 64), "r"(zero), "l"(pol) : "memory");
      else
        asm volatile(OP_WAIT(".reg .pred pf;\nsetp.ne.u32 pf, %11, 0;\nsetp.eq.u32 ps, %14, %1;\n")
                     "@pn cp.async.bulk.tensor.4d.shared::cluster.global.mbarrier::complete_tx::bytes [%7], [%8, {%17, %12, %10, %13}], [%5];\n"
                     "@pf fence.proxy.async.shared::cta;\n"
                     "@pa mbarrier.arrive.expect_tx.shared::cta.b64 _, [%5], %6;\n"
                     "@ps mbarrier.arrive.shared::cta.b64 _, [%15 + %16];\n"
                     "}\n" ::OP_ARGS, "r"(row), "r"(par), "r"(solo), "r"(eb), "n"(bar(B_EMPTY)), "r"(zero) : "memory");
    }
  }
}

template <int N, uint32_t LO> __device__ __forceinline__ void advance(uint32_t& x, uint32_t inc) {
  constexpr uint32_t LEN = (N == 192 ? NU : 24) * 512;
  x += inc; if (x >= LO + LEN) x -= LEN;
}
__device__ __forceinline__ bool full_test(uint32_t i8) {
  uint32_t ok;
  asm volatile("{\n.reg .pred p;\nmbarrier.test_wait.parity.shared::cta.b64 p, [%1 + %3], %2;\nselp.u32 %0, 1, 0, p;\n}\n" : "=r"(ok) : "r"(i8 & 0x78), "r"(i8 >> 7), "n"(bar(B_FULL)) : "memory");
  return ok;
}
__device__ __forceinline__ void full_wait(uint32_t i8) { mbar_wait(bar(B_FULL) + (i8 & 0x78), i8 >> 7); }
__device__ __forceinline__ void release(uint32_t i8, uint32_t p) {
  asm volatile("{\n.reg .pred q;\nsetp.ne.u32 q, %1, 0;\n@q mbarrier.arrive.shared::cta.b64 _, [%0 + %2];\n}\n" ::"r"(i8 & 0x78), "r"(p), "n"(bar(B_EMPTY)) : "memory");
}
template <int N, int RELK, int FIRSTK>
__device__ __forceinline__ bool kstep(float (&acc)[2][N / 2], uint32_t hiA, uint32_t hiB, uint32_t& a, uint32_t& b, uint32_t inc, uint32_t& i8, uint32_t x) {
  constexpr uint32_t MI = N == 192 ? 64 : 512;
  wgmma_fence();
  if (FIRSTK == 2) { wgmma_z(acc[0], dsc(hiA, a), dsc(hiB, b)); wgmma_z(acc[1], dsc(hiA, a + MI), dsc(hiB, b)); }
  else { wgmma(acc[0], dsc(hiA, a), dsc(hiB, b)); wgmma(acc[1], dsc(hiA, a + MI), dsc(hiB, b)); }
  i8 += 8;
  const bool ok = full_test(i8);
#pragma unroll
  for (int k = 1; k < 4; k++) {
    wgmma(acc[0], dsc(hiA, a + 2 * k), dsc(hiB, b + 128 * k)); wgmma(acc[1], dsc(hiA, a + MI + 2 * k), dsc(hiB, b + 128 * k));
    if (k == RELK || k == 3) wgmma_commit();
    if (k == 3) { advance<N, LO_A>(a, inc); advance<N, LO_B>(b, inc); }
    if (!FIRSTK && k == RELK) {
      wgmma_wait<1>();
      release(i8, x);
    }
  }
  return ok;
}
template <int MODE, int N, class F, class G>
__device__ __forceinline__ void mainloop(float (&acc)[2][N], uint32_t sig, int t, int wg, uint32_t& sp, F&& prepare, G&& first_half) {
  const uint32_t turn = bar(B_TURN) + 8 * (wg ^ 1);
  constexpr uint32_t hiA = MODE == 0 ? 0x40000080u : 0x40000040u, hiB = 0x40000040u;
  constexpr Seg S0 = GEN.s.seg[0];
  uint32_t i8 = S0.i8 & 0xffff, nxt = S0.end8 & 0xffff, a = S0.a, b = S0.b, inc = S0.end8 >> 16;
  if (MODE != 0 || t != 0) {
    if (MODE == 2 || (MODE == 0 ? t != 12 : t != 4 && t != 15)) mbar_wait(bar(B_TURN) + 8 * wg, (t - 1) >> 1);
    i8 = c_sched.seg[sp].i8 & 0xffff; nxt = c_sched.seg[sp].end8 & 0xffff; a = c_sched.seg[sp].a; b = c_sched.seg[sp].b; inc = c_sched.seg[sp].end8 >> 16;
  }
  uint32_t hiA_ = hiA, hiB_ = hiB;
  if (MODE == 2) { hiA_ = uni(hiA, lane_now()); hiB_ = uni(hiB, lane_now() * 2); }
  full_wait(i8);
  TL(t, 2);
  TS(i8, wg);
  bool ok = kstep<N * 2, 3, MODE == 2 ? 1 : 2>(acc, hiA_, hiB_, a, b, inc, i8, 0);
  if (MODE == 2 && (t == 2 || t == 13)) bar_sync(NB_OGO, 256);
#pragma unroll 1
  while (true) {
    uint32_t act;
    if (MODE != 2) { hiA_ = uni(hiA, lane_now()); hiB_ = uni(hiB, lane_now() * 2); }
#pragma unroll 1
    while (true) {
      if (!ok) full_wait(i8);
      TS(i8, wg);
      ok = kstep<N * 2, MODE == 1 ? 1 : 3, 0>(acc, hiA_, hiB_, a, b, inc, i8, sig);
      if (__builtin_expect(i8 == nxt, 0)) {
        act = c_sched.seg[sp++].i8 >> 16;
        if (MODE == 1) mbar_arrive_if(turn, sig & (act >> 1));
        if (act & (MODE == 0 ? A_END | A_DRAIN | A_SYNC : MODE == 1 ? A_END | A_DRAIN : A_END)) break;
        nxt = c_sched.seg[sp].end8 & 0xffff; a = c_sched.seg[sp].a; b = c_sched.seg[sp].b;
        if (MODE == 1) inc = c_sched.seg[sp].end8 >> 16;
      }
    }
    if (MODE == 2 || (act & A_END)) break;
    nxt = c_sched.seg[sp].end8 & 0xffff; a = c_sched.seg[sp].a; b = c_sched.seg[sp].b;
    if (MODE == 1) inc = c_sched.seg[sp].end8 >> 16;
    if (MODE == 0 && (act & A_SYNC)) bar_arrive(NB_PX, 256);
    wgmma_wait<0>();
    release(i8 + 8, sig);
    i8 = c_sched.seg[sp].i8 & 0xffff;
    if (MODE == 1 || (act & A_WAIT)) mbar_wait(bar(B_TURN) + 8 * wg, (t - 1) >> 1);
    full_wait(i8);
    if (MODE == 0 && (act & A_SYNC)) bar_sync(NB_PY, 256);
    TS(i8, wg);
    ok = kstep<N * 2, 3, 1>(acc, hiA, hiB, a, b, inc, i8, 0);
  }
  if (MODE != 1) {
    constexpr int TL_ = MODE == 0 ? TAILQ : TAIL;
    uint32_t ta[TL_], tb[TL_];
#pragma unroll
    for (int x = 0; x < TL_; x++) {
      full_wait(i8 + 8 * x);
      TS(i8 + 8 * x, wg);
      ta[x] = a; tb[x] = b;
      advance<N * 2, LO_A>(a, inc); advance<N * 2, LO_B>(b, inc);
    }
#pragma unroll
    for (int h = 0; h < 2; h++) {
      const int mi = MODE == 0 ? 1 - h : h;
      wgmma_fence();
#pragma unroll
      for (int x = 0; x < TL_; x++)
#pragma unroll
        for (int k = 0; k < 4; k++) wgmma(acc[mi], dsc(hiA, ta[x] + mi * (MODE == 0 ? 64 : 512) + 2 * k), dsc(hiB, tb[x] + 128 * k));
      wgmma_commit();
      if (TL_ > 1 && h == 0) { wgmma_wait<1>(); release(i8 + 8, sig); prepare(); }
    }
    mbar_arrive_if(turn, sig);
    if (TL_ == 1) { wgmma_wait<2>(); release(i8 + 8, sig); prepare(); }
    wgmma_wait<1>();
    first_half();
    wgmma_wait<0>();
#pragma unroll
    for (int x = 0; x < TL_; x++) release(i8 + 16 + 8 * x, sig);
  } else {
    prepare();
    wgmma_wait<0>();
    release(i8 + 8, sig);
  }
}

template <int SWAP, int BY_SM>
__global__ void __launch_bounds__(384, 1) fused_kernel(Scratch* sc, const Ops* ops, const bf16* x0, bf16* out, const __grid_constant__ Params P) {
  extern __shared__ __align__(1024) uint8_t smem_raw[];
  const int tid = threadIdx.x;
  if (tid == 0) prefetch_tmap(&P.tm[M_X0]);
  if (tid == 128) prefetch_tmap(&P.tm[M_WQKV]);
  if (tid == 256) { mbar_init(bar(B_FULL), 2); fence_bar_init(); fence_proxy_async_smem(); }
  const int wg = __shfl_sync(0xffffffffu, tid >> 7, 0);
  const int w = __shfl_sync(0xffffffffu, (tid >> 5) & 3, 0);
  const int lane = tid & 31;
  const uint32_t t_entry = clock_now();
  int b = blockIdx.x;
  if (BY_SM) {
    uint32_t smid; asm volatile("mov.u32 %0, %%smid;" : "=r"(smid));
    const int tp = smid >> 1;
    const int q7 = (tp - 32) * 37 >> 8;
    const int v0 = (tp & 7) * 8 + (tp >> 3), v1 = tp * 8 - 244 - q7 * 55, v2 = tp < 62 ? tp + 4 : tp - 58;
    b = (tp < 32 ? v0 : tp < 60 ? v1 : v2) * 2 + (smid & 1);
  }
  const int mg = (b >> 5) & 3, m = mg * 4 + (b & 3);
  const int c = ((b >> 2) & 7) ^ (BY_SM ? 0 : (mg & 1) * 7);
  const int row0 = (m & 7) * 128, par = m >> 3;
  if (__builtin_expect(b >= NCTA, 0)) { helper_cta(P, sc, b - NCTA, wg, w); return; }
  if (wg == 2 && w == 0) {
    if (elect_one()) {
      tma4d(SB, &P.tm[M_X0], 0, row0, 0, par, bar(B_FULL));
      tma4d(SB + 16384, &P.tm[M_WQKV], c * 64, 0, 0, 0, bar(B_FULL));
      mbar_expect_tx(bar(B_FULL), 40960);
      mbar_arrive(bar(B_FULL));
    }
    __syncwarp();
    TLW(0, 1);
  } else {
    const int g = wg * 4 + w - (wg == 2);
    if (elect_one()) {
#pragma unroll
      for (int x = 1; x < 10; x++) mbar_init(bar(x) + g * 72, g < 4 ? 2 : g == 4 ? 4 : 1);
      fence_bar_init();
      fence_proxy_async_smem();
    }
    __syncwarp();
  }
  if (__builtin_expect(wg == 2, 0)) {
    reg_dealloc<40>();
    if (w < 2) {
      if (w == 0) producer<false>(P, ops->a, NOP0, lane, c, row0, par, t_entry);
      else producer<true>(P, ops->b, NOP1, lane, c, row0, par, t_entry);
    } else if (w == 2) {
      if (smem_u32(smem_raw) != SB) __trap();
      __syncthreads();
      const uint32_t tag = ld_epoch(sc->epoch + b);
      uint32_t* const flag = sc->flags[m * 8 + c];
      if (lane < 4) asm volatile("st.relaxed.gpu.global.v4.u32 [%0], {%1, %1, %1, %1};" ::"l"(flag + lane * 4), "r"(tag * 32 - 1) : "memory");
      __syncwarp();
      int ev = 0;
      uint32_t t_st = t_entry;
#pragma unroll 1
      for (int t = 0; t < 21; t++) {
        const int i = t >= 11 ? t - 11 : t;
        const bool od = i == 2 || i == 10;
        const uint32_t sig = c_sched.task[t].sig;
        const uint32_t pf = i == 0 ? 1 << M_OL | 1 << M_O | 1 << M_WO : i == 1 ? 1 << M_O24 | 1 << M_W13 | 1 << M_W13P | 1 << M_YL | 1 << M_Y : i == 3 ? 1 << M_HL :
                            i == 7 ? 1 << M_H | 1 << M_W2 : i == 10 ? 1 << M_WQKV | 1 << M_YL | 1 << M_Y : 0;
        if ((pf >> lane) & 1) prefetch_tmap(&P.tm[lane]);
        __syncwarp();
        if (od) {
          asm volatile("{\n.reg .pred pe, pw;\n.reg .u32 it;\nsetp.eq.u32 pe, %4, 1;\nmov.u32 it, 0;\n"
                       "WAIT_%=:\nmbarrier.try_wait.parity.shared::cta.b64 pw, [%0], %1;\n@pw bra.uni GO_%=;\n"
                       "add.u32 it, it, 1;\nsetp.lt.u32 pw, it, 0x10000;\n@pw bra.uni WAIT_%=;\ntrap;\n"
                       "GO_%=:\nfence.proxy.async.global;\nfence.acq_rel.gpu;\n"
                       "@pe red.relaxed.gpu.global.add.u32 [%2], %4;\n@pe mbarrier.arrive.shared::cta.b64 _, [%3];\n}\n"
                       ::"r"(bar(B_SIG + 1)), "r"(sig >> 1), "l"(&sc->cnt[mg][ev] + lane), "r"(bar(B_PUB) + 8 * ev), "r"(lane + 1) : "memory");
          ev++;
          TLW(t, 4);
        }
        if (i == 1) {
          mbar_wait(bar(B_SIG), sig);
          fence_proxy_async_smem();
#pragma unroll 1
          for (int r = 8; r < 128; r += 32) tma4d_store(&P.tm[M_O24], SM_STG + r * 128, row0 + r, 8 + c, par);
        } else {
          const CUtensorMap* mp = &P.tm[i == 0 ? M_OL : od ? M_YL : M_HL];
          const uint32_t src = od ? SB + ((c_sched.task[t].stg >> 8) & 31) * 8192 : SM_STG;
          const int blk = (od ? 1 : i ? i - 3 : 0) * 8 + c, gap = i == 0 ? GAP_O : od ? GAP_Y : i == 9 ? GAP_H6 : GAP_H;
          const int nr = i && !od ? 64 : 128;
#pragma unroll 1
          for (int r0 = 0; r0 < 128; r0 += nr) {
            const int s = od ? 3 : i ? r0 >> 6 : 1;
            mbar_wait(bar(B_SIG) + 8 * s, sig >> s);
            if (od) mbar_wait(bar(B_DEP - 1) + 8 * ev, 0);
            fence_proxy_async_smem();
            const uint32_t now = clock_now();
            if ((int)(now - t_st) > 0) t_st = now;
#pragma unroll 1
            for (int r = r0; r < r0 + nr; r += PROWS) {
              delay_until(t_st, 0);
              t_st += gap;
              tma4d_store(mp, src + r * 128, row0 + r, blk, par);
            }
          }
        }
        if (elect_one()) { bulk_commit(); bulk_wait(); }
        __syncwarp();
        if (i == 1) mbar_wait(bar(B_SIG + 1), sig >> 1);
        if (elect_one()) {
          mbar_arrive(od ? bar(B_SF) : bar(B_FREE));
          if (i < 3 || i > 6) {
            asm volatile("fence.proxy.async.global;" ::: "memory");
            st_release(flag, tag * 32 + ev);
            mbar_arrive(bar(B_PUB) + 8 * ev);
          }
        }
        __syncwarp();
        if (i < 3 || i > 6) ev++;
        if (!od) TLW(t, 4);
      }
      if (lane == 0) sc->epoch[b] = tag;
    } else {
      __syncthreads();
      const uint32_t tag = ld_epoch(sc->epoch + b);
      delay_until(t_entry, WARM_T);
      asm volatile("st.shared.u32 [%0], %1;" ::"r"(SM_TAG + 4), "r"(reinterpret_cast<const uint32_t*>(&c_sched)[min(lane * 16, (int)sizeof(Sched) / 4 - 1)]) : "memory");
      int ncs = 0;
#pragma unroll 1
      for (int it = 0; it < 20; it++) {
        const int l = it >= 11, i = it - l * 11, e = i < 2 ? 0 : i - 2, ev = l * E_N + e;
#pragma unroll 1
        for (; ncs < (it < 2 ? it + 1 : it < 6 ? 2 : 9); ncs++) {
          uint4 v[2];
          ld_tag_wait<200>(v, &sc->cs[ncs][c][lane], tag);
          const uint32_t a = SM_CS + (ncs < 2 ? ncs * 768 : 512 + ncs * 512) + ((lane & 17) | (lane & 6) << 1 | (lane & 8) >> 2) * 4;
#pragma unroll
          for (int j = 0; j < 2; j++) {
            sts4f(a + j * 128, __uint_as_float(v[j].x)); sts4f(a + j * 128 + 256, __uint_as_float(v[j].y));
            if (ncs < 2) sts4f(a + j * 128 + 512, __uint_as_float(v[j].z));
          }
          mbar_arrive_warp(bar(B_CS) + 8 * ncs);
        }
        if (i == 0 || i == 2) {
          const int u = l * 2 + (i >> 1);
          uint4 v[6] = {};
          mbar_wait(bar(B_QT), u);
          if (m & 7) ld_tag_wait<0>(v, &sc->halo[u][m - 1][c][0][lane], tag);
          const uint32_t xa = xch(i, 0) + lane * 16;
          sts16(xa, v[0].x, v[0].y, v[0].z, v[1].x); sts16(xa + 512, v[1].y, v[1].z, v[2].x, v[2].y);
          sts16(xa + 1024, v[2].z, v[3].x, v[3].y, v[3].z); sts16(xa + 1536, v[4].x, v[4].y, v[4].z, v[5].x);
          if (lane < 4) sts16(stat(l * 2) - 64 + lane * 16, v[5].y, 0, v[5].z, 0);
          mbar_arrive_warp(bar(B_XCH));
          continue;
        }
        const bool all = e == E_YA || e == E_XA;
        const uint32_t* fp = all ? &sc->cnt[mg][ev] : sc->flags[m * 8 + (lane & 7)];
        uint32_t want = tag * 32 + (all ? 0 : ev);
        asm volatile("" : "+l"(fp), "+r"(want));
        mbar_wait(bar(B_PUB) + 8 * ev, 0);
        wait_flags(fp, want);
        mbar_arrive_warp(bar(B_DEP) + 8 * ev);
        if (e == E_YB || e == E_XB) {
          const int p = e == E_XB ? 1 : l * 2;
          if (elect_one()) {
            mbar_expect_tx(bar(B_SF + 1), 8192);
            asm volatile("cp.async.bulk.shared::cluster.global.mbarrier::complete_tx::bytes [%0], [%1], 8192, [%2];" ::"r"(SM_STG), "l"(&sc->stat[p][m][0][0]), "r"(bar(B_SF + 1)) : "memory");
          }
          __syncwarp();
          mbar_wait(bar(B_SF + 1), p);
#pragma unroll 1
          for (int h = 0; h < 2; h++) {
            float s0 = 0.f, q0 = 0.f, s1 = 0.f, q1 = 0.f;
#pragma unroll 4
            for (int j = 0; j < 8; j++) {
              float x0, x1, x2, x3;
              lds16f(SM_STG + j * 1024 + h * 512 + lane * 16, x0, x1, x2, x3);
              s0 += x0; q0 += x1; s1 += x2; q1 += x3;
            }
            const float2 r0 = ln_finish(s0, q0), r1 = ln_finish(s1, q1);
            sts16(stat(p + 1) + (h * 64 + lane * 2) * 8, __float_as_uint(r0.x), __float_as_uint(r0.y), __float_as_uint(r1.x), __float_as_uint(r1.y));
          }
          mbar_arrive_warp(bar(B_STAT) + 8 * (p + 1));
        }
      }
    }
  } else {
    const int tw = tid & 127;
    reg_alloc<232>();
    uint32_t sig;
    asm volatile("mov.u32 %0, %1;" : "=r"(sig) : "r"((uint32_t)(tw == 0)));
    __syncthreads();

    if (wg == 1) {
      const uint32_t tag = ld_epoch(sc->epoch + b);
      uint4* const mine = &sc->stat0[m][c * 16 + w * 4 + (lane >> 3)];
      if ((lane & 7) == 0) st_tag(mine, 0, 0, 0, 0);
      __syncwarp();
      delay_until(t_entry, ST_ROWS);
      const bf16* xr = x0 + (size_t)((row0 + c * 16 + w * 4 + (lane >> 3)) * 2 + par) * D_ + (lane & 7) * 8;
      float sum = 0.f, sq = 0.f;
#pragma unroll 1
      for (int j0 = 0; j0 < 16; j0 += 4) {
        uint4 xv[4];
#pragma unroll
        for (int j = 0; j < 4; j++) xv[j] = ldcg16(xr + (j0 + j) * 64);
#pragma unroll
        for (int j = 0; j < 4; j++) {
          const uint32_t x[4] = {xv[j].x, xv[j].y, xv[j].z, xv[j].w};
#pragma unroll
          for (int e = 0; e < 8; e++) { const float d = e & 1 ? bf_hi(x[e >> 1]) : bf_lo(x[e >> 1]); sum += d; sq = fmaf(d, d, sq); }
        }
      }
#pragma unroll
      for (int o = 4; o > 0; o >>= 1) { sum += __shfl_xor_sync(0xffffffffu, sum, o); sq += __shfl_xor_sync(0xffffffffu, sq, o); }
      const float2 fin = ln_finish(sum, sq);
      if ((lane & 7) == 0) st_tag(mine, __float_as_uint(fin.x), __float_as_uint(fin.y), 0, tag);
      __syncwarp();
      TL(22, 5);
      uint4 v[1];
      ld_tag_wait<200>(v, &sc->stat0[m][tw], tag);
      sts8f(stat(0) + tw * 8, __uint_as_float(v[0].x), __uint_as_float(v[0].y));
      if (tw == 0) { asm volatile("st.shared.u32 [%0], %1;" ::"r"(SM_TAG), "r"(tag) : "memory"); sts16(SM_ZERO, 0, 0, 0, 0); }
      mbar_arrive_warp(bar(B_STAT));
      TL(22, 6);
    }

    uint32_t sp = wg * NSEG;
#pragma unroll 1
    for (int t = wg; t < 22; t += 2) {
      const int l = t >= 11, i = t - l * 11;
      if (t == 0) TL(t, 0);
      if (i < 2) {
        float acc[2][96];
        if (w == 3 && (m & 7) < 7) {
#pragma unroll
          for (int j = 0; j < 6; j++) st_tag(&sc->halo[l * 2 + i][m][c][j][lane_now()], 0, 0, 0, 0);
        }
        uint32_t Q[4][8], K[4][8], V[4][8], sta, csa;
        float2 st[4];
        auto fix = [&](int g, int j, float2 cs) {
          const int mi = g & 1, half = g >> 1;
          return pack_bf16_v(fmaf(st[g].y, cs.x, acc[mi][j * 4 + half * 2]), fmaf(st[g].y, cs.y, acc[mi][j * 4 + half * 2 + 1]));
        };
        mainloop<0>(acc, sig, t, wg, sp, [&]() {
          const int lane = lane_now();
          mbar_wait(bar(B_FREE), l * 9 + i - 1);
          mbar_wait(bar(B_STAT) + l * 16, 0);
          mbar_wait(bar(B_CS) + i * 8, 0);
          sta = stat(l * 2) + w * 256;
          csa = SM_CS + i * 768 + (lane & 3) * 16;
          st[1] = lds8f(sta + (8 + (lane >> 2)) * 8); st[3] = lds8f(sta + (24 + (lane >> 2)) * 8);
        }, [&]() {
          const int lane = lane_now();
          mbar_arrive_if(bar(B_QT), sig);
#pragma unroll
          for (int j = 0; j < 8; j += 2) {
            float2 c0, c1;
            lds16f(csa + (16 + j) * 32, c0.x, c0.y, c1.x, c1.y);
            V[3][j] = movmat(fix(3, 16 + j, c0)); V[3][j + 1] = movmat(fix(3, 17 + j, c1));
            lds16f(csa + (8 + j) * 32, c0.x, c0.y, c1.x, c1.y);
            K[3][j] = fix(3, 8 + j, c0); K[3][j + 1] = fix(3, 9 + j, c1);
          }
          if (w < 3) {
            const uint32_t xa = xch(i, w + 1) + lane * 16;
            sts16(xa, K[3][0], K[3][1], K[3][2], K[3][3]); sts16(xa + 512, K[3][4], K[3][5], K[3][6], K[3][7]);
            sts16(xa + 1024, V[3][0], V[3][1], V[3][2], V[3][3]); sts16(xa + 1536, V[3][4], V[3][5], V[3][6], V[3][7]);
            mbar_arrive_warp(bar(B_XCH));
          } else if ((m & 7) < 7) {
            const uint32_t tag = lds4(SM_TAG), r0 = lds4(sta + (24 + 2 * (lane & 3)) * 8), r1 = lds4(sta + (25 + 2 * (lane & 3)) * 8);
            uint4* const p = &sc->halo[l * 2 + i][m][c][0][lane];
            st_tag(p, K[3][0], K[3][1], K[3][2], tag); st_tag(p + 32, K[3][3], K[3][4], K[3][5], tag); st_tag(p + 64, K[3][6], K[3][7], V[3][0], tag);
            st_tag(p + 96, V[3][1], V[3][2], V[3][3], tag); st_tag(p + 128, V[3][4], V[3][5], V[3][6], tag); st_tag(p + 160, V[3][7], r0, r1, tag);
          }
        });
        TL(t, 3);
        const int lane = lane_now(), q = lane & 3, r8 = lane >> 2;
        st[0] = lds8f(sta + r8 * 8); st[2] = lds8f(sta + (16 + r8) * 8);
#pragma unroll
        for (int j0 = 22; j0 >= 0; j0 -= 2) {
          float2 cs[2];
          lds16f(csa + j0 * 32, cs[0].x, cs[0].y, cs[1].x, cs[1].y);
#pragma unroll
          for (int j = j0; j < j0 + 2; j++)
#pragma unroll
            for (int g = 0; g < (j < 8 ? 4 : 3); g++) {
              const uint32_t pk = fix(g, j, cs[j - j0]);
              if (j < 8) Q[g][j] = pk; else if (j < 16) K[g][j - 8] = pk; else V[g][j - 16] = movmat(pk);
            }
        }
        const bool up0 = (2 * q) > r8, up1 = (2 * q + 1) > r8;
        const uint32_t mskP = (up0 ? 0xffffu : 0u) | (up1 ? 0xffff0000u : 0u);
        TL(t, 5);
        uint32_t Kp[8] = {}, Vp[8] = {}, PS[2][4] = {}, PP[2][4] = {};
        float sS[2][4][2], sP[2][4][2] = {}, O[2][4][4][2], z0, z1, z2, z3;
        auto receive = [&]() {
          const uint32_t xa = xch(i, w) + lane * 16;
          mbar_wait(bar(B_XCH), i);
          lds16(xa, Kp[0], Kp[1], Kp[2], Kp[3]); lds16(xa + 512, Kp[4], Kp[5], Kp[6], Kp[7]);
          lds16(xa + 1024, Vp[0], Vp[1], Vp[2], Vp[3]); lds16(xa + 1536, Vp[4], Vp[5], Vp[6], Vp[7]);
          TL(i == 0 ? 22 : 23, t < 11 ? 3 : 4);
        };
        auto score0 = [&]() {
          float dm0, dm1;
#pragma unroll
          for (int h = 0; h < 2; h++) mma16816(sP[h][0][0], sP[h][0][1], dm0, dm1, Q[0][h * 4], Q[0][h * 4], Q[0][h * 4 + 1], Q[0][h * 4 + 1], Kp[h * 4], Kp[h * 4 + 1], z0, z1, z2, z3);
#pragma unroll
          for (int h = 0; h < 2; h++)
            mma16816(sP[h][0][0], sP[h][0][1], dm0, dm1, Q[0][h * 4 + 2], Q[0][h * 4 + 2], Q[0][h * 4 + 3], Q[0][h * 4 + 3], Kp[h * 4 + 2], Kp[h * 4 + 3], sP[h][0][0], sP[h][0][1], 0.f, 0.f);
        };
        auto softmax = [&](int g) {
          const float rk0 = lds4f(sta + (g * 8 + 2 * q - (up0 ? 8 : 0)) * 8), rk1 = lds4f(sta + (g * 8 + 2 * q + 1 - (up1 ? 8 : 0)) * 8);
          const float f = st[g].x * (0.17677669529663687f * LOG2E), f0 = f * rk0, f1 = f * rk1;
          const bool noprev = g == 0 && (m & 7) == 0 && w == 0;
#pragma unroll
          for (int h = 0; h < 2; h++) {
            float v0 = (up0 ? sP[h][g][0] : sS[h][g][0]) * f0, v1 = (up1 ? sP[h][g][1] : sS[h][g][1]) * f1;
            if (noprev && up0) v0 = -1e9f * LOG2E;
            if (noprev && up1) v1 = -1e9f * LOG2E;
            float mx = fmaxf(v0, v1);
            mx = fmaxf(mx, __shfl_xor_sync(0xffffffffu, mx, 1)); mx = fmaxf(mx, __shfl_xor_sync(0xffffffffu, mx, 2));
            const float e0 = ex2f(v0 - mx), e1 = ex2f(v1 - mx);
            float sum = e0 + e1;
            sum += __shfl_xor_sync(0xffffffffu, sum, 1); sum += __shfl_xor_sync(0xffffffffu, sum, 2);
            const float inv = rcpf(sum);
            const uint32_t pk = pack_bf16_v(e0 * inv * rk0, e1 * inv * rk1);
            PS[h][g] = pk & ~mskP; PP[h][g] = pk & mskP;
          }
        };
        const uint32_t sa = SM_STG + (w * 32 + (lane & 7)) * 128 + (((lane >> 3) ^ (lane & 7)) << 4);
        auto stage = [&](int g) {
#pragma unroll
          for (int h = 0; h < 2; h++)
            stsm4((sa ^ (h * 64)) + g * 1024, pack_bf16_v(O[h][g][0][0], O[h][g][0][1]), pack_bf16_v(O[h][g][1][0], O[h][g][1][1]),
                  pack_bf16_v(O[h][g][2][0], O[h][g][2][1]), pack_bf16_v(O[h][g][3][0], O[h][g][3][1]));
        };
        if (i == 0) { receive(); bar_sync(NB_PX, 256); }
        lds16f(SM_ZERO, z0, z1, z2, z3);
        if (i == 0) score0();
#pragma unroll
        for (int h = 0; h < 2; h++) {
          float dm0, dm1;
          const int j0 = h * 4;
#pragma unroll
          for (int g = 0; g < 3; g++) mma16816(sS[h][g][0], sS[h][g][1], sP[h][g + 1][0], sP[h][g + 1][1], Q[g][j0], Q[g + 1][j0], Q[g][j0 + 1], Q[g + 1][j0 + 1], K[g][j0], K[g][j0 + 1], z0, z1, z2, z3);
          mma16816(sS[h][3][0], sS[h][3][1], dm0, dm1, Q[3][j0], Q[3][j0], Q[3][j0 + 1], Q[3][j0 + 1], K[3][j0], K[3][j0 + 1], z0, z1, z2, z3);
        }
#pragma unroll
        for (int h = 0; h < 2; h++) {
          float dm0, dm1;
          const int j0 = h * 4 + 2;
#pragma unroll
          for (int g = 0; g < 3; g++) mma16816(sS[h][g][0], sS[h][g][1], sP[h][g + 1][0], sP[h][g + 1][1], Q[g][j0], Q[g + 1][j0], Q[g][j0 + 1], Q[g + 1][j0 + 1], K[g][j0], K[g][j0 + 1],
                                               sS[h][g][0], sS[h][g][1], sP[h][g + 1][0], sP[h][g + 1][1]);
          mma16816(sS[h][3][0], sS[h][3][1], dm0, dm1, Q[3][j0], Q[3][j0], Q[3][j0 + 1], Q[3][j0 + 1], K[3][j0], K[3][j0 + 1], sS[h][3][0], sS[h][3][1], 0.f, 0.f);
        }
        if (i == 0) { bar_arrive(NB_PY, 256); softmax(0); }
#pragma unroll
        for (int g = 1; g < 4; g++) softmax(g);
        TL(23, i == 0 ? (t < 11 ? 5 : 6) : 7);
        if (i == 0) bar_sync(NB_PX + ((PS[0][1] | PS[0][2] | PS[0][3] | PS[1][1] | PS[1][2] | PS[1][3]) & __float_as_uint(z0)), 256);
        lds16f(SM_ZERO, z0, z1, z2, z3);
        auto pv0 = [&]() {
#pragma unroll
          for (int x = 0; x < 8; x++) {
            float dm0, dm1;
            mma16816(O[x >> 2][0][x & 3][0], O[x >> 2][0][x & 3][1], dm0, dm1, PS[x >> 2][0], 0u, PP[x >> 2][0], 0u, V[0][x], Vp[x], z0, z1, z2, z3);
          }
        };
#pragma unroll
        for (int x = 0; x < 8; x++) {
          const int h = x >> 2, j = x & 3;
          mma16816(O[h][1][j][0], O[h][1][j][1], O[h][2][j][0], O[h][2][j][1], PS[h][1], PP[h][2], PP[h][1], 0u, V[1][x], V[0][x], z0, z1, z2, z3);
        }
#pragma unroll
        for (int x = 0; x < 8; x++) {
          const int h = x >> 2, j = x & 3;
          mma16816(O[h][3][j][0], O[h][3][j][1], O[h][2][j][0], O[h][2][j][1], PS[h][3], 0u, PP[h][3], PS[h][2], V[3][x], V[2][x], 0.f, 0.f, O[h][2][j][0], O[h][2][j][1]);
        }
        if (i) {
          stage(1); stage(2); stage(3);
          mbar_arrive_warp(bar(B_SIG));
          receive(); score0(); softmax(0);
        }
        pv0();
        if (i == 0) { bar_arrive(NB_PY, 256); stage(1); stage(2); stage(3); stage(0); }
        else { stage(0); copy_out<2>(SM_STG + w * 4096, sc->o, par * (S_ * D_) + (row0 + w * 32) * 128 + (8 + c) * PANEL, 128, lane); }
        mbar_arrive_warp(bar(B_SIG + 1));
        if (i) bar_arrive(NB_OGO, 256);
        TL(t, 6);
      } else if (i > 2 && i < 10) {
        float acc[2][64];
        float2 cs[16];
        float hr[4];
        uint32_t so, sta;
        mainloop<1>(acc, sig, t, wg, sp, [&]() {
          const int lane = lane_now();
          so = SM_STG + (w * 16 + (lane & 7)) * 128 + (((lane >> 3) ^ (lane & 7)) << 4);
          sta = stat(l * 2 + 1) + (w * 16 + (lane >> 2)) * 8;
          mbar_wait(bar(B_STAT + 1) + l * 16, 0);
          mbar_wait(bar(B_CS - 1) + 8 * i, 0);
#pragma unroll
          for (int j = 0; j < 16; j += 2) lds16f(SM_CS + i * 512 + (lane & 3) * 16 + j * 32, cs[j].x, cs[j].y, cs[j + 1].x, cs[j + 1].y);
#pragma unroll
          for (int j = 0; j < 4; j++) hr[j] = 0.5f * lds4f(sta + (j >> 1) * 512 + (j & 1) * 64);
          mbar_wait(bar(B_FREE), l * 9 + i - 2);
        }, []() {});
        TL(t, 3);
        float mn[8];
#pragma unroll
        for (int x = 0; x < 2; x++) mn[x] = __uint_as_float(lds4(sta + 4 + (x >> 2) * 512 + ((x >> 1) & 1) * 64));
#pragma unroll
        for (int x = 0; x < 8; x++) {
          const int mi = x >> 2, half = (x >> 1) & 1, g = x & 1;
          uint32_t v[4];
#pragma unroll
          for (int j = 0; j < 4; j++) {
            const int jg = g * 4 + j + SWAP * 8, ju = jg ^ 8;
            const float2 cg = cs[jg], cu = cs[ju];
            const float g0 = fmaf(mn[x], cg.x, acc[mi][jg * 4 + half * 2]), g1 = fmaf(mn[x], cg.y, acc[mi][jg * 4 + half * 2 + 1]);
            const float u0 = fmaf(mn[x], cu.x, acc[mi][ju * 4 + half * 2]), u1 = fmaf(mn[x], cu.y, acc[mi][ju * 4 + half * 2 + 1]);
            const float a0 = g0 * hr[x >> 1], a1 = g1 * hr[x >> 1];
            v[j] = pack_bf16(fmaf(a0, tanhf_(a0), a0) * u0, fmaf(a1, tanhf_(a1), a1) * u1);
          }
          stsm4((so ^ (g * 64)) + (mi * 64 + half * 8) * 128, v[0], v[1], v[2], v[3]);
          if ((x & 3) == 3) mbar_arrive_warp(bar(B_SIG + mi));
          if (x + 2 < 8) mn[x + 2] = __uint_as_float(lds4(sta + 4 + ((x + 2) >> 2) * 512 + (((x + 2) >> 1) & 1) * 64));
        }
        TL(t, 6);
      } else {
        float acc[2][64], rsc[4];
        {
          const int lane = lane_now();
          const uint32_t e = c_sched.task[t].res;
          const uint32_t ra = SB + (w * 16 + (lane & 7)) * 128 + (((lane >> 3) ^ (lane & 7)) << 4);
          float sd[4];
#pragma unroll
          for (int j = 0; j < 4; j++) {
            rsc[j] = i == 10 ? lds4f(stat(l * 2 + 1) + ((j >> 1) * 64 + w * 16 + (j & 1) * 8 + (lane >> 2)) * 8) : 1.f;
            sd[j] = rcpf(rsc[j]);
          }
          const uint32_t zero = lds4(SM_ZERO);
          mbar_wait(bar(B_RES), i == 10);
          uint32_t dep[16];
#pragma unroll
          for (int x = 0; x < 16; x++) {
            const int mi = x >> 3, half = (x >> 2) & 1, g = x & 3;
            uint32_t v[4];
            ldsm4(((e >> ((g >> 1) * 8)) & 31) * 8192 + ((ra ^ ((g & 1) * 64)) | (x ? dep[x - 1] : 0)) + (mi * 64 + half * 8) * 128, v[0], v[1], v[2], v[3]);
#pragma unroll
            for (int j = 0; j < 4; j++) {
              asm volatile("shl.b32 %0, %1, 16;" : "=f"(acc[mi][(g * 4 + j) * 4 + half * 2]) : "r"(v[j]));
              asm volatile("and.b32 %0, %1, 0xffff0000;" : "=f"(acc[mi][(g * 4 + j) * 4 + half * 2 + 1]) : "r"(v[j]));
              { acc[mi][(g * 4 + j) * 4 + half * 2] *= sd[mi * 2 + half]; acc[mi][(g * 4 + j) * 4 + half * 2 + 1] *= sd[mi * 2 + half]; }
            }
            asm("and.b32 %0, %1, %2;" : "=r"(dep[x]) : "f"(acc[mi][(g * 4 + 3) * 4 + half * 2 + 1]), "r"(zero));
          }
          mbar_arrive_warp(bar(B_RF));
        }
        auto stage = [&](int mi, int hi) {
          const int lane = lane_now();
          const uint32_t sw = SB + ((c_sched.task[t].stg >> (8 * hi)) & 31) * 8192 + (mi * 64 + w * 16) * 128, so = sw + (lane & 7) * 128 + (((lane >> 3) ^ (lane & 7)) << 4);
#pragma unroll
          for (int half = 0; half < 2; half++)
#pragma unroll
            for (int g = 0; g < 2; g++) {
              uint32_t v[4];
#pragma unroll
              for (int j = 0; j < 4; j++) {
                acc[mi][(hi * 8 + g * 4 + j) * 4 + half * 2] *= rsc[mi * 2 + half]; acc[mi][(hi * 8 + g * 4 + j) * 4 + half * 2 + 1] *= rsc[mi * 2 + half];
                v[j] = pack_bf16(acc[mi][(hi * 8 + g * 4 + j) * 4 + half * 2], acc[mi][(hi * 8 + g * 4 + j) * 4 + half * 2 + 1]);
              }
              stsm4((so ^ (g * 64)) + half * 1024, v[0], v[1], v[2], v[3]);
            }
          if (mi && !hi) mbar_arrive_warp(bar(B_SIG));
          if (hi == 0 || t == 21) {
            const int pitch = t == 21 ? D_ * 4 : 128;
            copy_out<4>(sw, t == 21 ? out : sc->y, (row0 + mi * 64 + w * 16) * pitch + (t == 21 ? par * (D_ * 2) + (hi * 8 + c) * 128 : par * (S_ * D_) + c * PANEL), pitch, lane);
          }
        };
        mainloop<2>(acc, sig, t, wg, sp, []() {}, [&]() { stage(0, 0); stage(0, 1); });
        TL(t, 3);
        stage(1, 0); mbar_arrive_warp(bar(B_SIG + 1));
        TL(t, 6);
        stage(1, 1); mbar_arrive_warp(bar(B_SIG + 2));
        if (t < 21) {
          const int lane = lane_now(), q = lane & 3;
          const uint32_t zero = lds4(SM_ZERO);
          float s[4], s2[4];
#pragma unroll
          for (int x = 0; x < 4; x++) {
            float a0 = x ? __uint_as_float(__float_as_uint(s[x - 1]) & zero) : 0.f, b0 = x ? __uint_as_float(__float_as_uint(s2[x - 1]) & zero) : 0.f;
#pragma unroll
            for (int j = 0; j < 32; j++) { const float d = acc[x >> 1][(j >> 1) * 4 + (x & 1) * 2 + (j & 1)]; a0 += d; b0 = fmaf(d, d, b0); }
            s[x] = a0; s2[x] = b0;
          }
#pragma unroll
          for (int x = 0; x < 2; x++) {
            s[x] = (q & 2 ? s[x + 2] : s[x]) + __shfl_xor_sync(0xffffffffu, q & 2 ? s[x] : s[x + 2], 2);
            s2[x] = (q & 2 ? s2[x + 2] : s2[x]) + __shfl_xor_sync(0xffffffffu, q & 2 ? s2[x] : s2[x + 2], 2);
          }
          const float r = (q & 1 ? s[1] : s[0]) + __shfl_xor_sync(0xffffffffu, q & 1 ? s[0] : s[1], 1);
          const float r2 = (q & 1 ? s2[1] : s2[0]) + __shfl_xor_sync(0xffffffffu, q & 1 ? s2[0] : s2[1], 1);
          asm volatile("st.global.v2.f32 [%0], {%1, %2};" ::"l"(&sc->stat[i == 10 ? 1 : l * 2][m][c][(q >> 1) * 64 + w * 16 + (q & 1) * 8 + (lane >> 2)]), "f"(r), "f"(r2) : "memory");
          mbar_arrive_warp(bar(B_SIG + 3));
        }
      }
    }
  }
}

typedef CUresult (*PFN_encodeTiled)(CUtensorMap*, CUtensorMapDataType, cuuint32_t, void*, const cuuint64_t*, const cuuint64_t*, const cuuint32_t*,
                                    const cuuint32_t*, CUtensorMapInterleave, CUtensorMapSwizzle, CUtensorMapL2promotion, CUtensorMapFloatOOBfill);

void make_map(PFN_encodeTiled enc, CUtensorMap* mp, const void* ptr, int rank, const cuuint64_t* gd, const cuuint64_t* gs, const cuuint32_t* bd) {
  const cuuint32_t es[4] = {1, 1, 1, 1};
  enc(mp, CU_TENSOR_MAP_DATA_TYPE_BFLOAT16, rank, const_cast<void*>(ptr), gd, gs, bd, es, CU_TENSOR_MAP_INTERLEAVE_NONE, CU_TENSOR_MAP_SWIZZLE_128B,
      CU_TENSOR_MAP_L2_PROMOTION_L2_128B, CU_TENSOR_MAP_FLOAT_OOB_FILL_NONE);
}
void make_map_act(PFN_encodeTiled enc, CUtensorMap* mp, const void* ptr, uint64_t cols, uint64_t s1, uint64_t s2, uint64_t s3, uint32_t rows) {
  const cuuint64_t gd[4] = {64, S_ / 2, cols / 64, 2}, gs[3] = {s1, s2, s3};
  const cuuint32_t bd[4] = {64, rows, 1, 1};
  make_map(enc, mp, ptr, 4, gd, gs, bd);
}
void make_map_w(PFN_encodeTiled enc, CUtensorMap* mp, const void* ptr, uint64_t rows, uint64_t cols, uint32_t np, uint64_t sp, uint64_t tiles, uint32_t nt) {
  const cuuint64_t gd[4] = {512, rows, np, tiles}, gs[3] = {cols * 2, sp, 1024};
  const cuuint32_t bd[4] = {64, 64, np, nt};
  make_map(enc, mp, ptr, 4, gd, gs, bd);
}

}

extern "C" void kernel_launch(void* const* d_in, const int* in_sizes, int n_in, void* d_out, int out_size) {
  (void)in_sizes; (void)n_in; (void)out_size;
  static PFN_encodeTiled enc = nullptr;
  static void *p_sc, *p_ops, *p_w;
  static int by_sm = 0;
  void (*const kernels[4])(Scratch*, const Ops*, const bf16*, bf16*, Params) = {fused_kernel<0, 0>, fused_kernel<1, 0>, fused_kernel<0, 1>, fused_kernel<1, 1>};
  if (!enc) {
    void* fn = nullptr; cudaDriverEntryPointQueryResult qr;
    cudaGetDriverEntryPoint("cuTensorMapEncodeTiled", &fn, cudaEnableDefault, &qr);
    enc = (PFN_encodeTiled)fn;
    cudaGetSymbolAddress(&p_sc, g_sc); cudaGetSymbolAddress(&p_ops, g_ops); cudaGetSymbolAddress(&p_w, g_w13);
    for (int i = 0; i < 4; i++) cudaFuncSetAttribute(kernels[i], cudaFuncAttributeMaxDynamicSharedMemorySize, SM_TOTAL);
    int dev = 0, sms = 0;
    cudaGetDevice(&dev);
    cudaDeviceGetAttribute(&sms, cudaDevAttrMultiProcessorCount, dev);
    by_sm = sms == NCTA + NHELP;
    for (int i = 1; i < 4 && by_sm; i++) {
      cudaLaunchConfig_t cfg = {};
      cudaLaunchAttribute at;
      at.id = cudaLaunchAttributeClusterDimension; at.val.clusterDim.x = 1 << i; at.val.clusterDim.y = at.val.clusterDim.z = 1;
      cfg.gridDim = dim3(NCTA); cfg.blockDim = dim3(384); cfg.dynamicSmemBytes = SM_TOTAL; cfg.attrs = &at; cfg.numAttrs = 1;
      int n = 0;
      if (cudaOccupancyMaxActiveClusters(&n, kernels[0], &cfg) != cudaSuccess) { (void)cudaGetLastError(); n = 0; }
      by_sm = n == (i == 1 ? 66 : i == 2 ? 30 : 15);
    }
  }
  Params P;
  Scratch* const sc = (Scratch*)p_sc;
  make_map_act(enc, &P.tm[M_X0], d_in[0], D_, D_ * 4, 128, D_ * 2, 128);
  make_map_act(enc, &P.tm[M_O], sc->o, D_, 128, PANEL, S_ * D_, 128);
  make_map_act(enc, &P.tm[M_Y], sc->y, D_, 128, PANEL, S_ * D_, 128);
  make_map_act(enc, &P.tm[M_H], sc->h, F_, 128, PANEL, S_ * F_, 128);
  make_map_act(enc, &P.tm[M_OL], sc->o, D_, 128, PANEL, S_ * D_, PROWS);
  make_map_act(enc, &P.tm[M_YL], sc->y, D_, 128, PANEL, S_ * D_, PROWS);
  make_map_act(enc, &P.tm[M_HL], sc->h, F_, 128, PANEL, S_ * F_, PROWS);
  make_map_act(enc, &P.tm[M_O24], sc->o, D_, 128, PANEL, S_ * D_, 24);
  make_map_w(enc, &P.tm[M_WQKV], d_in[1], D_, 3 * D_, 3, D_ * 2, 2, 1);
  make_map_w(enc, &P.tm[M_WO], d_in[2], D_, D_, 2, 1024, 1, 1);
  make_map_w(enc, &P.tm[M_W2], d_in[6], F_, D_, 2, 1024, 1, 1);
  const char *w1 = (const char*)d_in[4], *w3 = (const char*)d_in[5];
  if ((uint64_t)(w1 < w3 ? w3 - w1 : w1 - w3) >> 39) {
    cudaMemcpyAsync(p_w, w1, (size_t)D_ * F_ * 2, cudaMemcpyDeviceToDevice);
    cudaMemcpyAsync((bf16*)p_w + D_ * F_, w3, (size_t)D_ * F_ * 2, cudaMemcpyDeviceToDevice);
    w1 = (const char*)p_w; w3 = w1 + (size_t)D_ * F_ * 2;
  }
  const bool swap = w3 < w1;
  make_map_w(enc, &P.tm[M_W13], swap ? w3 : w1, D_, F_, 2, swap ? w1 - w3 : w3 - w1, 7, 1);
  make_map_w(enc, &P.tm[M_W13P], swap ? w3 : w1, D_, F_, 2, swap ? w1 - w3 : w3 - w1, 7, 2);
  kernels[by_sm * 2 + swap]<<<NCTA + NHELP, 384, SM_TOTAL>>>(sc, (const Ops*)p_ops, (const bf16*)d_in[0], (bf16*)d_out, P);
}
```

```cpp
#include <cuda_runtime.h>
#include <cuda_bf16.h>
#include <cuda.h>
#include <stdint.h>
#include <stddef.h>

typedef __nv_bfloat16 bf16;
#define GU_E 3
#define G_N1 7
#define Q_P1 4
#define Q_P2 6
#define Q_P0 1
#define RES_O 3
#define RES_D 3
#define HOLD_O 6
#define PROWS 16
#define GAP_O 150
#define GAP_Y 100
#define GAP_H 350
#define GAP_H6 1000
#define ST_T1 600
#define ST_D1 700
#define ST_ROWS 3500
#define WARM_T 4000
constexpr int TAILQ = 1, TAIL = 2;

namespace {

constexpr int S_ = 2048, D_ = 1024, F_ = 3584;
constexpr int PANEL = S_ / 2 * 128;
constexpr int NCTA = 128;
constexpr int NHELP = 4;

constexpr uint32_t SB = 1024;
constexpr int NU = 25;
constexpr uint32_t SM_STG  = SB + NU * 8192;
__host__ __device__ constexpr uint32_t xch(int i, int w) { return i ? SM_STG - 8192 + w * 2048 : SM_STG + w * 4096; }
constexpr uint32_t BARS    = SM_STG + 16384;
constexpr uint32_t SM_STAT = BARS + 896;
__host__ __device__ constexpr uint32_t stat(int set) { return SM_STAT + set * 1088 + 64; }
constexpr uint32_t SM_CS   = SM_STAT + 4352;
constexpr uint32_t SM_END  = SM_CS + 5120;
constexpr int SM_TOTAL = SM_END - SB;
static_assert(BARS % 1024 == 0 && SM_TOTAL <= 232448, "smem");
constexpr int B_FULL = 0, B_EMPTY = 16, B_SIG = 37, B_XCH = 41, B_RF = 42, B_STAT = 45, B_TURN = 49, B_RES = 51, B_FREE = 52, B_SF = 53, B_QT = 55, B_PASS = 56,
              B_CS = 57, B_DEP = 66, B_PUB = 82, B_N = 100;
__host__ __device__ constexpr uint32_t bar(int i) { return BARS + 8 * i; }
constexpr uint32_t SM_TAG = BARS + 8 * B_N, SM_ZERO = SM_TAG + 16;
constexpr int NB_PX = 1, NB_PY = 2, NB_OGO = 3, NB_END = 4;

constexpr int E_O0 = 0, E_O1 = 1, E_YA = 2, E_YB = 3, E_H4 = 4, E_XA = 7, E_XB = 8, E_N = 9;

constexpr int M_X0 = 0, M_O = 1, M_Y = 2, M_H = 3;
constexpr int M_WQKV = 4, M_WO = 5, M_W13 = 6, M_W13P = 7, M_W2 = 8;
constexpr int M_OL = 9, M_YL = 10, M_HL = 11, M_O24 = 12, M_N = 13;

constexpr int FIRST = 5;
constexpr int NOPA = 416, NOPB = 416, NSEG = 40;
constexpr uint32_t A_END = 1, A_TURN = 2, A_DRAIN = 4, A_WAIT = 8, A_SYNC = 16;
constexpr uint32_t A_MARK = 0;
struct Task { uint32_t stg, res, sig; };
struct Seg { uint32_t i8, end8, a, b; };
constexpr uint32_t LO_A = 0x10000 + SB / 16, LO_B = 0x2000000 + SB / 16;
struct Sched { Seg seg[2 * NSEG]; Task task[22]; };
struct Ops { uint2 a[NOPA + 64], b[NOPB + 64]; };
struct Gen {
  Sched s{}; Ops o{};
  int n[2] = {0, 0}, nseg[2] = {0, NSEG}, cur = -1, pos = 0, err = 0, res = 0, nres = 0;
  int mask[400] = {}, sa[400] = {}, sb[400][2] = {}, own[NU][2] = {}, tok[NU] = {}, known[2][2] = {{-1, -1}, {-1, -1}};
  constexpr void emit(int p, int wait, int par, int dst, int map, int kb8, int arr, int load, int y) {
    if (cur < FIRST) return;
    const uint2 e{(uint32_t)((p ? y >> 10 | (load ? map - M_WQKV : 0) << 3 | (y & 63) << 6 : (y & 63) | (y >> 10) << 6 | map << 7) | load << 12 | dst << 13 | (res ? B_RES : B_FULL + (cur & 15)) << 18 | wait << 24) | (uint32_t)(par & 1) << 31,
                  (uint32_t)(((y >> 6) & 15) | arr << 4 | (!p && arr && mask[cur] != 3 && !res) << 5 | ((cur + 2) & 15) << 9 | kb8 << 13)};
    if (p) o.b[n[1]++] = e; else o.a[n[0]++] = e;
  }
  constexpr bool done(int p, int x) const { return x < 0 || ((!(mask[x] & 1) || known[p][0] >= x) && (!(mask[x] & 2) || known[p][1] >= x)); }
  constexpr void op(int p, int dst, int nu, int map, int kb8, int arr, int y, int xw = -1, int xp = 0) {
    int w[8] = {}, wp[8] = {}, nw = 0;
    if (xw >= 0) { w[nw] = xw; wp[nw++] = xp; }
    for (int u = dst; u < dst + nu; u++) if (tok[u] && (u == dst || tok[u] != tok[u - 1])) { w[nw] = (tok[u] - 1) >> 1; wp[nw++] = tok[u] - 1; }
    for (int x = cur - 1; x >= 0; x--) {
      bool need = x <= cur - 12;
      for (int u = dst; u < dst + nu; u++) need = need || own[u][0] == x + 1 || own[u][1] == x + 1;
      if (!need || done(p, x)) continue;
      if (cur - x >= 16 || !done(p, x - 16)) err |= 1;
      w[nw] = B_EMPTY + ((x + 2) & 15); wp[nw++] = x >> 4;
      for (int g = 0; g < 2; g++) if (((mask[x] >> g) & 1) && known[p][g] < x) known[p][g] = x;
    }
    for (; nw > 1; nw--) emit(p, w[nw - 1], wp[nw - 1], 0, 0, 0, 0, 0, 0);
    emit(p, nw ? w[0] : B_PASS, nw ? wp[0] : 1, dst, map, kb8, arr, nu > 0, y);
    for (int u = dst; u < dst + nu; u++) { own[u][0] = cur + 1; own[u][1] = 0; tok[u] = 0; }
  }
  constexpr int step(int m) { mask[++cur] = m; return cur; }
  constexpr int slot() { int u = (pos + 1) & ~1; if (u >= 24) u = 0; pos = u + 2; return u; }
  constexpr int qslot() { int u = (pos + 4) / 5 * 5; if (u >= NU) u = 0; pos = u + 5; return u; }
  constexpr void stage(int u, int first, int t) {
    first -= TAIL;
    for (int x = u; x < u + 2; x++) { if (own[x][0] > first || own[x][1] > first || tok[x]) err |= 2; own[x][0] = cur + 1; own[x][1] = 0; tok[x] = t; }
  }
  static constexpr int kown(int hi) { return hi * 8 | 1 << 9; }
  static constexpr int kskip(int hi, int j) { return (hi * 8 + j) | (j + 1) << 6; }
  static constexpr int kpos(int p) { return p < 2 ? kown(p) : p < 9 ? kskip(0, p - 2) : kskip(1, p - 9); }
  constexpr void segs(int t, const int* st, const uint32_t* act, int cnt, int tail, int inc0) {
    const int g = t & 1, wrap = inc0 == 5 ? NU : 24;
    int j0 = 0;
    for (int j = 0; j < cnt; j++) {
      const int x = st[j], inc = inc0 ? inc0 : mask[st[j0]] == 3 ? 6 : 4;
      const bool next = j + 1 < cnt && st[j + 1] == x + 1 && mask[x + 1] == mask[x] && sa[x + 1] == (sa[x] + inc) % wrap && sb[x + 1][g] == (sb[x][g] + inc) % wrap;
      if (j >= cnt - tail - 1 && j + 1 < cnt && !next) err |= 4;
      if (j + 1 < cnt && st[j + 1] != x + 1 && !(act[j] & A_DRAIN)) err |= 8;
      if (j >= cnt - tail || (next && !act[j] && j != cnt - tail - 1)) continue;
      if (j == j0 && (j == 0 || (inc0 != 4 && (act[j - 1] & (A_DRAIN | A_SYNC))))) err |= 16;
      const int y = st[j0];
      s.seg[nseg[g]++] = Seg{(uint32_t)y * 8 | (act[j] | (j == cnt - tail - 1 ? A_END : 0)) << 16, (uint32_t)(x + 1) * 8 | inc * 512 << 16, LO_A + sa[y] * 512, LO_B + sb[y][g] * 512};
      j0 = j + 1;
    }
  }
  constexpr void residual(int t, int map, bool q) {
    const int u0 = q ? qslot() : slot(), u1 = q ? u0 + 2 : slot();
    res = 1;
    op(0, u0, 2, map, 4, 1, kown(0)); op(0, u1, 2, map, 0, 0, kown(1));
    res = 0;
    for (int x = 0; x < 4; x++) { const int u = (x < 2 ? u0 : u1) + (x & 1); own[u][0] = 0; tok[u] = 1 + B_RF * 2 + (nres & 1); }
    nres++;
    s.task[t].res = u0 | u1 << 8;
  }
  constexpr Gen() {
    int cs[4] = {};
    for (int t = 0; t < 22; t++) {
      const int i = t % 11, use = i == 0 ? 2 : (i == 2 || i == 10) ? 15 : 3;
      for (int x = 0; x < 4; x++) if ((use >> x) & 1) s.task[t].sig |= (cs[x]++ & 1) << x;
    }
    for (int l = 0; l < 2; l++) {
      const int T = l * 11, dep = B_DEP + l * E_N;
      int st[7][56] = {};
      uint32_t act[7][56] = {};
      if (l == 1) {
        const int first = cur + 1;
        for (int j = 0; j < 4; j++) {
          const int x = st[j >> 1][j & 1] = step(1 << ((T + (j >> 1)) & 1)), u = qslot();
          sb[x][0] = sb[x][1] = u + 2;
          if (j < 2) {
            sa[x] = (u + 5) % NU; stage(sa[x], first, j ? 1 + B_SF * 2 + 1 : 0); s.task[10].stg |= sa[x] << (8 * j);
            op(0, 0, 0, 0, 0, 1, 1 << 10, B_SIG + 2 * j, s.task[10].sig >> (2 * j));
          }
          else { sa[x] = sa[x - 2]; own[sa[x]][1] = own[sa[x] + 1][1] = x + 1; op(0, 0, 0, 0, 0, 1, 0); }
          op(1, u + 2, 3, M_WQKV, 3, 1, kown(j & 1) | (j >> 1) << 10);
        }
        act[0][1] = A_DRAIN; act[1][1] = A_DRAIN | A_WAIT;
      }
      for (int i = 0; i < 2; i++) {
        for (int j = 2 * l; j < 16; j++) {
          if (i && j == 16 - RES_O) residual(T + 2, l ? M_Y : M_X0, true);
          const int x = st[i][j] = step(1 << ((T + i) & 1)), u = qslot(), k = l ? kpos(j) : j;
          sa[x] = u; sb[x][0] = sb[x][1] = u + 2;
          op(0, u, 2, l ? M_Y : M_X0, 2, 1, k, l && i == 0 && (j == 2 || j == 9) ? B_DEP + (j == 2 ? E_XA : E_XB) : -1);
          op(1, u + 2, 3, M_WQKV, 3, 1, k | i << 10);
        }
        if (i) act[1][Q_P1 - 1 + (l ? 2 : Q_P0)] = act[1][Q_P2 - 1 + (l ? 2 : Q_P0)] = A_SYNC;
        if (i && own[NU - 1][0] > cur - TAILQ) err |= 256;
        segs(T + i, st[i], act[i], 16, TAILQ, 5);
      }
      for (int j = 0; j < 16; j++) {
        const int x = st[0][j] = step(1 << (T & 1)), k = j < 8 ? j : j == 8 ? kown(1) : kskip(1, j - 9), hold = j == HOLD_O ? B_PUB + l * E_N + E_O1 : -1;
        act[0][j] = j == 8 ? A_MARK : 0;
        if (j != 8) { sa[x] = slot(); op(0, sa[x], 2, M_O, 2, 1, k, j == 0 ? dep + E_O0 : j == 9 ? dep + E_O1 : hold); }
        else { sa[x] = NU; op(0, 0, 0, 0, 0, 1, 1 << 10, B_SIG + 1, s.task[T + 1].sig >> 1); }
        sb[x][0] = sb[x][1] = slot();
        op(1, sb[x][0], 2, M_WO, 2, 1, k, hold);
      }
      segs(T + 2, st[0], act[0], 16, TAIL, 4);
      int beg[8] = {0, 16}, end[7] = {16, 32 - G_N1}, cnt[7] = {};
      for (int j = 2; j < 7; j++) { beg[j] = end[j - 2] + GU_E; end[j] = beg[j] + 16; }
      beg[7] = end[6];
      const int first = cur + 1;
      for (int j = 0; j < end[6]; j++) {
        int tl[2] = {-1, -1}, m = 0;
        for (int v = 0; v < 7; v++) if ((j >= beg[v] && j < end[v]) || (v == 1 && j < G_N1)) { const int g = (T + 3 + v) & 1; if (tl[g] >= 0) err |= 32; tl[g] = v; m |= 1 << g; }
        if (!m) err |= 32;
        if (j == end[6] - RES_D) residual(T + 10, M_Y, false);
        const int x = step(m), k = kpos(j < 16 ? j : (j + G_N1) & 15);
        const int v0 = m == 3 ? (tl[0] < tl[1] ? tl[0] : tl[1]) : tl[m >> 1];
        const int ps = (pos + 1) / 2 % 12;
        const bool last = m == 3 && (ps % 3 == 1 || (j >= 2 && j < G_N1 && (ps % 3 == 0 || (j == 2 && ps != 11))));
        if (!last) sa[x] = slot();
        const int u = slot();
        if (m == 3 && slot() != u + 2) err |= 32;
        if (last) sa[x] = slot();
        if (j < 2) { stage(sa[x], first, j ? 1 + B_SF * 2 : 0); s.task[T + 2].stg |= sa[x] << (8 * j); op(0, 0, 0, 0, 0, 1, 1 << 10, B_SIG + 2 * j, s.task[T + 2].sig >> (2 * j)); }
        else op(0, sa[x], 2, M_Y, 2, 1, k, j == 2 ? dep + E_YA : j == 9 ? dep + E_YB : -1);
        op(1, u, m == 3 ? 4 : 2, m == 3 ? M_W13P : M_W13, m == 3 ? 4 : 2, 1, k | v0 << 10, j == 3 ? B_PUB + l * E_N + E_YA : -1);
        for (int g = 0; g < 2; g++) {
          const int v = tl[g];
          if (v < 0) continue;
          sb[x][g] = u + (v - v0) * 2;
          act[v][cnt[v]] = j == beg[v + 1] - 1 ? A_TURN : v == 1 && j == G_N1 - 1 ? A_DRAIN | A_WAIT : v == 0 && j == 1 ? A_MARK : 0;
          st[v][cnt[v]++] = x;
        }
      }
      for (int v = 0; v < 7; v++) { if (cnt[v] != 16) err |= 64; segs(T + 3 + v, st[v], act[v], 16, 0, 0); }
      for (int j = 0; j < 56; j++) {
        const int x = st[0][j] = step(1 << (T & 1));
        act[0][j] = 0;
        sa[x] = slot(); op(0, sa[x], 2, M_H, 2, 1, j, j == 0 ? dep + E_H4 : j == 40 ? dep + E_H4 + 1 : j == 48 ? dep + E_H4 + 2 : -1);
        sb[x][0] = sb[x][1] = slot(); op(1, sb[x][0], 2, M_W2, 2, 1, j);
      }
      segs(T + 10, st[0], act[0], 56, TAIL, 4);
    }
    { const int u0 = slot(), u1 = slot(); stage(u0, cur + 1, 0); stage(u1, cur + 1, 0); s.task[21].stg = u0 | u1 << 8; }
    if (n[0] > NOPA || n[1] > NOPB || nseg[0] >= NSEG || nseg[1] >= 2 * NSEG) err |= 128;
    for (int x = n[0]; x < NOPA + 64; x++) o.a[x] = uint2{B_PASS << 24 | 1u << 31, 0};
    for (int x = n[1]; x < NOPB + 64; x++) o.b[x] = uint2{B_PASS << 24 | 1u << 31, 0};
  }
};
constexpr Gen GEN{};
static_assert(GEN.err == 0, "schedule");
constexpr int NOP0 = (GEN.n[0] + 31) / 32 * 32, NOP1 = (GEN.n[1] + 31) / 32 * 32;

struct __align__(64) Params {
  CUtensorMap tm[M_N];
};

}

__constant__ Sched c_sched = GEN.s;
__device__ const Ops g_ops = GEN.o;
struct __align__(1024) Scratch {
  float2 stat[3][16][8][128];
  uint4 stat0[16][128];
  uint4 halo[4][16][8][6][32];
  uint4 cs[9][8][64];
  uint32_t flags[NCTA][32];
  uint32_t cnt[4][32];
  uint32_t epoch[NCTA + NHELP];
  __align__(1024) bf16 o[S_ * D_];
  bf16 y[S_ * D_], h[S_ * F_];
};
__device__ Scratch g_sc;
__device__ __align__(1024) bf16 g_w13[2 * D_ * F_];

#define TL(t, i) do {} while (0)
#define TS(i8, wg) do {} while (0)
#define TLW(t, i) do {} while (0)
#define MB_LIMIT (1 << 16)
#define FL_LIMIT (1 << 21)

namespace {

__device__ __forceinline__ uint32_t smem_u32(const void* p) { return (uint32_t)__cvta_generic_to_shared(p); }
__device__ __forceinline__ void mbar_init(uint32_t br, uint32_t cnt) { asm volatile("mbarrier.init.shared::cta.b64 [%0], %1;" ::"r"(br), "r"(cnt)); }
__device__ __forceinline__ void mbar_expect_tx(uint32_t br, uint32_t bytes) { asm volatile("mbarrier.arrive.expect_tx.shared::cta.b64 _, [%0], %1;" ::"r"(br), "r"(bytes) : "memory"); }
__device__ __forceinline__ void mbar_arrive(uint32_t br) { asm volatile("mbarrier.arrive.shared::cta.b64 _, [%0];" ::"r"(br) : "memory"); }
__device__ __forceinline__ void mbar_arrive_if(uint32_t br, uint32_t p) {
  asm volatile("{\n.reg .pred q;\nsetp.ne.u32 q, %1, 0;\n@q mbarrier.arrive.shared::cta.b64 _, [%0];\n}\n" ::"r"(br), "r"(p) : "memory");
}
__device__ __forceinline__ void mbar_arrive_warp(uint32_t br) {
  asm volatile("{\n.reg .pred q;\nbar.warp.sync 0xffffffff;\nelect.sync _|q, 0xffffffff;\n@q mbarrier.arrive.shared::cta.b64 _, [%0];\n}\n" ::"r"(br) : "memory");
}
__device__ __forceinline__ bool mbar_try_wait(uint32_t br, uint32_t parity) {
  uint32_t ok;
  asm volatile("{\n.reg .pred p;\nmbarrier.try_wait.parity.shared::cta.b64 p, [%1], %2;\nselp.u32 %0, 1, 0, p;\n}\n" : "=r"(ok) : "r"(br), "r"(parity) : "memory");
  return ok;
}
__device__ __forceinline__ void mbar_wait(uint32_t br, uint32_t parity) {
#pragma unroll 1
  for (int it = 0; it < MB_LIMIT; ++it) { if (mbar_try_wait(br, parity)) return; }
  __trap();
}
__device__ __forceinline__ bool elect_one() { uint32_t p; asm volatile("{\n.reg .pred P;\nelect.sync _|P, 0xffffffff;\nselp.u32 %0, 1, 0, P;\n}\n" : "=r"(p)); return p; }
__device__ __forceinline__ void fence_proxy_async_smem() { asm volatile("fence.proxy.async.shared::cta;" ::: "memory"); }
__device__ __forceinline__ void tma4d(uint32_t dst, const CUtensorMap* m, int c0, int c1, int c2, int c3, uint32_t br) {
  asm volatile("cp.async.bulk.tensor.4d.shared::cluster.global.mbarrier::complete_tx::bytes [%0], [%1, {%3, %4, %5, %6}], [%2];" ::"r"(dst), "l"(m), "r"(br), "r"(c0), "r"(c1), "r"(c2), "r"(c3) : "memory");
}
__device__ __forceinline__ void tma4d_store(const CUtensorMap* m, uint32_t src, int c1, int c2, int c3) {
  asm volatile("{\n.reg .pred p;\nelect.sync _|p, 0xffffffff;\n@p cp.async.bulk.tensor.4d.global.shared::cta.bulk_group [%0, {%5, %2, %3, %4}], [%1];\n}\n" ::"l"(m), "r"(src), "r"(c1), "r"(c2), "r"(c3), "r"(0) : "memory");
}
__device__ __forceinline__ void stsm4(uint32_t a, uint32_t x, uint32_t y, uint32_t z, uint32_t w) {
  asm volatile("stmatrix.sync.aligned.m8n8.x4.shared.b16 [%0], {%1,%2,%3,%4};" ::"r"(a), "r"(x), "r"(y), "r"(z), "r"(w) : "memory");
}
__device__ __forceinline__ void stsm4t(uint32_t a, uint32_t x, uint32_t y, uint32_t z, uint32_t w) {
  asm volatile("stmatrix.sync.aligned.m8n8.x4.trans.shared.b16 [%0], {%1,%2,%3,%4};" ::"r"(a), "r"(x), "r"(y), "r"(z), "r"(w) : "memory");
}
__device__ __forceinline__ void ldsm4(uint32_t a, uint32_t& x, uint32_t& y, uint32_t& z, uint32_t& w) {
  asm volatile("ldmatrix.sync.aligned.m8n8.x4.shared.b16 {%0,%1,%2,%3}, [%4];" : "=r"(x), "=r"(y), "=r"(z), "=r"(w) : "r"(a) : "memory");
}
__device__ __forceinline__ void st_tag(uint4* p, uint32_t a, uint32_t b, uint32_t c, uint32_t tag) {
  asm volatile("{\n.reg .b64 x, y;\n.reg .b128 z;\nmov.b64 x, {%1, %2};\nmov.b64 y, {%3, %4};\nmov.b128 z, {x, y};\nst.relaxed.gpu.global.b128 [%0], z;\n}\n" ::"l"(p), "r"(a), "r"(b), "r"(c), "r"(tag) : "memory");
}
__device__ __forceinline__ uint4 ld_tag(const uint4* p) {
  uint4 v;
  asm volatile("{\n.reg .b64 x, y;\n.reg .b128 z;\nld.relaxed.gpu.global.b128 z, [%4];\nmov.b128 {x, y}, z;\nmov.b64 {%0, %1}, x;\nmov.b64 {%2, %3}, y;\n}\n" : "=r"(v.x), "=r"(v.y), "=r"(v.z), "=r"(v.w) : "l"(p) : "memory");
  return v;
}
template <int NAP, int N> __device__ __forceinline__ void ld_tag_wait(uint4 (&v)[N], const uint4* p, uint32_t tag) {
#pragma unroll 1
  for (int it = 0; it < FL_LIMIT; ++it) {
    uint32_t bad = 0;
#pragma unroll
    for (int j = 0; j < N; j++) v[j] = ld_tag(p + j * 32);
#pragma unroll
    for (int j = 0; j < N; j++) bad |= v[j].w ^ tag;
    if (__all_sync(0xffffffffu, bad == 0)) return;
    if (NAP) __nanosleep(NAP);
  }
  __trap();
}
__device__ __forceinline__ void prefetch_tmap(const CUtensorMap* m) { asm volatile("prefetch.tensormap [%0];" ::"l"(m) : "memory"); }
__device__ __forceinline__ void wgmma_fence() { asm volatile("wgmma.fence.sync.aligned;" ::: "memory"); }
__device__ __forceinline__ void wgmma_commit() { asm volatile("wgmma.commit_group.sync.aligned;" ::: "memory"); }
template <int N> __device__ __forceinline__ void wgmma_wait() { asm volatile("wgmma.wait_group.sync.aligned %0;" ::"n"(N) : "memory"); }
template <int R> __device__ __forceinline__ void reg_alloc() { asm volatile("setmaxnreg.inc.sync.aligned.u32 %0;" ::"n"(R)); }
template <int R> __device__ __forceinline__ void reg_dealloc() { asm volatile("setmaxnreg.dec.sync.aligned.u32 %0;" ::"n"(R)); }
__device__ __forceinline__ void bar_sync(int id, int n) { asm volatile("bar.sync %0, %1;" ::"r"(id), "r"(n) : "memory"); }
__device__ __forceinline__ void bar_arrive(int id, int n) { asm volatile("bar.arrive %0, %1;" ::"r"(id), "r"(n) : "memory"); }
__device__ __forceinline__ uint32_t ld_acquire(const uint32_t* p) { uint32_t v; asm volatile("ld.acquire.gpu.global.u32 %0, [%1];" : "=r"(v) : "l"(p) : "memory"); return v; }
__device__ __forceinline__ void st_release(uint32_t* p, uint32_t v) { asm volatile("st.release.gpu.global.u32 [%0], %1;" ::"l"(p), "r"(v) : "memory"); }
__device__ __forceinline__ uint4 ldcg16(const void* p) { uint4 v; asm volatile("ld.global.cg.v4.u32 {%0,%1,%2,%3}, [%4];" : "=r"(v.x), "=r"(v.y), "=r"(v.z), "=r"(v.w) : "l"(p) : "memory"); return v; }
__device__ __forceinline__ float2 lds8f(uint32_t a) { float2 v; asm volatile("ld.shared.v2.f32 {%0,%1}, [%2];" : "=f"(v.x), "=f"(v.y) : "r"(a)); return v; }
__device__ __forceinline__ float lds4f(uint32_t a) { float v; asm volatile("ld.shared.f32 %0, [%1];" : "=f"(v) : "r"(a)); return v; }
__device__ __forceinline__ uint32_t lds4(uint32_t a) { uint32_t v; asm volatile("ld.shared.u32 %0, [%1];" : "=r"(v) : "r"(a) : "memory"); return v; }
__device__ __forceinline__ void lds16f(uint32_t a, float& x, float& y, float& z, float& w) { asm volatile("ld.shared.v4.f32 {%0,%1,%2,%3}, [%4];" : "=f"(x), "=f"(y), "=f"(z), "=f"(w) : "r"(a) : "memory"); }
__device__ __forceinline__ void sts8f(uint32_t a, float x, float y) { asm volatile("st.shared.v2.f32 [%0], {%1,%2};" ::"r"(a), "f"(x), "f"(y) : "memory"); }
__device__ __forceinline__ void sts4f(uint32_t a, float x) { asm volatile("st.shared.f32 [%0], %1;" ::"r"(a), "f"(x) : "memory"); }
__device__ __forceinline__ void sts16(uint32_t a, uint32_t x, uint32_t y, uint32_t z, uint32_t w) { asm volatile("st.shared.v4.u32 [%0], {%1,%2,%3,%4};" ::"r"(a), "r"(x), "r"(y), "r"(z), "r"(w) : "memory"); }
__device__ __forceinline__ void lds16(uint32_t a, uint32_t& x, uint32_t& y, uint32_t& z, uint32_t& w) { asm volatile("ld.shared.v4.u32 {%0,%1,%2,%3}, [%4];" : "=r"(x), "=r"(y), "=r"(z), "=r"(w) : "r"(a) : "memory"); }
__device__ __forceinline__ uint32_t pack_bf16(float a, float b) { uint32_t r; asm("cvt.rn.bf16x2.f32 %0, %1, %2;" : "=r"(r) : "f"(b), "f"(a)); return r; }
__device__ __forceinline__ uint32_t pack_bf16_v(float a, float b) { uint32_t r; asm volatile("cvt.rn.bf16x2.f32 %0, %1, %2;" : "=r"(r) : "f"(b), "f"(a)); return r; }
__device__ __forceinline__ float bf_lo(uint32_t v) { return __uint_as_float(v << 16); }
__device__ __forceinline__ float bf_hi(uint32_t v) { return __uint_as_float(v & 0xffff0000u); }
constexpr float LOG2E = 1.4426950408889634f;
__device__ __forceinline__ float ex2f(float x) { float y; asm("ex2.approx.ftz.f32 %0, %1;" : "=f"(y) : "f"(x)); return y; }
__device__ __forceinline__ float tanhf_(float x) { float y; asm("tanh.approx.f32 %0, %1;" : "=f"(y) : "f"(x)); return y; }
__device__ __forceinline__ float rcpf(float x) { float y; asm("rcp.approx.ftz.f32 %0, %1;" : "=f"(y) : "f"(x)); return y; }
__device__ __forceinline__ float bf_round(float a) { return bf_lo(pack_bf16(a, 0.f)); }
__device__ __forceinline__ uint32_t movmat(uint32_t a) { uint32_t d; asm volatile("movmatrix.sync.aligned.m8n8.trans.b16 %0, %1;" : "=r"(d) : "r"(a)); return d; }
__device__ __forceinline__ void mma16816(float& d0, float& d1, float& d2, float& d3, uint32_t a0, uint32_t a1, uint32_t a2, uint32_t a3, uint32_t b0, uint32_t b1,
                                         float c0, float c1, float c2, float c3) {
  asm volatile("mma.sync.aligned.m16n8k16.row.col.f32.bf16.bf16.f32 {%0,%1,%2,%3}, {%4,%5,%6,%7}, {%8,%9}, {%10,%11,%12,%13};"
               : "=f"(d0), "=f"(d1), "=f"(d2), "=f"(d3) : "r"(a0), "r"(a1), "r"(a2), "r"(a3), "r"(b0), "r"(b1), "f"(c0), "f"(c1), "f"(c2), "f"(c3));
}
template <int N> __device__ __forceinline__ void copy_out(uint32_t a, void* base, uint32_t ofs, int pitch, int lane) {
  a += (lane >> 3) * 128 + (((lane ^ (lane >> 3)) & 7) << 4);
  char* const g = static_cast<char*>(base) + (ofs + (lane >> 3) * pitch + (lane & 7) * 16);
  uint32_t v[N][4];
  __syncwarp();
#pragma unroll
  for (int j = 0; j < N; j++) lds16((a ^ ((j & 1) * 64)) + j * 512, v[j][0], v[j][1], v[j][2], v[j][3]);
#pragma unroll
  for (int j = 0; j < N; j++) asm volatile("st.global.v4.u32 [%0], {%1, %2, %3, %4};" ::"l"(g + j * 4 * pitch), "r"(v[j][0]), "r"(v[j][1]), "r"(v[j][2]), "r"(v[j][3]) : "memory");
}
__device__ __forceinline__ int lane_now() { int v; asm volatile("mov.u32 %0, %%laneid;" : "=r"(v)); return v; }
__device__ __forceinline__ uint32_t uni(uint32_t x, int lane) { return __shfl_sync(0xffffffffu, x + lane, 0); }
__device__ __forceinline__ uint64_t dsc(uint32_t hi, uint32_t lo) { return ((uint64_t)hi << 32) | lo; }

#define R8(a, o) "+f"(a[o]), "+f"(a[o + 1]), "+f"(a[o + 2]), "+f"(a[o + 3]), "+f"(a[o + 4]), "+f"(a[o + 5]), "+f"(a[o + 6]), "+f"(a[o + 7])
#define R32(a, o) R8(a, o), R8(a, o + 8), R8(a, o + 16), R8(a, o + 24)
#define REG64 "%0, %1, %2, %3, %4, %5, %6, %7, %8, %9, %10, %11, %12, %13, %14, %15, %16, %17, %18, %19, %20, %21, %22, %23, %24, %25, %26, %27, %28, %29, %30, %31, " \
              "%32, %33, %34, %35, %36, %37, %38, %39, %40, %41, %42, %43, %44, %45, %46, %47, %48, %49, %50, %51, %52, %53, %54, %55, %56, %57, %58, %59, %60, %61, %62, %63"
#define REG96 REG64 ", %64, %65, %66, %67, %68, %69, %70, %71, %72, %73, %74, %75, %76, %77, %78, %79, %80, %81, %82, %83, %84, %85, %86, %87, %88, %89, %90, %91, %92, %93, %94, %95"
__device__ __forceinline__ void wgmma(float (&d)[64], uint64_t da, uint64_t db) {
  asm volatile("wgmma.mma_async.sync.aligned.m64n128k16.f32.bf16.bf16 {" REG64 "}, %64, %65, 1, 1, 1, 0, 1;\n"
               : R32(d, 0), R32(d, 32) : "l"(da), "l"(db));
}
__device__ __forceinline__ void wgmma(float (&d)[96], uint64_t da, uint64_t db) {
  asm volatile("wgmma.mma_async.sync.aligned.m64n192k16.f32.bf16.bf16 {" REG96 "}, %96, %97, 1, 1, 1, 0, 1;\n"
               : R32(d, 0), R32(d, 32), R32(d, 64) : "l"(da), "l"(db));
}
#define W8(a, o) "=f"(a[o]), "=f"(a[o + 1]), "=f"(a[o + 2]), "=f"(a[o + 3]), "=f"(a[o + 4]), "=f"(a[o + 5]), "=f"(a[o + 6]), "=f"(a[o + 7])
#define W32(a, o) W8(a, o), W8(a, o + 8), W8(a, o + 16), W8(a, o + 24)
__device__ __forceinline__ void wgmma_z(float (&d)[64], uint64_t da, uint64_t db) {
  asm volatile("wgmma.mma_async.sync.aligned.m64n128k16.f32.bf16.bf16 {" REG64 "}, %64, %65, 0, 1, 1, 0, 1;\n"
               : W32(d, 0), W32(d, 32) : "l"(da), "l"(db));
}
__device__ __forceinline__ void wgmma_z(float (&d)[96], uint64_t da, uint64_t db) {
  asm volatile("wgmma.mma_async.sync.aligned.m64n192k16.f32.bf16.bf16 {" REG96 "}, %96, %97, 0, 1, 1, 0, 1;\n"
               : W32(d, 0), W32(d, 32), W32(d, 64) : "l"(da), "l"(db));
}

__device__ __forceinline__ void wgmma_cs(float (&d)[4], uint64_t da, uint64_t db) {
  asm volatile("wgmma.mma_async.sync.aligned.m64n8k16.f32.bf16.bf16 {%0, %1, %2, %3}, %4, %5, 1, 1, 1, 1, 0;\n" : "+f"(d[0]), "+f"(d[1]), "+f"(d[2]), "+f"(d[3]) : "l"(da), "l"(db));
}
__device__ __forceinline__ void bulk_commit() { asm volatile("cp.async.bulk.commit_group;" ::: "memory"); }
__device__ __forceinline__ void bulk_wait() { asm volatile("cp.async.bulk.wait_group 0;" ::: "memory"); }
__device__ __forceinline__ void fence_bar_init() { asm volatile("fence.mbarrier_init.release.cluster;" ::: "memory"); }

__device__ __forceinline__ uint32_t clock_now() { uint32_t v; asm volatile("mov.u32 %0, %%clock;" : "=r"(v)); return v; }
__device__ __forceinline__ void delay_until(uint32_t t0, int cycles) {
#pragma unroll 1
  for (int it = 0; it < 1000 && (int)(clock_now() - t0) < cycles; it++) __nanosleep(40);
}
__device__ __forceinline__ uint32_t ld_epoch(const uint32_t* p) { uint32_t v; asm volatile("ld.global.u32 %0, [%1];" : "=r"(v) : "l"(p) : "memory"); return v + 1; }
__device__ __forceinline__ void wait_flags(const uint32_t* f, uint32_t tag) {
#pragma unroll 1
  for (int it = 0; it < FL_LIMIT; ++it) if (__all_sync(0xffffffffu, (int)(ld_acquire(f) - tag) >= 0)) return;
  __trap();
}

__device__ __forceinline__ float2 ln_finish(float sum, float sq) {
  const float mean = sum * (1.f / D_), var = fmaxf(fmaf(-mean, mean, sq * (1.f / D_)), 0.f);
  const float mb = bf_round(mean);
  const float vb = bf_round(var);
  const float sd = bf_round(sqrtf(bf_round(vb + 1e-5f)));
  return make_float2(1.0f / sd, -mb);
}

__device__ __forceinline__ void helper_cta(const Params& P, Scratch* sc, int e, int wg, int w) {
  const int tid = threadIdx.x;
  if (tid == 256) {
#pragma unroll
    for (int i = 0; i < 16; i++) mbar_init(bar(i), 1);
    fence_bar_init();
  }
  if (tid < 64) sts16(SM_STG + tid * 16, 0x3f803f80u, 0x3f803f80u, 0x3f803f80u, 0x3f803f80u);
  fence_proxy_async_smem();
  __syncthreads();
  if (wg == 2) {
    if (w == 0) {
#pragma unroll 1
      for (int n = 0; n < 9 * 32; n++) {
        const int job = n >> 5;
        const uint32_t fb = bar(n & 7), dst = SB + (n & 7) * 24576;
        mbar_wait(bar(8 + (n & 7)), (n >> 3) + 1);
        if (elect_one()) {
          mbar_expect_tx(fb, job < 2 ? 24576 : 16384);
          tma4d(dst, &P.tm[job < 2 ? M_WQKV : M_W13], (e * 2 + (n & 1)) * 64, (n & 30) * 32, 0, job < 2 ? job : job - 2, fb);
        }
        __syncwarp();
      }
    }
  } else {
    const uint32_t tag = ld_epoch(sc->epoch + NCTA + e);
    const int lane = tid & 31;
#pragma unroll 1
    for (int job = 0; job < 9; job++) {
      float s[3][4] = {};
#pragma unroll 1
      for (int n = job * 32 + wg; n < job * 32 + 32; n += 2) {
        mbar_wait(bar(n & 7), n >> 3);
        wgmma_fence();
        const uint32_t a = ((SB + (n & 7) * 24576) >> 4) + 0x2000000;
#pragma unroll
        for (int k = 0; k < 8; k++) wgmma_cs(s[k & 1], dsc(0x40000040u, a + (k & 1) * 512 + (k >> 1) * 128), dsc(0x40000040u, (SM_STG >> 4) + 0x10000));
        if (job < 2) {
          wgmma_fence();
#pragma unroll
          for (int k = 0; k < 4; k++) wgmma_cs(s[2], dsc(0x40000040u, a + 1024 + k * 128), dsc(0x40000040u, (SM_STG >> 4) + 0x10000));
        }
        wgmma_commit();
        wgmma_wait<0>();
        mbar_arrive_if(bar(8 + (n & 7)), (tid & 127) == 0);
      }
      if (!(lane & 2))
        st_tag(&sc->cs[job][e * 2 + wg][w * 16 + (lane & 1) * 8 + (lane >> 2)], __float_as_uint(lane & 1 ? s[0][2] : s[0][0]), __float_as_uint(lane & 1 ? s[1][2] : s[1][0]),
               __float_as_uint(lane & 1 ? s[2][2] : s[2][0]), tag);
      __syncwarp();
    }
    bar_sync(NB_END, 256);
    if (tid == 0) sc->epoch[NCTA + e] = tag;
  }
}

template <bool WEIGHTS>
__device__ __forceinline__ void producer(const Params& P, const uint2* tab, int nop, int lane, int c, int row, int par, uint32_t t_entry) {
  uint64_t pol;
  asm volatile("createpolicy.fractional.L2::evict_first.b64 %0, 1.0;" : "=l"(pol));
  __syncthreads();
  uint2 nx = __ldg(tab + lane), n2 = __ldg(tab + 32 + lane);
#pragma unroll 1
  for (int j = 1; j < FIRST; j++) {
    delay_until(t_entry, ST_T1 + (j - 1) * ST_D1);
    if (elect_one()) {
      mbar_expect_tx(bar(B_FULL) + 8 * j, WEIGHTS ? 24576 : 16384);
      if (WEIGHTS) tma4d(SB + j * 40960 + 16384, &P.tm[M_WQKV], c * 64, j * 64, 0, 0, bar(B_FULL) + 8 * j);
      else tma4d(SB + j * 40960, &P.tm[M_X0], 0, row, j, par, bar(B_FULL) + 8 * j);
    }
    __syncwarp();
  }
  if (!WEIGHTS && lane == 0) {
#pragma unroll
    for (int j = 0; j < FIRST; j++) mbar_arrive(bar(B_EMPTY + 2 + j));
  }
  __syncwarp();
  auto word = [&](uint2 e) { return e.x + (((int)(e.y & 7) > c) + (e.y & 8 ? c : 0)) * (WEIGHTS ? 64 : 1); };
  uint32_t xn = __shfl_sync(0xffffffffu, word(nx), 0);
  const uint64_t maps = reinterpret_cast<uint64_t>(&P.tm[WEIGHTS ? M_WQKV : 0]);
  if ((uint32_t)maps > 0xfffff000u) __trap();
  const uint32_t sb = uni(SB, lane), bars = uni(BARS, lane), zero = uni(0, lane), mlo = uni((uint32_t)maps, lane), mhi = uni(maps >> 32, lane);
#pragma unroll 1
  for (int base = 0; base < nop; base += 32) {
    const uint2 e = nx;
    nx = n2;
    n2 = __ldg(tab + base + 64 + lane);
    const uint32_t xw = word(lane ? e : nx), bytes = e.y & 0xe000, eb = (e.y >> 6) & 0x78;
    const int arr = e.y & 16 ? lane + 1 : 0, solo = e.y & 32 ? lane + 1 : 0;
#pragma unroll 1
    for (int j = 1; j <= 32; j++) {
      const uint32_t x = xn;
      xn = __shfl_sync(0xffffffffu, xw, j);
#define OP_WAIT(X) "{\n.reg .pred pe, pa, pn, ps, pw;\n.reg .u32 it;\n" \
                "elect.sync _|pe, 0xffffffff;\nsetp.eq.u32 pa, %0, %1;\nsetp.ne.and.u32 pn, %2, 0, pe;\n" X \
                "mov.u32 it, 0;\n" \
                "WAIT_%=:\n" \
                "mbarrier.try_wait.parity.shared::cta.b64 pw, [%3 + %9], %4;\n" \
                "@pw bra.uni GO_%=;\n" \
                "add.u32 it, it, 1;\nsetp.lt.u32 pw, it, 0x10000;\n" \
                "@pw bra.uni WAIT_%=;\n" \
                "trap;\n" \
                "GO_%=:\n"
#define OP_ARGS "r"(arr), "r"(j), "r"(x & (1 << 12)), "r"((x >> 21) & 0x3f8), "r"(x >> 31), "r"(((x >> 15) & 0x1f8) | bars), "r"(bytes), "r"((x & 0x3e000) | sb), \
                "l"(dsc(mhi, mlo + (WEIGHTS ? (x & 0x38) * 16 : x & 0x180))), "n"(BARS), "r"(x & (WEIGHTS ? 0xfc0 : 63)), "r"(x & (WEIGHTS ? 7 : 64))
      if (WEIGHTS)
        asm volatile(OP_WAIT("")
                     "@pn cp.async.bulk.tensor.4d.shared::cluster.global.mbarrier::complete_tx::bytes.L2::cache_hint [%7], [%8, {%12, %10, %13, %11}], [%5], %14;\n"
                     "@pa mbarrier.arrive.expect_tx.shared::cta.b64 _, [%5], %6;\n"
                     "}\n" ::OP_ARGS, "r"(c * 64), "r"(zero), "l"(pol) : "memory");
      else
        asm volatile(OP_WAIT(".reg .pred pf;\nsetp.ne.u32 pf, %11, 0;\nsetp.eq.u32 ps, %14, %1;\n")
                     "@pn cp.async.bulk.tensor.4d.shared::cluster.global.mbarrier::complete_tx::bytes [%7], [%8, {%17, %12, %10, %13}], [%5];\n"
                     "@pf fence.proxy.async.shared::cta;\n"
                     "@pa mbarrier.arrive.expect_tx.shared::cta.b64 _, [%5], %6;\n"
                     "@ps mbarrier.arrive.shared::cta.b64 _, [%15 + %16];\n"
                     "}\n" ::OP_ARGS, "r"(row), "r"(par), "r"(solo), "r"(eb), "n"(bar(B_EMPTY)), "r"(zero) : "memory");
    }
  }
}

template <int N, uint32_t LO> __device__ __forceinline__ void advance(uint32_t& x, uint32_t inc) {
  constexpr uint32_t LEN = (N == 192 ? NU : 24) * 512;
  x += inc; if (x >= LO + LEN) x -= LEN;
}
__device__ __forceinline__ bool full_test(uint32_t i8) {
  uint32_t ok;
  asm volatile("{\n.reg .pred p;\nmbarrier.test_wait.parity.shared::cta.b64 p, [%1 + %3], %2;\nselp.u32 %0, 1, 0, p;\n}\n" : "=r"(ok) : "r"(i8 & 0x78), "r"(i8 >> 7), "n"(bar(B_FULL)) : "memory");
  return ok;
}
__device__ __forceinline__ void full_wait(uint32_t i8) { mbar_wait(bar(B_FULL) + (i8 & 0x78), i8 >> 7); }
__device__ __forceinline__ void release(uint32_t i8, uint32_t p) {
  asm volatile("{\n.reg .pred q;\nsetp.ne.u32 q, %1, 0;\n@q mbarrier.arrive.shared::cta.b64 _, [%0 + %2];\n}\n" ::"r"(i8 & 0x78), "r"(p), "n"(bar(B_EMPTY)) : "memory");
}
template <int N, int RELK, int FIRSTK>
__device__ __forceinline__ bool kstep(float (&acc)[2][N / 2], uint32_t hiA, uint32_t hiB, uint32_t& a, uint32_t& b, uint32_t inc, uint32_t& i8, uint32_t x) {
  constexpr uint32_t MI = N == 192 ? 64 : 512;
  wgmma_fence();
  if (FIRSTK == 2) { wgmma_z(acc[0], dsc(hiA, a), dsc(hiB, b)); wgmma_z(acc[1], dsc(hiA, a + MI), dsc(hiB, b)); }
  else { wgmma(acc[0], dsc(hiA, a), dsc(hiB, b)); wgmma(acc[1], dsc(hiA, a + MI), dsc(hiB, b)); }
  i8 += 8;
  const bool ok = full_test(i8);
#pragma unroll
  for (int k = 1; k < 4; k++) {
    wgmma(acc[0], dsc(hiA, a + 2 * k), dsc(hiB, b + 128 * k)); wgmma(acc[1], dsc(hiA, a + MI + 2 * k), dsc(hiB, b + 128 * k));
    if (k == RELK || k == 3) wgmma_commit();
    if (k == 3) { advance<N, LO_A>(a, inc); advance<N, LO_B>(b, inc); }
    if (!FIRSTK && k == RELK) {
      wgmma_wait<1>();
      release(i8, x);
    }
  }
  return ok;
}
template <int MODE, int N, class F, class G>
__device__ __forceinline__ void mainloop(float (&acc)[2][N], uint32_t sig, int t, int wg, uint32_t& sp, F&& prepare, G&& first_half) {
  const uint32_t turn = bar(B_TURN) + 8 * (wg ^ 1);
  constexpr uint32_t hiA = MODE == 0 ? 0x40000080u : 0x40000040u, hiB = 0x40000040u;
  constexpr Seg S0 = GEN.s.seg[0];
  uint32_t i8 = S0.i8 & 0xffff, nxt = S0.end8 & 0xffff, a = S0.a, b = S0.b, inc = S0.end8 >> 16;
  if (MODE != 0 || t != 0) {
    if (MODE == 2 || (MODE == 0 ? t != 12 : t != 4 && t != 15)) mbar_wait(bar(B_TURN) + 8 * wg, (t - 1) >> 1);
    i8 = c_sched.seg[sp].i8 & 0xffff; nxt = c_sched.seg[sp].end8 & 0xffff; a = c_sched.seg[sp].a; b = c_sched.seg[sp].b; inc = c_sched.seg[sp].end8 >> 16;
  }
  uint32_t hiA_ = hiA, hiB_ = hiB;
  if (MODE == 2) { hiA_ = uni(hiA, lane_now()); hiB_ = uni(hiB, lane_now() * 2); }
  full_wait(i8);
  TL(t, 2);
  TS(i8, wg);
  bool ok = kstep<N * 2, 3, MODE == 2 ? 1 : 2>(acc, hiA_, hiB_, a, b, inc, i8, 0);
  if (MODE == 2 && (t == 2 || t == 13)) bar_sync(NB_OGO, 256);
#pragma unroll 1
  while (true) {
    uint32_t act;
    if (MODE != 2) { hiA_ = uni(hiA, lane_now()); hiB_ = uni(hiB, lane_now() * 2); }
#pragma unroll 1
    while (true) {
      if (!ok) full_wait(i8);
      TS(i8, wg);
      ok = kstep<N * 2, MODE == 1 ? 1 : 3, 0>(acc, hiA_, hiB_, a, b, inc, i8, sig);
      if (__builtin_expect(i8 == nxt, 0)) {
        act = c_sched.seg[sp++].i8 >> 16;
        if (MODE == 1) mbar_arrive_if(turn, sig & (act >> 1));
        if (act & (MODE == 0 ? A_END | A_DRAIN | A_SYNC : MODE == 1 ? A_END | A_DRAIN : A_END)) break;
        nxt = c_sched.seg[sp].end8 & 0xffff; a = c_sched.seg[sp].a; b = c_sched.seg[sp].b;
        if (MODE == 1) inc = c_sched.seg[sp].end8 >> 16;
      }
    }
    if (MODE == 2 || (act & A_END)) break;
    nxt = c_sched.seg[sp].end8 & 0xffff; a = c_sched.seg[sp].a; b = c_sched.seg[sp].b;
    if (MODE == 1) inc = c_sched.seg[sp].end8 >> 16;
    if (MODE == 0 && (act & A_SYNC)) bar_arrive(NB_PX, 256);
    wgmma_wait<0>();
    release(i8 + 8, sig);
    i8 = c_sched.seg[sp].i8 & 0xffff;
    if (MODE == 1 || (act & A_WAIT)) mbar_wait(bar(B_TURN) + 8 * wg, (t - 1) >> 1);
    full_wait(i8);
    if (MODE == 0 && (act & A_SYNC)) bar_sync(NB_PY, 256);
    TS(i8, wg);
    ok = kstep<N * 2, 3, 1>(acc, hiA, hiB, a, b, inc, i8, 0);
  }
  if (MODE != 1) {
    constexpr int TL_ = MODE == 0 ? TAILQ : TAIL;
    uint32_t ta[TL_], tb[TL_];
#pragma unroll
    for (int x = 0; x < TL_; x++) {
      full_wait(i8 + 8 * x);
      TS(i8 + 8 * x, wg);
      ta[x] = a; tb[x] = b;
      advance<N * 2, LO_A>(a, inc); advance<N * 2, LO_B>(b, inc);
    }
#pragma unroll
    for (int h = 0; h < 2; h++) {
      const int mi = MODE == 0 ? 1 - h : h;
      wgmma_fence();
#pragma unroll
      for (int x = 0; x < TL_; x++)
#pragma unroll
        for (int k = 0; k < 4; k++) wgmma(acc[mi], dsc(hiA, ta[x] + mi * (MODE == 0 ? 64 : 512) + 2 * k), dsc(hiB, tb[x] + 128 * k));
      wgmma_commit();
      if (TL_ > 1 && h == 0) { wgmma_wait<1>(); release(i8 + 8, sig); prepare(); }
    }
    mbar_arrive_if(turn, sig);
    if (TL_ == 1) { wgmma_wait<2>(); release(i8 + 8, sig); prepare(); }
    wgmma_wait<1>();
    first_half();
    wgmma_wait<0>();
#pragma unroll
    for (int x = 0; x < TL_; x++) release(i8 + 16 + 8 * x, sig);
  } else {
    prepare();
    wgmma_wait<0>();
    release(i8 + 8, sig);
  }
}

template <int SWAP, int BY_SM>
__global__ void __launch_bounds__(384, 1) fused_kernel(Scratch* sc, const Ops* ops, const bf16* x0, bf16* out, const __grid_constant__ Params P) {
  extern __shared__ __align__(1024) uint8_t smem_raw[];
  const int tid = threadIdx.x;
  if (tid == 0) prefetch_tmap(&P.tm[M_X0]);
  if (tid == 128) prefetch_tmap(&P.tm[M_WQKV]);
  if (tid == 256) { mbar_init(bar(B_FULL), 2); fence_bar_init(); fence_proxy_async_smem(); }
  const int wg = __shfl_sync(0xffffffffu, tid >> 7, 0);
  const int w = __shfl_sync(0xffffffffu, (tid >> 5) & 3, 0);
  const int lane = tid & 31;
  const uint32_t t_entry = clock_now();
  int b = blockIdx.x;
  if (BY_SM) {
    uint32_t smid; asm volatile("mov.u32 %0, %%smid;" : "=r"(smid));
    const int tp = smid >> 1;
    const int q7 = (tp - 32) * 37 >> 8;
    const int v0 = (tp & 7) * 8 + (tp >> 3), v1 = tp * 8 - 244 - q7 * 55, v2 = tp < 62 ? tp + 4 : tp - 58;
    b = (tp < 32 ? v0 : tp < 60 ? v1 : v2) * 2 + (smid & 1);
  }
  const int mg = (b >> 5) & 3, m = mg * 4 + (b & 3);
  const int c = ((b >> 2) & 7) ^ (BY_SM ? 0 : (mg & 1) * 7);
  const int row0 = (m & 7) * 128, par = m >> 3;
  if (__builtin_expect(b >= NCTA, 0)) { helper_cta(P, sc, b - NCTA, wg, w); return; }
  if (wg == 2 && w == 0) {
    if (elect_one()) {
      tma4d(SB, &P.tm[M_X0], 0, row0, 0, par, bar(B_FULL));
      tma4d(SB + 16384, &P.tm[M_WQKV], c * 64, 0, 0, 0, bar(B_FULL));
      mbar_expect_tx(bar(B_FULL), 40960);
      mbar_arrive(bar(B_FULL));
    }
    __syncwarp();
    TLW(0, 1);
  } else {
    const int g = wg * 4 + w - (wg == 2);
    if (elect_one()) {
#pragma unroll
      for (int x = 1; x < 10; x++) mbar_init(bar(x) + g * 72, g < 4 ? 2 : g == 4 ? 4 : 1);
      fence_bar_init();
      fence_proxy_async_smem();
    }
    __syncwarp();
  }
  if (__builtin_expect(wg == 2, 0)) {
    reg_dealloc<40>();
    if (w < 2) {
      if (w == 0) producer<false>(P, ops->a, NOP0, lane, c, row0, par, t_entry);
      else producer<true>(P, ops->b, NOP1, lane, c, row0, par, t_entry);
    } else if (w == 2) {
      if (smem_u32(smem_raw) != SB) __trap();
      __syncthreads();
      const uint32_t tag = ld_epoch(sc->epoch + b);
      uint32_t* const flag = sc->flags[m * 8 + c];
      if (lane < 4) asm volatile("st.relaxed.gpu.global.v4.u32 [%0], {%1, %1, %1, %1};" ::"l"(flag + lane * 4), "r"(tag * 32 - 1) : "memory");
      __syncwarp();
      int ev = 0;
      uint32_t t_st = t_entry;
#pragma unroll 1
      for (int t = 0; t < 21; t++) {
        const int i = t >= 11 ? t - 11 : t;
        const bool od = i == 2 || i == 10;
        const uint32_t sig = c_sched.task[t].sig;
        const uint32_t pf = i == 0 ? 1 << M_OL | 1 << M_O | 1 << M_WO : i == 1 ? 1 << M_O24 | 1 << M_W13 | 1 << M_W13P | 1 << M_YL | 1 << M_Y : i == 3 ? 1 << M_HL :
                            i == 7 ? 1 << M_H | 1 << M_W2 : i == 10 ? 1 << M_WQKV | 1 << M_YL | 1 << M_Y : 0;
        if ((pf >> lane) & 1) prefetch_tmap(&P.tm[lane]);
        __syncwarp();
        if (od) {
          asm volatile("{\n.reg .pred pe, pw;\n.reg .u32 it;\nsetp.eq.u32 pe, %4, 1;\nmov.u32 it, 0;\n"
                       "WAIT_%=:\nmbarrier.try_wait.parity.shared::cta.b64 pw, [%0], %1;\n@pw bra.uni GO_%=;\n"
                       "add.u32 it, it, 1;\nsetp.lt.u32 pw, it, 0x10000;\n@pw bra.uni WAIT_%=;\ntrap;\n"
                       "GO_%=:\nfence.proxy.async.global;\nfence.acq_rel.gpu;\n"
                       "@pe red.relaxed.gpu.global.add.u32 [%2], %4;\n@pe mbarrier.arrive.shared::cta.b64 _, [%3];\n}\n"
                       ::"r"(bar(B_SIG + 1)), "r"(sig >> 1), "l"(&sc->cnt[mg][ev] + lane), "r"(bar(B_PUB) + 8 * ev), "r"(lane + 1) : "memory");
          ev++;
          TLW(t, 4);
        }
        if (i == 1) {
          mbar_wait(bar(B_SIG), sig);
          fence_proxy_async_smem();
#pragma unroll 1
          for (int r = 8; r < 128; r += 32) tma4d_store(&P.tm[M_O24], SM_STG + r * 128, row0 + r, 8 + c, par);
        } else {
          const CUtensorMap* mp = &P.tm[i == 0 ? M_OL : od ? M_YL : M_HL];
          const uint32_t src = od ? SB + ((c_sched.task[t].stg >> 8) & 31) * 8192 : SM_STG;
          const int blk = (od ? 1 : i ? i - 3 : 0) * 8 + c, gap = i == 0 ? GAP_O : od ? GAP_Y : i == 9 ? GAP_H6 : GAP_H;
          const int nr = i && !od ? 64 : 128;
#pragma unroll 1
          for (int r0 = 0; r0 < 128; r0 += nr) {
            const int s = od ? 3 : i ? r0 >> 6 : 1;
            mbar_wait(bar(B_SIG) + 8 * s, sig >> s);
            if (od) mbar_wait(bar(B_DEP - 1) + 8 * ev, 0);
            fence_proxy_async_smem();
            const uint32_t now = clock_now();
            if ((int)(now - t_st) > 0) t_st = now;
#pragma unroll 1
            for (int r = r0; r < r0 + nr; r += PROWS) {
              delay_until(t_st, 0);
              t_st += gap;
              tma4d_store(mp, src + r * 128, row0 + r, blk, par);
            }
          }
        }
        if (elect_one()) { bulk_commit(); bulk_wait(); }
        __syncwarp();
        if (i == 1) mbar_wait(bar(B_SIG + 1), sig >> 1);
        if (elect_one()) {
          mbar_arrive(od ? bar(B_SF) : bar(B_FREE));
          if (i < 3 || i > 6) {
            asm volatile("fence.proxy.async.global;" ::: "memory");
            st_release(flag, tag * 32 + ev);
            mbar_arrive(bar(B_PUB) + 8 * ev);
          }
        }
        __syncwarp();
        if (i < 3 || i > 6) ev++;
        if (!od) TLW(t, 4);
      }
      if (lane == 0) sc->epoch[b] = tag;
    } else {
      __syncthreads();
      const uint32_t tag = ld_epoch(sc->epoch + b);
      delay_until(t_entry, WARM_T);
      asm volatile("st.shared.u32 [%0], %1;" ::"r"(SM_TAG + 4), "r"(reinterpret_cast<const uint32_t*>(&c_sched)[min(lane * 16, (int)sizeof(Sched) / 4 - 1)]) : "memory");
      int ncs = 0;
#pragma unroll 1
      for (int it = 0; it < 20; it++) {
        const int l = it >= 11, i = it - l * 11, e = i < 2 ? 0 : i - 2, ev = l * E_N + e;
#pragma unroll 1
        for (; ncs < (it < 2 ? it + 1 : it < 6 ? 2 : 9); ncs++) {
          uint4 v[2];
          ld_tag_wait<200>(v, &sc->cs[ncs][c][lane], tag);
          const uint32_t a = SM_CS + (ncs < 2 ? ncs * 768 : 512 + ncs * 512) + ((lane & 17) | (lane & 6) << 1 | (lane & 8) >> 2) * 4;
#pragma unroll
          for (int j = 0; j < 2; j++) {
            sts4f(a + j * 128, __uint_as_float(v[j].x)); sts4f(a + j * 128 + 256, __uint_as_float(v[j].y));
            if (ncs < 2) sts4f(a + j * 128 + 512, __uint_as_float(v[j].z));
          }
          mbar_arrive_warp(bar(B_CS) + 8 * ncs);
        }
        if (i == 0 || i == 2) {
          const int u = l * 2 + (i >> 1);
          uint4 v[6] = {};
          mbar_wait(bar(B_QT), u);
          if (m & 7) ld_tag_wait<0>(v, &sc->halo[u][m - 1][c][0][lane], tag);
          const uint32_t xa = xch(i, 0) + lane * 16;
          sts16(xa, v[0].x, v[0].y, v[0].z, v[1].x); sts16(xa + 512, v[1].y, v[1].z, v[2].x, v[2].y);
          sts16(xa + 1024, v[2].z, v[3].x, v[3].y, v[3].z); sts16(xa + 1536, v[4].x, v[4].y, v[4].z, v[5].x);
          if (lane < 4) sts16(stat(l * 2) - 64 + lane * 16, v[5].y, 0, v[5].z, 0);
          mbar_arrive_warp(bar(B_XCH));
          continue;
        }
        const bool all = e == E_YA || e == E_XA;
        const uint32_t* fp = all ? &sc->cnt[mg][ev] : sc->flags[m * 8 + (lane & 7)];
        uint32_t want = tag * 32 + (all ? 0 : ev);
        asm volatile("" : "+l"(fp), "+r"(want));
        mbar_wait(bar(B_PUB) + 8 * ev, 0);
        wait_flags(fp, want);
        mbar_arrive_warp(bar(B_DEP) + 8 * ev);
        if (e == E_YB || e == E_XB) {
          const int p = e == E_XB ? 1 : l * 2;
          if (elect_one()) {
            mbar_expect_tx(bar(B_SF + 1), 8192);
            asm volatile("cp.async.bulk.shared::cluster.global.mbarrier::complete_tx::bytes [%0], [%1], 8192, [%2];" ::"r"(SM_STG), "l"(&sc->stat[p][m][0][0]), "r"(bar(B_SF + 1)) : "memory");
          }
          __syncwarp();
          mbar_wait(bar(B_SF + 1), p);
#pragma unroll 1
          for (int h = 0; h < 2; h++) {
            float s0 = 0.f, q0 = 0.f, s1 = 0.f, q1 = 0.f;
#pragma unroll 4
            for (int j = 0; j < 8; j++) {
              float x0, x1, x2, x3;
              lds16f(SM_STG + j * 1024 + h * 512 + lane * 16, x0, x1, x2, x3);
              s0 += x0; q0 += x1; s1 += x2; q1 += x3;
            }
            const float2 r0 = ln_finish(s0, q0), r1 = ln_finish(s1, q1);
            sts16(stat(p + 1) + (h * 64 + lane * 2) * 8, __float_as_uint(r0.x), __float_as_uint(r0.y), __float_as_uint(r1.x), __float_as_uint(r1.y));
          }
          mbar_arrive_warp(bar(B_STAT) + 8 * (p + 1));
        }
      }
    }
  } else {
    const int tw = tid & 127;
    reg_alloc<232>();
    uint32_t sig;
    asm volatile("mov.u32 %0, %1;" : "=r"(sig) : "r"((uint32_t)(tw == 0)));
    __syncthreads();

    if (wg == 1) {
      const uint32_t tag = ld_epoch(sc->epoch + b);
      uint4* const mine = &sc->stat0[m][c * 16 + w * 4 + (lane >> 3)];
      if ((lane & 7) == 0) st_tag(mine, 0, 0, 0, 0);
      __syncwarp();
      delay_until(t_entry, ST_ROWS);
      const bf16* xr = x0 + (size_t)((row0 + c * 16 + w * 4 + (lane >> 3)) * 2 + par) * D_ + (lane & 7) * 8;
      float sum = 0.f, sq = 0.f;
#pragma unroll 1
      for (int j0 = 0; j0 < 16; j0 += 4) {
        uint4 xv[4];
#pragma unroll
        for (int j = 0; j < 4; j++) xv[j] = ldcg16(xr + (j0 + j) * 64);
#pragma unroll
        for (int j = 0; j < 4; j++) {
          const uint32_t x[4] = {xv[j].x, xv[j].y, xv[j].z, xv[j].w};
#pragma unroll
          for (int e = 0; e < 8; e++) { const float d = e & 1 ? bf_hi(x[e >> 1]) : bf_lo(x[e >> 1]); sum += d; sq = fmaf(d, d, sq); }
        }
      }
#pragma unroll
      for (int o = 4; o > 0; o >>= 1) { sum += __shfl_xor_sync(0xffffffffu, sum, o); sq += __shfl_xor_sync(0xffffffffu, sq, o); }
      const float2 fin = ln_finish(sum, sq);
      if ((lane & 7) == 0) st_tag(mine, __float_as_uint(fin.x), __float_as_uint(fin.y), 0, tag);
      __syncwarp();
      TL(22, 5);
      uint4 v[1];
      ld_tag_wait<200>(v, &sc->stat0[m][tw], tag);
      sts8f(stat(0) + tw * 8, __uint_as_float(v[0].x), __uint_as_float(v[0].y));
      if (tw == 0) { asm volatile("st.shared.u32 [%0], %1;" ::"r"(SM_TAG), "r"(tag) : "memory"); sts16(SM_ZERO, 0, 0, 0, 0); }
      mbar_arrive_warp(bar(B_STAT));
      TL(22, 6);
    }

    uint32_t sp = wg * NSEG;
#pragma unroll 1
    for (int t = wg; t < 22; t += 2) {
      const int l = t >= 11, i = t - l * 11;
      if (t == 0) TL(t, 0);
      if (i < 2) {
        float acc[2][96];
        if (w == 3 && (m & 7) < 7) {
#pragma unroll
          for (int j = 0; j < 6; j++) st_tag(&sc->halo[l * 2 + i][m][c][j][lane_now()], 0, 0, 0, 0);
        }
        uint32_t Q[4][8], K[4][8], V[4][8], sta, csa;
        float2 st[4];
        auto fix = [&](int g, int j, float2 cs) {
          const int mi = g & 1, half = g >> 1;
          return pack_bf16_v(fmaf(st[g].y, cs.x, acc[mi][j * 4 + half * 2]), fmaf(st[g].y, cs.y, acc[mi][j * 4 + half * 2 + 1]));
        };
        mainloop<0>(acc, sig, t, wg, sp, [&]() {
          const int lane = lane_now();
          mbar_wait(bar(B_FREE), l * 9 + i - 1);
          mbar_wait(bar(B_STAT) + l * 16, 0);
          mbar_wait(bar(B_CS) + i * 8, 0);
          sta = stat(l * 2) + w * 256;
          csa = SM_CS + i * 768 + (lane & 3) * 16;
          st[1] = lds8f(sta + (8 + (lane >> 2)) * 8); st[3] = lds8f(sta + (24 + (lane >> 2)) * 8);
        }, [&]() {
          const int lane = lane_now();
          mbar_arrive_if(bar(B_QT), sig);
#pragma unroll
          for (int j = 0; j < 8; j += 2) {
            float2 c0, c1;
            lds16f(csa + (16 + j) * 32, c0.x, c0.y, c1.x, c1.y);
            V[3][j] = movmat(fix(3, 16 + j, c0)); V[3][j + 1] = movmat(fix(3, 17 + j, c1));
            lds16f(csa + (8 + j) * 32, c0.x, c0.y, c1.x, c1.y);
            K[3][j] = fix(3, 8 + j, c0); K[3][j + 1] = fix(3, 9 + j, c1);
          }
          if (w < 3) {
            const uint32_t xa = xch(i, w + 1) + lane * 16;
            sts16(xa, K[3][0], K[3][1], K[3][2], K[3][3]); sts16(xa + 512, K[3][4], K[3][5], K[3][6], K[3][7]);
            sts16(xa + 1024, V[3][0], V[3][1], V[3][2], V[3][3]); sts16(xa + 1536, V[3][4], V[3][5], V[3][6], V[3][7]);
            mbar_arrive_warp(bar(B_XCH));
          } else if ((m & 7) < 7) {
            const uint32_t tag = lds4(SM_TAG), r0 = lds4(sta + (24 + 2 * (lane & 3)) * 8), r1 = lds4(sta + (25 + 2 * (lane & 3)) * 8);
            uint4* const p = &sc->halo[l * 2 + i][m][c][0][lane];
            st_tag(p, K[3][0], K[3][1], K[3][2], tag); st_tag(p + 32, K[3][3], K[3][4], K[3][5], tag); st_tag(p + 64, K[3][6], K[3][7], V[3][0], tag);
            st_tag(p + 96, V[3][1], V[3][2], V[3][3], tag); st_tag(p + 128, V[3][4], V[3][5], V[3][6], tag); st_tag(p + 160, V[3][7], r0, r1, tag);
          }
        });
        TL(t, 3);
        const int lane = lane_now(), q = lane & 3, r8 = lane >> 2;
        st[0] = lds8f(sta + r8 * 8); st[2] = lds8f(sta + (16 + r8) * 8);
#pragma unroll
        for (int j0 = 22; j0 >= 0; j0 -= 2) {
          float2 cs[2];
          lds16f(csa + j0 * 32, cs[0].x, cs[0].y, cs[1].x, cs[1].y);
#pragma unroll
          for (int j = j0; j < j0 + 2; j++)
#pragma unroll
            for (int g = 0; g < (j < 8 ? 4 : 3); g++) {
              const uint32_t pk = fix(g, j, cs[j - j0]);
              if (j < 8) Q[g][j] = pk; else if (j < 16) K[g][j - 8] = pk; else V[g][j - 16] = movmat(pk);
            }
        }
        const bool up0 = (2 * q) > r8, up1 = (2 * q + 1) > r8;
        const uint32_t mskP = (up0 ? 0xffffu : 0u) | (up1 ? 0xffff0000u : 0u);
        uint32_t ka0 = sta + q * 16 - (up0 ? 64 : 0), ka1 = sta + q * 16 + (up1 ? -56 : 8);
        asm volatile("" : "+r"(ka0), "+r"(ka1));
        TL(t, 5);
        uint32_t Kp[8] = {}, Vp[8] = {}, PS[2][4] = {}, PP[2][4] = {};
        float sS[2][4][2], sP[2][4][2] = {}, O[2][4][4][2], z0, z1, z2, z3;
        auto receive = [&]() {
          const uint32_t xa = xch(i, w) + lane * 16;
          mbar_wait(bar(B_XCH), i);
          lds16(xa, Kp[0], Kp[1], Kp[2], Kp[3]); lds16(xa + 512, Kp[4], Kp[5], Kp[6], Kp[7]);
          lds16(xa + 1024, Vp[0], Vp[1], Vp[2], Vp[3]); lds16(xa + 1536, Vp[4], Vp[5], Vp[6], Vp[7]);
          TL(i == 0 ? 22 : 23, t < 11 ? 3 : 4);
        };
        auto score = [&](float& s0, float& s1, float& s2, float& s3, int g, const uint32_t (&k)[8], int j, bool first) {
          mma16816(s0, s1, s2, s3, Q[g][j], Q[g + 1][j], Q[g][j + 1], Q[g + 1][j + 1], k[j], k[j + 1], first ? z0 : s0, first ? z1 : s1, first ? z2 : s2, first ? z3 : s3);
        };
        auto score0 = [&]() {
          float d[2][2];
#pragma unroll
          for (int x = 0; x < 4; x++) score(sP[x & 1][0][0], sP[x & 1][0][1], d[x & 1][0], d[x & 1][1], 0, Kp, (x & 1) * 4 + (x & 2), x < 2);
        };
        auto softmax = [&](int g) {
          const float rk0 = lds4f(ka0 + g * 64), rk1 = lds4f(ka1 + g * 64);
          const float f = st[g].x * (0.17677669529663687f * LOG2E), f0 = f * rk0, f1 = f * rk1;
          const bool noprev = g == 0 && (m & 7) == 0 && w == 0;
#pragma unroll
          for (int h = 0; h < 2; h++) {
            float v0 = (up0 ? sP[h][g][0] : sS[h][g][0]) * f0, v1 = (up1 ? sP[h][g][1] : sS[h][g][1]) * f1;
            if (noprev && up0) v0 = -1e9f * LOG2E;
            if (noprev && up1) v1 = -1e9f * LOG2E;
            float mx = fmaxf(v0, v1);
            mx = fmaxf(mx, __shfl_xor_sync(0xffffffffu, mx, 1)); mx = fmaxf(mx, __shfl_xor_sync(0xffffffffu, mx, 2));
            const float e0 = ex2f(v0 - mx), e1 = ex2f(v1 - mx);
            float sum = e0 + e1;
            sum += __shfl_xor_sync(0xffffffffu, sum, 1); sum += __shfl_xor_sync(0xffffffffu, sum, 2);
            const float inv = rcpf(sum);
            const uint32_t pk = pack_bf16_v(e0 * rk0 * inv, e1 * rk1 * inv);
            PS[h][g] = pk & ~mskP; PP[h][g] = pk & mskP;
          }
        };
        const uint32_t sa = SM_STG + (w * 32 + (lane & 7)) * 128 + (((lane >> 3) ^ (lane & 7)) << 4);
        auto stage = [&](int g) {
#pragma unroll
          for (int h = 0; h < 2; h++)
            stsm4t((sa ^ (h * 64)) + g * 1024, pack_bf16_v(O[h][g][0][0], O[h][g][0][1]), pack_bf16_v(O[h][g][1][0], O[h][g][1][1]),
                  pack_bf16_v(O[h][g][2][0], O[h][g][2][1]), pack_bf16_v(O[h][g][3][0], O[h][g][3][1]));
        };
        if (i == 0) { receive(); bar_sync(NB_PX, 256); }
        lds16f(SM_ZERO, z0, z1, z2, z3);
        if (i == 0) score0();
        {
          float d[2][2];
#pragma unroll
          for (int x = 0; x < 4; x++) {
            const int h = x & 1, j = h * 4 + (x & 2);
#pragma unroll
            for (int g = 0; g < 3; g++) score(sS[h][g][0], sS[h][g][1], sP[h][g + 1][0], sP[h][g + 1][1], g, K[g], j, x < 2);
            score(d[h][0], d[h][1], sS[h][3][0], sS[h][3][1], 2, K[3], j, x < 2);
          }
        }
        if (i == 0) { bar_arrive(NB_PY, 256); softmax(0); }
#pragma unroll
        for (int g = 1; g < 4; g++) softmax(g);
        TL(23, i == 0 ? (t < 11 ? 5 : 6) : 7);
        if (i == 0) bar_sync(NB_PX + ((PS[0][1] | PS[0][2] | PS[0][3] | PS[1][1] | PS[1][2] | PS[1][3]) & __float_as_uint(z0)), 256);
        lds16f(SM_ZERO, z0, z1, z2, z3);
        auto pv = [&](int g, const uint32_t (&vp)[8]) {
#pragma unroll
          for (int x = 0; x < 8; x += 2) {
            const int h = x >> 2, j = x & 3;
            mma16816(O[h][g][j][0], O[h][g][j][1], O[h][g][j + 1][0], O[h][g][j + 1][1], vp[x], vp[x + 1], V[g][x], V[g][x + 1], PP[h][g], PS[h][g], z0, z1, z2, z3);
          }
        };
        pv(1, V[0]); pv(3, V[2]); pv(2, V[1]);
        if (i) {
          stage(1); stage(2); stage(3);
          mbar_arrive_warp(bar(B_SIG));
          receive(); score0(); softmax(0);
        }
        pv(0, Vp);
        if (i == 0) { bar_arrive(NB_PY, 256); stage(1); stage(2); stage(3); stage(0); }
        else { stage(0); copy_out<2>(SM_STG + w * 4096, sc->o, par * (S_ * D_) + (row0 + w * 32) * 128 + (8 + c) * PANEL, 128, lane); }
        mbar_arrive_warp(bar(B_SIG + 1));
        if (i) bar_arrive(NB_OGO, 256);
        TL(t, 6);
      } else if (i > 2 && i < 10) {
        float acc[2][64];
        float2 cs[16];
        float hr[4];
        uint32_t so, sta;
        mainloop<1>(acc, sig, t, wg, sp, [&]() {
          const int lane = lane_now();
          so = SM_STG + (w * 16 + (lane & 7)) * 128 + (((lane >> 3) ^ (lane & 7)) << 4);
          sta = stat(l * 2 + 1) + (w * 16 + (lane >> 2)) * 8;
          mbar_wait(bar(B_STAT + 1) + l * 16, 0);
          mbar_wait(bar(B_CS - 1) + 8 * i, 0);
#pragma unroll
          for (int j = 0; j < 16; j += 2) lds16f(SM_CS + i * 512 + (lane & 3) * 16 + j * 32, cs[j].x, cs[j].y, cs[j + 1].x, cs[j + 1].y);
#pragma unroll
          for (int j = 0; j < 4; j++) hr[j] = 0.5f * lds4f(sta + (j >> 1) * 512 + (j & 1) * 64);
          mbar_wait(bar(B_FREE), l * 9 + i - 2);
        }, []() {});
        TL(t, 3);
        float mn[8];
#pragma unroll
        for (int x = 0; x < 2; x++) mn[x] = __uint_as_float(lds4(sta + 4 + (x >> 2) * 512 + ((x >> 1) & 1) * 64));
#pragma unroll
        for (int x = 0; x < 8; x++) {
          const int mi = x >> 2, half = (x >> 1) & 1, g = x & 1;
          uint32_t v[4];
#pragma unroll
          for (int j = 0; j < 4; j++) {
            const int jg = g * 4 + j + SWAP * 8, ju = jg ^ 8;
            const float2 cg = cs[jg], cu = cs[ju];
            const float g0 = fmaf(mn[x], cg.x, acc[mi][jg * 4 + half * 2]), g1 = fmaf(mn[x], cg.y, acc[mi][jg * 4 + half * 2 + 1]);
            const float u0 = fmaf(mn[x], cu.x, acc[mi][ju * 4 + half * 2]), u1 = fmaf(mn[x], cu.y, acc[mi][ju * 4 + half * 2 + 1]);
            const float a0 = g0 * hr[x >> 1], a1 = g1 * hr[x >> 1];
            v[j] = pack_bf16(fmaf(a0, tanhf_(a0), a0) * u0, fmaf(a1, tanhf_(a1), a1) * u1);
          }
          stsm4((so ^ (g * 64)) + (mi * 64 + half * 8) * 128, v[0], v[1], v[2], v[3]);
          if ((x & 3) == 3) mbar_arrive_warp(bar(B_SIG + mi));
          if (x + 2 < 8) mn[x + 2] = __uint_as_float(lds4(sta + 4 + ((x + 2) >> 2) * 512 + (((x + 2) >> 1) & 1) * 64));
        }
        TL(t, 6);
      } else {
        float acc[2][64], rsc[4];
        {
          const int lane = lane_now();
          const uint32_t e = c_sched.task[t].res;
          const uint32_t ra = SB + (w * 16 + (lane & 7)) * 128 + (((lane >> 3) ^ (lane & 7)) << 4);
          float sd[4];
#pragma unroll
          for (int j = 0; j < 4; j++) {
            rsc[j] = i == 10 ? lds4f(stat(l * 2 + 1) + ((j >> 1) * 64 + w * 16 + (j & 1) * 8 + (lane >> 2)) * 8) : 1.f;
            sd[j] = rcpf(rsc[j]);
          }
          const uint32_t zero = lds4(SM_ZERO);
          mbar_wait(bar(B_RES), i == 10);
          uint32_t dep[16];
#pragma unroll
          for (int x = 0; x < 16; x++) {
            const int mi = x >> 3, half = (x >> 2) & 1, g = x & 3;
            uint32_t v[4];
            ldsm4(((e >> ((g >> 1) * 8)) & 31) * 8192 + ((ra ^ ((g & 1) * 64)) | (x ? dep[x - 1] : 0)) + (mi * 64 + half * 8) * 128, v[0], v[1], v[2], v[3]);
#pragma unroll
            for (int j = 0; j < 4; j++) {
              asm volatile("shl.b32 %0, %1, 16;" : "=f"(acc[mi][(g * 4 + j) * 4 + half * 2]) : "r"(v[j]));
              asm volatile("and.b32 %0, %1, 0xffff0000;" : "=f"(acc[mi][(g * 4 + j) * 4 + half * 2 + 1]) : "r"(v[j]));
              { acc[mi][(g * 4 + j) * 4 + half * 2] *= sd[mi * 2 + half]; acc[mi][(g * 4 + j) * 4 + half * 2 + 1] *= sd[mi * 2 + half]; }
            }
            asm("and.b32 %0, %1, %2;" : "=r"(dep[x]) : "f"(acc[mi][(g * 4 + 3) * 4 + half * 2 + 1]), "r"(zero));
          }
          mbar_arrive_warp(bar(B_RF));
        }
        auto stage = [&](int mi, int hi) {
          const int lane = lane_now();
          const uint32_t sw = SB + ((c_sched.task[t].stg >> (8 * hi)) & 31) * 8192 + (mi * 64 + w * 16) * 128, so = sw + (lane & 7) * 128 + (((lane >> 3) ^ (lane & 7)) << 4);
#pragma unroll
          for (int half = 0; half < 2; half++)
#pragma unroll
            for (int g = 0; g < 2; g++) {
              uint32_t v[4];
#pragma unroll
              for (int j = 0; j < 4; j++) {
                acc[mi][(hi * 8 + g * 4 + j) * 4 + half * 2] *= rsc[mi * 2 + half]; acc[mi][(hi * 8 + g * 4 + j) * 4 + half * 2 + 1] *= rsc[mi * 2 + half];
                v[j] = pack_bf16(acc[mi][(hi * 8 + g * 4 + j) * 4 + half * 2], acc[mi][(hi * 8 + g * 4 + j) * 4 + half * 2 + 1]);
              }
              stsm4((so ^ (g * 64)) + half * 1024, v[0], v[1], v[2], v[3]);
            }
          if (mi && !hi) mbar_arrive_warp(bar(B_SIG));
          if (hi == 0 || t == 21) {
            const int pitch = t == 21 ? D_ * 4 : 128;
            copy_out<4>(sw, t == 21 ? out : sc->y, (row0 + mi * 64 + w * 16) * pitch + (t == 21 ? par * (D_ * 2) + (hi * 8 + c) * 128 : par * (S_ * D_) + c * PANEL), pitch, lane);
          }
        };
        mainloop<2>(acc, sig, t, wg, sp, []() {}, [&]() { stage(0, 0); stage(0, 1); });
        TL(t, 3);
        stage(1, 0); mbar_arrive_warp(bar(B_SIG + 1));
        TL(t, 6);
        stage(1, 1); mbar_arrive_warp(bar(B_SIG + 2));
        if (t < 21) {
          const int lane = lane_now(), q = lane & 3;
          const uint32_t zero = lds4(SM_ZERO);
          float s[4], s2[4];
#pragma unroll
          for (int x = 0; x < 4; x++) {
            float a0 = x ? __uint_as_float(__float_as_uint(s[x - 1]) & zero) : 0.f, b0 = x ? __uint_as_float(__float_as_uint(s2[x - 1]) & zero) : 0.f;
#pragma unroll
            for (int j = 0; j < 32; j++) { const float d = acc[x >> 1][(j >> 1) * 4 + (x & 1) * 2 + (j & 1)]; a0 += d; b0 = fmaf(d, d, b0); }
            s[x] = a0; s2[x] = b0;
          }
#pragma unroll
          for (int x = 0; x < 2; x++) {
            s[x] = (q & 2 ? s[x + 2] : s[x]) + __shfl_xor_sync(0xffffffffu, q & 2 ? s[x] : s[x + 2], 2);
            s2[x] = (q & 2 ? s2[x + 2] : s2[x]) + __shfl_xor_sync(0xffffffffu, q & 2 ? s2[x] : s2[x + 2], 2);
          }
          const float r = (q & 1 ? s[1] : s[0]) + __shfl_xor_sync(0xffffffffu, q & 1 ? s[0] : s[1], 1);
          const float r2 = (q & 1 ? s2[1] : s2[0]) + __shfl_xor_sync(0xffffffffu, q & 1 ? s2[0] : s2[1], 1);
          asm volatile("st.global.v2.f32 [%0], {%1, %2};" ::"l"(&sc->stat[i == 10 ? 1 : l * 2][m][c][(q >> 1) * 64 + w * 16 + (q & 1) * 8 + (lane >> 2)]), "f"(r), "f"(r2) : "memory");
          mbar_arrive_warp(bar(B_SIG + 3));
        }
      }
    }
  }
}

typedef CUresult (*PFN_encodeTiled)(CUtensorMap*, CUtensorMapDataType, cuuint32_t, void*, const cuuint64_t*, const cuuint64_t*, const cuuint32_t*,
                                    const cuuint32_t*, CUtensorMapInterleave, CUtensorMapSwizzle, CUtensorMapL2promotion, CUtensorMapFloatOOBfill);

void make_map(PFN_encodeTiled enc, CUtensorMap* mp, const void* ptr, int rank, const cuuint64_t* gd, const cuuint64_t* gs, const cuuint32_t* bd) {
  const cuuint32_t es[4] = {1, 1, 1, 1};
  enc(mp, CU_TENSOR_MAP_DATA_TYPE_BFLOAT16, rank, const_cast<void*>(ptr), gd, gs, bd, es, CU_TENSOR_MAP_INTERLEAVE_NONE, CU_TENSOR_MAP_SWIZZLE_128B,
      CU_TENSOR_MAP_L2_PROMOTION_L2_128B, CU_TENSOR_MAP_FLOAT_OOB_FILL_NONE);
}
void make_map_act(PFN_encodeTiled enc, CUtensorMap* mp, const void* ptr, uint64_t cols, uint64_t s1, uint64_t s2, uint64_t s3, uint32_t rows) {
  const cuuint64_t gd[4] = {64, S_ / 2, cols / 64, 2}, gs[3] = {s1, s2, s3};
  const cuuint32_t bd[4] = {64, rows, 1, 1};
  make_map(enc, mp, ptr, 4, gd, gs, bd);
}
void make_map_w(PFN_encodeTiled enc, CUtensorMap* mp, const void* ptr, uint64_t rows, uint64_t cols, uint32_t np, uint64_t sp, uint64_t tiles, uint32_t nt) {
  const cuuint64_t gd[4] = {512, rows, np, tiles}, gs[3] = {cols * 2, sp, 1024};
  const cuuint32_t bd[4] = {64, 64, np, nt};
  make_map(enc, mp, ptr, 4, gd, gs, bd);
}

}

extern "C" void kernel_launch(void* const* d_in, const int* in_sizes, int n_in, void* d_out, int out_size) {
  (void)in_sizes; (void)n_in; (void)out_size;
  static PFN_encodeTiled enc = nullptr;
  static void *p_sc, *p_ops, *p_w;
  static int by_sm = 0;
  void (*const kernels[4])(Scratch*, const Ops*, const bf16*, bf16*, Params) = {fused_kernel<0, 0>, fused_kernel<1, 0>, fused_kernel<0, 1>, fused_kernel<1, 1>};
  if (!enc) {
    void* fn = nullptr; cudaDriverEntryPointQueryResult qr;
    cudaGetDriverEntryPoint("cuTensorMapEncodeTiled", &fn, cudaEnableDefault, &qr);
    enc = (PFN_encodeTiled)fn;
    cudaGetSymbolAddress(&p_sc, g_sc); cudaGetSymbolAddress(&p_ops, g_ops); cudaGetSymbolAddress(&p_w, g_w13);
    for (int i = 0; i < 4; i++) cudaFuncSetAttribute(kernels[i], cudaFuncAttributeMaxDynamicSharedMemorySize, SM_TOTAL);
    int dev = 0, sms = 0;
    cudaGetDevice(&dev);
    cudaDeviceGetAttribute(&sms, cudaDevAttrMultiProcessorCount, dev);
    by_sm = sms == NCTA + NHELP;
    for (int i = 1; i < 4 && by_sm; i++) {
      cudaLaunchConfig_t cfg = {};
      cudaLaunchAttribute at;
      at.id = cudaLaunchAttributeClusterDimension; at.val.clusterDim.x = 1 << i; at.val.clusterDim.y = at.val.clusterDim.z = 1;
      cfg.gridDim = dim3(NCTA); cfg.blockDim = dim3(384); cfg.dynamicSmemBytes = SM_TOTAL; cfg.attrs = &at; cfg.numAttrs = 1;
      int n = 0;
      if (cudaOccupancyMaxActiveClusters(&n, kernels[0], &cfg) != cudaSuccess) { (void)cudaGetLastError(); n = 0; }
      by_sm = n == (i == 1 ? 66 : i == 2 ? 30 : 15);
    }
  }
  Params P;
  Scratch* const sc = (Scratch*)p_sc;
  make_map_act(enc, &P.tm[M_X0], d_in[0], D_, D_ * 4, 128, D_ * 2, 128);
  make_map_act(enc, &P.tm[M_O], sc->o, D_, 128, PANEL, S_ * D_, 128);
  make_map_act(enc, &P.tm[M_Y], sc->y, D_, 128, PANEL, S_ * D_, 128);
  make_map_act(enc, &P.tm[M_H], sc->h, F_, 128, PANEL, S_ * F_, 128);
  make_map_act(enc, &P.tm[M_OL], sc->o, D_, 128, PANEL, S_ * D_, PROWS);
  make_map_act(enc, &P.tm[M_YL], sc->y, D_, 128, PANEL, S_ * D_, PROWS);
  make_map_act(enc, &P.tm[M_HL], sc->h, F_, 128, PANEL, S_ * F_, PROWS);
  make_map_act(enc, &P.tm[M_O24], sc->o, D_, 128, PANEL, S_ * D_, 24);
  make_map_w(enc, &P.tm[M_WQKV], d_in[1], D_, 3 * D_, 3, D_ * 2, 2, 1);
  make_map_w(enc, &P.tm[M_WO], d_in[2], D_, D_, 2, 1024, 1, 1);
  make_map_w(enc, &P.tm[M_W2], d_in[6], F_, D_, 2, 1024, 1, 1);
  const char *w1 = (const char*)d_in[4], *w3 = (const char*)d_in[5];
  if ((uint64_t)(w1 < w3 ? w3 - w1 : w1 - w3) >> 39) {
    cudaMemcpyAsync(p_w, w1, (size_t)D_ * F_ * 2, cudaMemcpyDeviceToDevice);
    cudaMemcpyAsync((bf16*)p_w + D_ * F_, w3, (size_t)D_ * F_ * 2, cudaMemcpyDeviceToDevice);
    w1 = (const char*)p_w; w3 = w1 + (size_t)D_ * F_ * 2;
  }
  const bool swap = w3 < w1;
  make_map_w(enc, &P.tm[M_W13], swap ? w3 : w1, D_, F_, 2, swap ? w1 - w3 : w3 - w1, 7, 1);
  make_map_w(enc, &P.tm[M_W13P], swap ? w3 : w1, D_, F_, 2, swap ? w1 - w3 : w3 - w1, 7, 2);
  kernels[by_sm * 2 + swap]<<<NCTA + NHELP, 384, SM_TOTAL>>>(sc, (const Ops*)p_ops, (const bf16*)d_in[0], (bf16*)d_out, P);
}
```

```cpp
#include <cuda_runtime.h>
#include <cuda_bf16.h>
#include <cuda.h>
#include <stdint.h>
#include <stddef.h>

typedef __nv_bfloat16 bf16;
#define GU_E 3
#define G_N1 7
#define Q_P1 4
#define Q_P2 6
#define Q_P0 1
#define RES_O 3
#define RES_D 3
#define HOLD_O 6
#define PROWS 16
#define GAP_O 150
#define GAP_Y 100
#define GAP_H 350
#define GAP_H6 1000
#define ST_T1 600
#define ST_D1 700
#define ST_ROWS 3500
#define WARM_T 4000
constexpr int TAILQ = 1, TAIL = 2;

namespace {

constexpr int S_ = 2048, D_ = 1024, F_ = 3584;
constexpr int PANEL = S_ / 2 * 128;
constexpr int NCTA = 128;
constexpr int NHELP = 4;

constexpr uint32_t SB = 1024;
constexpr int NU = 25;
constexpr uint32_t SM_STG  = SB + NU * 8192;
__host__ __device__ constexpr uint32_t xch(int i, int w) { return i ? SM_STG - 8192 + w * 2048 : SM_STG + w * 4096; }
constexpr uint32_t BARS    = SM_STG + 16384;
constexpr uint32_t SM_STAT = BARS + 896;
__host__ __device__ constexpr uint32_t stat(int set) { return SM_STAT + set * 1088 + 64; }
constexpr uint32_t SM_CS   = SM_STAT + 4352;
constexpr uint32_t SM_END  = SM_CS + 5120;
constexpr int SM_TOTAL = SM_END - SB;
static_assert(BARS % 1024 == 0 && SM_TOTAL <= 232448, "smem");
constexpr int B_FULL = 0, B_EMPTY = 16, B_SIG = 37, B_XCH = 41, B_RF = 42, B_STAT = 45, B_TURN = 49, B_RES = 51, B_FREE = 52, B_SF = 53, B_QT = 55, B_PASS = 56,
              B_CS = 57, B_DEP = 66, B_PUB = 82, B_N = 100;
__host__ __device__ constexpr uint32_t bar(int i) { return BARS + 8 * i; }
constexpr uint32_t SM_TAG = BARS + 8 * B_N, SM_ZERO = SM_TAG + 16;
constexpr int NB_PX = 1, NB_PY = 2, NB_OGO = 3, NB_END = 4;

constexpr int E_O0 = 0, E_O1 = 1, E_YA = 2, E_YB = 3, E_H4 = 4, E_XA = 7, E_XB = 8, E_N = 9;

constexpr int M_X0 = 0, M_O = 1, M_Y = 2, M_H = 3;
constexpr int M_WQKV = 4, M_WO = 5, M_W13 = 6, M_W13P = 7, M_W2 = 8;
constexpr int M_OL = 9, M_YL = 10, M_HL = 11, M_O24 = 12, M_N = 13;

constexpr int FIRST = 5;
constexpr int NOPA = 416, NOPB = 416, NSEG = 40;
constexpr uint32_t A_END = 1, A_TURN = 2, A_DRAIN = 4, A_WAIT = 8, A_SYNC = 16;
constexpr uint32_t A_MARK = 0;
struct Task { uint32_t stg, res, sig; };
struct Seg { uint32_t i8, end8, a, b; };
constexpr uint32_t LO_A = 0x10000 + SB / 16, LO_B = 0x2000000 + SB / 16;
struct Sched { Seg seg[2 * NSEG]; Task task[22]; };
struct Ops { uint2 a[NOPA + 64], b[NOPB + 64]; };
struct Gen {
  Sched s{}; Ops o{};
  int n[2] = {0, 0}, nseg[2] = {0, NSEG}, cur = -1, pos = 0, err = 0, res = 0, nres = 0;
  int mask[400] = {}, sa[400] = {}, sb[400][2] = {}, own[NU][2] = {}, tok[NU] = {}, known[2][2] = {{-1, -1}, {-1, -1}};
  constexpr void emit(int p, int wait, int par, int dst, int map, int kb8, int arr, int load, int y) {
    if (cur < FIRST) return;
    const uint2 e{(uint32_t)((p ? y >> 10 | (load ? map - M_WQKV : 0) << 3 | (y & 63) << 6 : (y & 63) | (y >> 10) << 6 | map << 7) | load << 12 | dst << 13 | (res ? B_RES : B_FULL + (cur & 15)) << 18 | wait << 24) | (uint32_t)(par & 1) << 31,
                  (uint32_t)(((y >> 6) & 15) | arr << 4 | (!p && arr && mask[cur] != 3 && !res) << 5 | ((cur + 2) & 15) << 9 | kb8 << 13)};
    if (p) o.b[n[1]++] = e; else o.a[n[0]++] = e;
  }
  constexpr bool done(int p, int x) const { return x < 0 || ((!(mask[x] & 1) || known[p][0] >= x) && (!(mask[x] & 2) || known[p][1] >= x)); }
  constexpr void op(int p, int dst, int nu, int map, int kb8, int arr, int y, int xw = -1, int xp = 0) {
    int w[8] = {}, wp[8] = {}, nw = 0;
    if (xw >= 0) { w[nw] = xw; wp[nw++] = xp; }
    for (int u = dst; u < dst + nu; u++) if (tok[u] && (u == dst || tok[u] != tok[u - 1])) { w[nw] = (tok[u] - 1) >> 1; wp[nw++] = tok[u] - 1; }
    for (int x = cur - 1; x >= 0; x--) {
      bool need = x <= cur - 12;
      for (int u = dst; u < dst + nu; u++) need = need || own[u][0] == x + 1 || own[u][1] == x + 1;
      if (!need || done(p, x)) continue;
      if (cur - x >= 16 || !done(p, x - 16)) err |= 1;
      w[nw] = B_EMPTY + ((x + 2) & 15); wp[nw++] = x >> 4;
      for (int g = 0; g < 2; g++) if (((mask[x] >> g) & 1) && known[p][g] < x) known[p][g] = x;
    }
    for (; nw > 1; nw--) emit(p, w[nw - 1], wp[nw - 1], 0, 0, 0, 0, 0, 0);
    emit(p, nw ? w[0] : B_PASS, nw ? wp[0] : 1, dst, map, kb8, arr, nu > 0, y);
    for (int u = dst; u < dst + nu; u++) { own[u][0] = cur + 1; own[u][1] = 0; tok[u] = 0; }
  }
  constexpr int step(int m) { mask[++cur] = m; return cur; }
  constexpr int slot() { int u = (pos + 1) & ~1; if (u >= 24) u = 0; pos = u + 2; return u; }
  constexpr int qslot() { int u = (pos + 4) / 5 * 5; if (u >= NU) u = 0; pos = u + 5; return u; }
  constexpr void stage(int u, int first, int t) {
    first -= TAIL;
    for (int x = u; x < u + 2; x++) { if (own[x][0] > first || own[x][1] > first || tok[x]) err |= 2; own[x][0] = cur + 1; own[x][1] = 0; tok[x] = t; }
  }
  static constexpr int kown(int hi) { return hi * 8 | 1 << 9; }
  static constexpr int kskip(int hi, int j) { return (hi * 8 + j) | (j + 1) << 6; }
  static constexpr int kpos(int p) { return p < 2 ? kown(p) : p < 9 ? kskip(0, p - 2) : kskip(1, p - 9); }
  constexpr void segs(int t, const int* st, const uint32_t* act, int cnt, int tail, int inc0) {
    const int g = t & 1, wrap = inc0 == 5 ? NU : 24;
    int j0 = 0;
    for (int j = 0; j < cnt; j++) {
      const int x = st[j], inc = inc0 ? inc0 : mask[st[j0]] == 3 ? 6 : 4;
      const bool next = j + 1 < cnt && st[j + 1] == x + 1 && mask[x + 1] == mask[x] && sa[x + 1] == (sa[x] + inc) % wrap && sb[x + 1][g] == (sb[x][g] + inc) % wrap;
      if (j >= cnt - tail - 1 && j + 1 < cnt && !next) err |= 4;
      if (j + 1 < cnt && st[j + 1] != x + 1 && !(act[j] & A_DRAIN)) err |= 8;
      if (j >= cnt - tail || (next && !act[j] && j != cnt - tail - 1)) continue;
      if (j == j0 && (j == 0 || (inc0 != 4 && (act[j - 1] & (A_DRAIN | A_SYNC))))) err |= 16;
      const int y = st[j0];
      s.seg[nseg[g]++] = Seg{(uint32_t)y * 8 | (act[j] | (j == cnt - tail - 1 ? A_END : 0)) << 16, (uint32_t)(x + 1) * 8 | inc * 512 << 16, LO_A + sa[y] * 512, LO_B + sb[y][g] * 512};
      j0 = j + 1;
    }
  }
  constexpr void residual(int t, int map, bool q) {
    const int u0 = q ? qslot() : slot(), u1 = q ? u0 + 2 : slot();
    res = 1;
    op(0, u0, 2, map, 4, 1, kown(0)); op(0, u1, 2, map, 0, 0, kown(1));
    res = 0;
    for (int x = 0; x < 4; x++) { const int u = (x < 2 ? u0 : u1) + (x & 1); own[u][0] = 0; tok[u] = 1 + B_RF * 2 + (nres & 1); }
    nres++;
    s.task[t].res = u0 | u1 << 8;
  }
  constexpr Gen() {
    int cs[4] = {};
    for (int t = 0; t < 22; t++) {
      const int i = t % 11, use = i == 0 ? 2 : (i == 2 || i == 10) ? 15 : 3;
      for (int x = 0; x < 4; x++) if ((use >> x) & 1) s.task[t].sig |= (cs[x]++ & 1) << x;
    }
    for (int l = 0; l < 2; l++) {
      const int T = l * 11, dep = B_DEP + l * E_N;
      int st[7][56] = {};
      uint32_t act[7][56] = {};
      if (l == 1) {
        const int first = cur + 1;
        for (int j = 0; j < 4; j++) {
          const int x = st[j >> 1][j & 1] = step(1 << ((T + (j >> 1)) & 1)), u = qslot();
          sb[x][0] = sb[x][1] = u + 2;
          if (j < 2) {
            sa[x] = (u + 5) % NU; stage(sa[x], first, j ? 1 + B_SF * 2 + 1 : 0); s.task[10].stg |= sa[x] << (8 * j);
            op(0, 0, 0, 0, 0, 1, 1 << 10, B_SIG + 2 * j, s.task[10].sig >> (2 * j));
          }
          else { sa[x] = sa[x - 2]; own[sa[x]][1] = own[sa[x] + 1][1] = x + 1; op(0, 0, 0, 0, 0, 1, 0); }
          op(1, u + 2, 3, M_WQKV, 3, 1, kown(j & 1) | (j >> 1) << 10);
        }
        act[0][1] = A_DRAIN; act[1][1] = A_DRAIN | A_WAIT;
      }
      for (int i = 0; i < 2; i++) {
        for (int j = 2 * l; j < 16; j++) {
          if (i && j == 16 - RES_O) residual(T + 2, l ? M_Y : M_X0, true);
          const int x = st[i][j] = step(1 << ((T + i) & 1)), u = qslot(), k = l ? kpos(j) : j;
          sa[x] = u; sb[x][0] = sb[x][1] = u + 2;
          op(0, u, 2, l ? M_Y : M_X0, 2, 1, k, l && i == 0 && (j == 2 || j == 9) ? B_DEP + (j == 2 ? E_XA : E_XB) : -1);
          op(1, u + 2, 3, M_WQKV, 3, 1, k | i << 10);
        }
        if (i) act[1][Q_P1 - 1 + (l ? 2 : Q_P0)] = act[1][Q_P2 - 1 + (l ? 2 : Q_P0)] = A_SYNC;
        if (i && own[NU - 1][0] > cur - TAILQ) err |= 256;
        segs(T + i, st[i], act[i], 16, TAILQ, 5);
      }
      for (int j = 0; j < 16; j++) {
        const int x = st[0][j] = step(1 << (T & 1)), k = j < 8 ? j : j == 8 ? kown(1) : kskip(1, j - 9), hold = j == HOLD_O ? B_PUB + l * E_N + E_O1 : -1;
        act[0][j] = j == 8 ? A_MARK : 0;
        if (j != 8) { sa[x] = slot(); op(0, sa[x], 2, M_O, 2, 1, k, j == 0 ? dep + E_O0 : j == 9 ? dep + E_O1 : hold); }
        else { sa[x] = NU; op(0, 0, 0, 0, 0, 1, 1 << 10, B_SIG + 1, s.task[T + 1].sig >> 1); }
        sb[x][0] = sb[x][1] = slot();
        op(1, sb[x][0], 2, M_WO, 2, 1, k, hold);
      }
      segs(T + 2, st[0], act[0], 16, TAIL, 4);
      int beg[8] = {0, 16}, end[7] = {16, 32 - G_N1}, cnt[7] = {};
      for (int j = 2; j < 7; j++) { beg[j] = end[j - 2] + GU_E; end[j] = beg[j] + 16; }
      beg[7] = end[6];
      const int first = cur + 1;
      for (int j = 0; j < end[6]; j++) {
        int tl[2] = {-1, -1}, m = 0;
        for (int v = 0; v < 7; v++) if ((j >= beg[v] && j < end[v]) || (v == 1 && j < G_N1)) { const int g = (T + 3 + v) & 1; if (tl[g] >= 0) err |= 32; tl[g] = v; m |= 1 << g; }
        if (!m) err |= 32;
        if (j == end[6] - RES_D) residual(T + 10, M_Y, false);
        const int x = step(m), k = kpos(j < 16 ? j : (j + G_N1) & 15);
        const int v0 = m == 3 ? (tl[0] < tl[1] ? tl[0] : tl[1]) : tl[m >> 1];
        const int ps = (pos + 1) / 2 % 12;
        const bool last = m == 3 && (ps % 3 == 1 || (j >= 2 && j < G_N1 && (ps % 3 == 0 || (j == 2 && ps != 11))));
        if (!last) sa[x] = slot();
        const int u = slot();
        if (m == 3 && slot() != u + 2) err |= 32;
        if (last) sa[x] = slot();
        if (j < 2) { stage(sa[x], first, j ? 1 + B_SF * 2 : 0); s.task[T + 2].stg |= sa[x] << (8 * j); op(0, 0, 0, 0, 0, 1, 1 << 10, B_SIG + 2 * j, s.task[T + 2].sig >> (2 * j)); }
        else op(0, sa[x], 2, M_Y, 2, 1, k, j == 2 ? dep + E_YA : j == 9 ? dep + E_YB : -1);
        op(1, u, m == 3 ? 4 : 2, m == 3 ? M_W13P : M_W13, m == 3 ? 4 : 2, 1, k | v0 << 10, j == 3 ? B_PUB + l * E_N + E_YA : -1);
        for (int g = 0; g < 2; g++) {
          const int v = tl[g];
          if (v < 0) continue;
          sb[x][g] = u + (v - v0) * 2;
          act[v][cnt[v]] = j == beg[v + 1] - 1 ? A_TURN : v == 1 && j == G_N1 - 1 ? A_DRAIN | A_WAIT : v == 0 && j == 1 ? A_MARK : 0;
          st[v][cnt[v]++] = x;
        }
      }
      for (int v = 0; v < 7; v++) { if (cnt[v] != 16) err |= 64; segs(T + 3 + v, st[v], act[v], 16, 0, 0); }
      for (int j = 0; j < 56; j++) {
        const int x = st[0][j] = step(1 << (T & 1));
        act[0][j] = 0;
        sa[x] = slot(); op(0, sa[x], 2, M_H, 2, 1, j, j == 0 ? dep + E_H4 : j == 40 ? dep + E_H4 + 1 : j == 48 ? dep + E_H4 + 2 : -1);
        sb[x][0] = sb[x][1] = slot(); op(1, sb[x][0], 2, M_W2, 2, 1, j);
      }
      segs(T + 10, st[0], act[0], 56, TAIL, 4);
    }
    { const int u0 = slot(), u1 = slot(); stage(u0, cur + 1, 0); stage(u1, cur + 1, 0); s.task[21].stg = u0 | u1 << 8; }
    if (n[0] > NOPA || n[1] > NOPB || nseg[0] >= NSEG || nseg[1] >= 2 * NSEG) err |= 128;
    for (int x = n[0]; x < NOPA + 64; x++) o.a[x] = uint2{B_PASS << 24 | 1u << 31, 0};
    for (int x = n[1]; x < NOPB + 64; x++) o.b[x] = uint2{B_PASS << 24 | 1u << 31, 0};
  }
};
constexpr Gen GEN{};
static_assert(GEN.err == 0, "schedule");
constexpr int NOP0 = (GEN.n[0] + 31) / 32 * 32, NOP1 = (GEN.n[1] + 31) / 32 * 32;

struct __align__(64) Params {
  CUtensorMap tm[M_N];
};

}

__constant__ Sched c_sched = GEN.s;
__device__ const Ops g_ops = GEN.o;
struct __align__(1024) Scratch {
  float2 stat[3][16][8][128];
  uint4 stat0[16][128];
  uint4 halo[4][16][8][6][32];
  uint4 cs[9][8][64];
  uint32_t flags[NCTA][32];
  uint32_t cnt[4][32];
  uint32_t epoch[NCTA + NHELP];
  __align__(1024) bf16 o[S_ * D_];
  bf16 y[S_ * D_], h[S_ * F_];
};
__device__ Scratch g_sc;
__device__ __align__(1024) bf16 g_w13[2 * D_ * F_];

#define TL(t, i) do {} while (0)
#define TS(i8, wg) do {} while (0)
#define TLW(t, i) do {} while (0)
#define MB_LIMIT (1 << 16)
#define FL_LIMIT (1 << 21)

namespace {

__device__ __forceinline__ uint32_t smem_u32(const void* p) { return (uint32_t)__cvta_generic_to_shared(p); }
__device__ __forceinline__ void mbar_init(uint32_t br, uint32_t cnt) { asm volatile("mbarrier.init.shared::cta.b64 [%0], %1;" ::"r"(br), "r"(cnt)); }
__device__ __forceinline__ void mbar_expect_tx(uint32_t br, uint32_t bytes) { asm volatile("mbarrier.arrive.expect_tx.shared::cta.b64 _, [%0], %1;" ::"r"(br), "r"(bytes) : "memory"); }
__device__ __forceinline__ void mbar_arrive(uint32_t br) { asm volatile("mbarrier.arrive.shared::cta.b64 _, [%0];" ::"r"(br) : "memory"); }
__device__ __forceinline__ void mbar_arrive_if(uint32_t br, uint32_t p) {
  asm volatile("{\n.reg .pred q;\nsetp.ne.u32 q, %1, 0;\n@q mbarrier.arrive.shared::cta.b64 _, [%0];\n}\n" ::"r"(br), "r"(p) : "memory");
}
__device__ __forceinline__ void mbar_arrive_warp(uint32_t br) {
  asm volatile("{\n.reg .pred q;\nbar.warp.sync 0xffffffff;\nelect.sync _|q, 0xffffffff;\n@q mbarrier.arrive.shared::cta.b64 _, [%0];\n}\n" ::"r"(br) : "memory");
}
__device__ __forceinline__ bool mbar_try_wait(uint32_t br, uint32_t parity) {
  uint32_t ok;
  asm volatile("{\n.reg .pred p;\nmbarrier.try_wait.parity.shared::cta.b64 p, [%1], %2;\nselp.u32 %0, 1, 0, p;\n}\n" : "=r"(ok) : "r"(br), "r"(parity) : "memory");
  return ok;
}
__device__ __forceinline__ void mbar_wait(uint32_t br, uint32_t parity) {
#pragma unroll 1
  for (int it = 0; it < MB_LIMIT; ++it) { if (mbar_try_wait(br, parity)) return; }
  __trap();
}
__device__ __forceinline__ bool elect_one() { uint32_t p; asm volatile("{\n.reg .pred P;\nelect.sync _|P, 0xffffffff;\nselp.u32 %0, 1, 0, P;\n}\n" : "=r"(p)); return p; }
__device__ __forceinline__ void fence_proxy_async_smem() { asm volatile("fence.proxy.async.shared::cta;" ::: "memory"); }
__device__ __forceinline__ void tma4d(uint32_t dst, const CUtensorMap* m, int c0, int c1, int c2, int c3, uint32_t br) {
  asm volatile("cp.async.bulk.tensor.4d.shared::cluster.global.mbarrier::complete_tx::bytes [%0], [%1, {%3, %4, %5, %6}], [%2];" ::"r"(dst), "l"(m), "r"(br), "r"(c0), "r"(c1), "r"(c2), "r"(c3) : "memory");
}
__device__ __forceinline__ void tma4d_store(const CUtensorMap* m, uint32_t src, int c1, int c2, int c3) {
  asm volatile("{\n.reg .pred p;\nelect.sync _|p, 0xffffffff;\n@p cp.async.bulk.tensor.4d.global.shared::cta.bulk_group [%0, {%5, %2, %3, %4}], [%1];\n}\n" ::"l"(m), "r"(src), "r"(c1), "r"(c2), "r"(c3), "r"(0) : "memory");
}
__device__ __forceinline__ void stsm4(uint32_t a, uint32_t x, uint32_t y, uint32_t z, uint32_t w) {
  asm volatile("stmatrix.sync.aligned.m8n8.x4.shared.b16 [%0], {%1,%2,%3,%4};" ::"r"(a), "r"(x), "r"(y), "r"(z), "r"(w) : "memory");
}
__device__ __forceinline__ void stsm4t(uint32_t a, uint32_t x, uint32_t y, uint32_t z, uint32_t w) {
  asm volatile("stmatrix.sync.aligned.m8n8.x4.trans.shared.b16 [%0], {%1,%2,%3,%4};" ::"r"(a), "r"(x), "r"(y), "r"(z), "r"(w) : "memory");
}
__device__ __forceinline__ void ldsm4(uint32_t a, uint32_t& x, uint32_t& y, uint32_t& z, uint32_t& w) {
  asm volatile("ldmatrix.sync.aligned.m8n8.x4.shared.b16 {%0,%1,%2,%3}, [%4];" : "=r"(x), "=r"(y), "=r"(z), "=r"(w) : "r"(a) : "memory");
}
__device__ __forceinline__ void st_tag(uint4* p, uint32_t a, uint32_t b, uint32_t c, uint32_t tag) {
  asm volatile("{\n.reg .b64 x, y;\n.reg .b128 z;\nmov.b64 x, {%1, %2};\nmov.b64 y, {%3, %4};\nmov.b128 z, {x, y};\nst.relaxed.gpu.global.b128 [%0], z;\n}\n" ::"l"(p), "r"(a), "r"(b), "r"(c), "r"(tag) : "memory");
}
__device__ __forceinline__ uint4 ld_tag(const uint4* p) {
  uint4 v;
  asm volatile("{\n.reg .b64 x, y;\n.reg .b128 z;\nld.relaxed.gpu.global.b128 z, [%4];\nmov.b128 {x, y}, z;\nmov.b64 {%0, %1}, x;\nmov.b64 {%2, %3}, y;\n}\n" : "=r"(v.x), "=r"(v.y), "=r"(v.z), "=r"(v.w) : "l"(p) : "memory");
  return v;
}
template <int NAP, int N> __device__ __forceinline__ void ld_tag_wait(uint4 (&v)[N], const uint4* p, uint32_t tag) {
#pragma unroll 1
  for (int it = 0; it < FL_LIMIT; ++it) {
    uint32_t bad = 0;
#pragma unroll
    for (int j = 0; j < N; j++) v[j] = ld_tag(p + j * 32);
#pragma unroll
    for (int j = 0; j < N; j++) bad |= v[j].w ^ tag;
    if (__all_sync(0xffffffffu, bad == 0)) return;
    if (NAP) __nanosleep(NAP);
  }
  __trap();
}
__device__ __forceinline__ void prefetch_tmap(const CUtensorMap* m) { asm volatile("prefetch.tensormap [%0];" ::"l"(m) : "memory"); }
__device__ __forceinline__ void wgmma_fence() { asm volatile("wgmma.fence.sync.aligned;" ::: "memory"); }
__device__ __forceinline__ void wgmma_commit() { asm volatile("wgmma.commit_group.sync.aligned;" ::: "memory"); }
template <int N> __device__ __forceinline__ void wgmma_wait() { asm volatile("wgmma.wait_group.sync.aligned %0;" ::"n"(N) : "memory"); }
template <int R> __device__ __forceinline__ void reg_alloc() { asm volatile("setmaxnreg.inc.sync.aligned.u32 %0;" ::"n"(R)); }
template <int R> __device__ __forceinline__ void reg_dealloc() { asm volatile("setmaxnreg.dec.sync.aligned.u32 %0;" ::"n"(R)); }
__device__ __forceinline__ void bar_sync(int id, int n) { asm volatile("bar.sync %0, %1;" ::"r"(id), "r"(n) : "memory"); }
__device__ __forceinline__ void bar_arrive(int id, int n) { asm volatile("bar.arrive %0, %1;" ::"r"(id), "r"(n) : "memory"); }
__device__ __forceinline__ uint32_t ld_acquire(const uint32_t* p) { uint32_t v; asm volatile("ld.acquire.gpu.global.u32 %0, [%1];" : "=r"(v) : "l"(p) : "memory"); return v; }
__device__ __forceinline__ void st_release(uint32_t* p, uint32_t v) { asm volatile("st.release.gpu.global.u32 [%0], %1;" ::"l"(p), "r"(v) : "memory"); }
__device__ __forceinline__ uint4 ldcg16(const void* p) { uint4 v; asm volatile("ld.global.cg.v4.u32 {%0,%1,%2,%3}, [%4];" : "=r"(v.x), "=r"(v.y), "=r"(v.z), "=r"(v.w) : "l"(p) : "memory"); return v; }
__device__ __forceinline__ float2 lds8f(uint32_t a) { float2 v; asm volatile("ld.shared.v2.f32 {%0,%1}, [%2];" : "=f"(v.x), "=f"(v.y) : "r"(a)); return v; }
__device__ __forceinline__ float lds4f(uint32_t a) { float v; asm volatile("ld.shared.f32 %0, [%1];" : "=f"(v) : "r"(a)); return v; }
__device__ __forceinline__ uint32_t lds4(uint32_t a) { uint32_t v; asm volatile("ld.shared.u32 %0, [%1];" : "=r"(v) : "r"(a) : "memory"); return v; }
__device__ __forceinline__ void lds16f(uint32_t a, float& x, float& y, float& z, float& w) { asm volatile("ld.shared.v4.f32 {%0,%1,%2,%3}, [%4];" : "=f"(x), "=f"(y), "=f"(z), "=f"(w) : "r"(a) : "memory"); }
__device__ __forceinline__ void sts8f(uint32_t a, float x, float y) { asm volatile("st.shared.v2.f32 [%0], {%1,%2};" ::"r"(a), "f"(x), "f"(y) : "memory"); }
__device__ __forceinline__ void sts4f(uint32_t a, float x) { asm volatile("st.shared.f32 [%0], %1;" ::"r"(a), "f"(x) : "memory"); }
__device__ __forceinline__ void sts16(uint32_t a, uint32_t x, uint32_t y, uint32_t z, uint32_t w) { asm volatile("st.shared.v4.u32 [%0], {%1,%2,%3,%4};" ::"r"(a), "r"(x), "r"(y), "r"(z), "r"(w) : "memory"); }
__device__ __forceinline__ void lds16(uint32_t a, uint32_t& x, uint32_t& y, uint32_t& z, uint32_t& w) { asm volatile("ld.shared.v4.u32 {%0,%1,%2,%3}, [%4];" : "=r"(x), "=r"(y), "=r"(z), "=r"(w) : "r"(a) : "memory"); }
__device__ __forceinline__ uint32_t pack_bf16(float a, float b) { uint32_t r; asm("cvt.rn.bf16x2.f32 %0, %1, %2;" : "=r"(r) : "f"(b), "f"(a)); return r; }
__device__ __forceinline__ uint32_t pack_bf16_v(float a, float b) { uint32_t r; asm volatile("cvt.rn.bf16x2.f32 %0, %1, %2;" : "=r"(r) : "f"(b), "f"(a)); return r; }
__device__ __forceinline__ float bf_lo(uint32_t v) { return __uint_as_float(v << 16); }
__device__ __forceinline__ float bf_hi(uint32_t v) { return __uint_as_float(v & 0xffff0000u); }
constexpr float LOG2E = 1.4426950408889634f;
__device__ __forceinline__ float ex2f(float x) { float y; asm("ex2.approx.ftz.f32 %0, %1;" : "=f"(y) : "f"(x)); return y; }
__device__ __forceinline__ float tanhf_(float x) { float y; asm("tanh.approx.f32 %0, %1;" : "=f"(y) : "f"(x)); return y; }
__device__ __forceinline__ float rcpf(float x) { float y; asm("rcp.approx.ftz.f32 %0, %1;" : "=f"(y) : "f"(x)); return y; }
__device__ __forceinline__ float bf_round(float a) { return bf_lo(pack_bf16(a, 0.f)); }
__device__ __forceinline__ uint32_t movmat(uint32_t a) { uint32_t d; asm volatile("movmatrix.sync.aligned.m8n8.trans.b16 %0, %1;" : "=r"(d) : "r"(a)); return d; }
__device__ __forceinline__ void mma16816(float& d0, float& d1, float& d2, float& d3, uint32_t a0, uint32_t a1, uint32_t a2, uint32_t a3, uint32_t b0, uint32_t b1,
                                         float c0, float c1, float c2, float c3) {
  asm volatile("mma.sync.aligned.m16n8k16.row.col.f32.bf16.bf16.f32 {%0,%1,%2,%3}, {%4,%5,%6,%7}, {%8,%9}, {%10,%11,%12,%13};"
               : "=f"(d0), "=f"(d1), "=f"(d2), "=f"(d3) : "r"(a0), "r"(a1), "r"(a2), "r"(a3), "r"(b0), "r"(b1), "f"(c0), "f"(c1), "f"(c2), "f"(c3));
}
template <int N> __device__ __forceinline__ void copy_out(uint32_t a, void* base, uint32_t ofs, int pitch, int lane) {
  a += (lane >> 3) * 128 + (((lane ^ (lane >> 3)) & 7) << 4);
  char* const g = static_cast<char*>(base) + (ofs + (lane >> 3) * pitch + (lane & 7) * 16);
  uint32_t v[N][4];
  __syncwarp();
#pragma unroll
  for (int j = 0; j < N; j++) lds16((a ^ ((j & 1) * 64)) + j * 512, v[j][0], v[j][1], v[j][2], v[j][3]);
#pragma unroll
  for (int j = 0; j < N; j++) asm volatile("st.global.v4.u32 [%0], {%1, %2, %3, %4};" ::"l"(g + j * 4 * pitch), "r"(v[j][0]), "r"(v[j][1]), "r"(v[j][2]), "r"(v[j][3]) : "memory");
}
__device__ __forceinline__ int lane_now() { int v; asm volatile("mov.u32 %0, %%laneid;" : "=r"(v)); return v; }
__device__ __forceinline__ uint32_t uni(uint32_t x, int lane) { return __shfl_sync(0xffffffffu, x + lane, 0); }
__device__ __forceinline__ uint64_t dsc(uint32_t hi, uint32_t lo) { return ((uint64_t)hi << 32) | lo; }

#define R8(a, o) "+f"(a[o]), "+f"(a[o + 1]), "+f"(a[o + 2]), "+f"(a[o + 3]), "+f"(a[o + 4]), "+f"(a[o + 5]), "+f"(a[o + 6]), "+f"(a[o + 7])
#define R32(a, o) R8(a, o), R8(a, o + 8), R8(a, o + 16), R8(a, o + 24)
#define REG64 "%0, %1, %2, %3, %4, %5, %6, %7, %8, %9, %10, %11, %12, %13, %14, %15, %16, %17, %18, %19, %20, %21, %22, %23, %24, %25, %26, %27, %28, %29, %30, %31, " \
              "%32, %33, %34, %35, %36, %37, %38, %39, %40, %41, %42, %43, %44, %45, %46, %47, %48, %49, %50, %51, %52, %53, %54, %55, %56, %57, %58, %59, %60, %61, %62, %63"
#define REG96 REG64 ", %64, %65, %66, %67, %68, %69, %70, %71, %72, %73, %74, %75, %76, %77, %78, %79, %80, %81, %82, %83, %84, %85, %86, %87, %88, %89, %90, %91, %92, %93, %94, %95"
__device__ __forceinline__ void wgmma(float (&d)[64], uint64_t da, uint64_t db) {
  asm volatile("wgmma.mma_async.sync.aligned.m64n128k16.f32.bf16.bf16 {" REG64 "}, %64, %65, 1, 1, 1, 0, 1;\n"
               : R32(d, 0), R32(d, 32) : "l"(da), "l"(db));
}
__device__ __forceinline__ void wgmma(float (&d)[96], uint64_t da, uint64_t db) {
  asm volatile("wgmma.mma_async.sync.aligned.m64n192k16.f32.bf16.bf16 {" REG96 "}, %96, %97, 1, 1, 1, 0, 1;\n"
               : R32(d, 0), R32(d, 32), R32(d, 64) : "l"(da), "l"(db));
}
#define W8(a, o) "=f"(a[o]), "=f"(a[o + 1]), "=f"(a[o + 2]), "=f"(a[o + 3]), "=f"(a[o + 4]), "=f"(a[o + 5]), "=f"(a[o + 6]), "=f"(a[o + 7])
#define W32(a, o) W8(a, o), W8(a, o + 8), W8(a, o + 16), W8(a, o + 24)
__device__ __forceinline__ void wgmma_z(float (&d)[64], uint64_t da, uint64_t db) {
  asm volatile("wgmma.mma_async.sync.aligned.m64n128k16.f32.bf16.bf16 {" REG64 "}, %64, %65, 0, 1, 1, 0, 1;\n"
               : W32(d, 0), W32(d, 32) : "l"(da), "l"(db));
}
__device__ __forceinline__ void wgmma_z(float (&d)[96], uint64_t da, uint64_t db) {
  asm volatile("wgmma.mma_async.sync.aligned.m64n192k16.f32.bf16.bf16 {" REG96 "}, %96, %97, 0, 1, 1, 0, 1;\n"
               : W32(d, 0), W32(d, 32), W32(d, 64) : "l"(da), "l"(db));
}

__device__ __forceinline__ void wgmma_cs(float (&d)[4], uint64_t da, uint64_t db) {
  asm volatile("wgmma.mma_async.sync.aligned.m64n8k16.f32.bf16.bf16 {%0, %1, %2, %3}, %4, %5, 1, 1, 1, 1, 0;\n" : "+f"(d[0]), "+f"(d[1]), "+f"(d[2]), "+f"(d[3]) : "l"(da), "l"(db));
}
__device__ __forceinline__ void bulk_commit() { asm volatile("cp.async.bulk.commit_group;" ::: "memory"); }
__device__ __forceinline__ void bulk_wait() { asm volatile("cp.async.bulk.wait_group 0;" ::: "memory"); }
__device__ __forceinline__ void fence_bar_init() { asm volatile("fence.mbarrier_init.release.cluster;" ::: "memory"); }

__device__ __forceinline__ uint32_t clock_now() { uint32_t v; asm volatile("mov.u32 %0, %%clock;" : "=r"(v)); return v; }
__device__ __forceinline__ void delay_until(uint32_t t0, int cycles) {
#pragma unroll 1
  for (int it = 0; it < 1000 && (int)(clock_now() - t0) < cycles; it++) __nanosleep(40);
}
__device__ __forceinline__ uint32_t ld_epoch(const uint32_t* p) { uint32_t v; asm volatile("ld.global.u32 %0, [%1];" : "=r"(v) : "l"(p) : "memory"); return v + 1; }
__device__ __forceinline__ void wait_flags(const uint32_t* f, uint32_t tag) {
#pragma unroll 1
  for (int it = 0; it < FL_LIMIT; ++it) if (__all_sync(0xffffffffu, (int)(ld_acquire(f) - tag) >= 0)) return;
  __trap();
}

__device__ __forceinline__ float2 ln_finish(float sum, float sq) {
  const float mean = sum * (1.f / D_), var = fmaxf(fmaf(-mean, mean, sq * (1.f / D_)), 0.f);
  const float mb = bf_round(mean);
  const float vb = bf_round(var);
  const float sd = bf_round(sqrtf(bf_round(vb + 1e-5f)));
  return make_float2(1.0f / sd, -mb);
}

__device__ __forceinline__ void helper_cta(const Params& P, Scratch* sc, int e, int wg, int w) {
  const int tid = threadIdx.x;
  if (tid == 256) {
#pragma unroll
    for (int i = 0; i < 16; i++) mbar_init(bar(i), 1);
    fence_bar_init();
  }
  if (tid < 64) sts16(SM_STG + tid * 16, 0x3f803f80u, 0x3f803f80u, 0x3f803f80u, 0x3f803f80u);
  fence_proxy_async_smem();
  __syncthreads();
  if (wg == 2) {
    if (w == 0) {
#pragma unroll 1
      for (int n = 0; n < 9 * 32; n++) {
        const int job = n >> 5;
        const uint32_t fb = bar(n & 7), dst = SB + (n & 7) * 24576;
        mbar_wait(bar(8 + (n & 7)), (n >> 3) + 1);
        if (elect_one()) {
          mbar_expect_tx(fb, job < 2 ? 24576 : 16384);
          tma4d(dst, &P.tm[job < 2 ? M_WQKV : M_W13], (e * 2 + (n & 1)) * 64, (n & 30) * 32, 0, job < 2 ? job : job - 2, fb);
        }
        __syncwarp();
      }
    }
  } else {
    const uint32_t tag = ld_epoch(sc->epoch + NCTA + e);
    const int lane = tid & 31;
#pragma unroll 1
    for (int job = 0; job < 9; job++) {
      float s[3][4] = {};
#pragma unroll 1
      for (int n = job * 32 + wg; n < job * 32 + 32; n += 2) {
        mbar_wait(bar(n & 7), n >> 3);
        wgmma_fence();
        const uint32_t a = ((SB + (n & 7) * 24576) >> 4) + 0x2000000;
#pragma unroll
        for (int k = 0; k < 8; k++) wgmma_cs(s[k & 1], dsc(0x40000040u, a + (k & 1) * 512 + (k >> 1) * 128), dsc(0x40000040u, (SM_STG >> 4) + 0x10000));
        if (job < 2) {
          wgmma_fence();
#pragma unroll
          for (int k = 0; k < 4; k++) wgmma_cs(s[2], dsc(0x40000040u, a + 1024 + k * 128), dsc(0x40000040u, (SM_STG >> 4) + 0x10000));
        }
        wgmma_commit();
        wgmma_wait<0>();
        mbar_arrive_if(bar(8 + (n & 7)), (tid & 127) == 0);
      }
      if (!(lane & 2))
        st_tag(&sc->cs[job][e * 2 + wg][w * 16 + (lane & 1) * 8 + (lane >> 2)], __float_as_uint(lane & 1 ? s[0][2] : s[0][0]), __float_as_uint(lane & 1 ? s[1][2] : s[1][0]),
               __float_as_uint(lane & 1 ? s[2][2] : s[2][0]), tag);
      __syncwarp();
    }
    bar_sync(NB_END, 256);
    if (tid == 0) sc->epoch[NCTA + e] = tag;
  }
}

template <bool WEIGHTS>
__device__ __forceinline__ void producer(const Params& P, const uint2* tab, int nop, int lane, int c, int row, int par, uint32_t t_entry) {
  uint64_t pol;
  asm volatile("createpolicy.fractional.L2::evict_first.b64 %0, 1.0;" : "=l"(pol));
  __syncthreads();
  uint2 nx = __ldg(tab + lane), n2 = __ldg(tab + 32 + lane);
#pragma unroll 1
  for (int j = 1; j < FIRST; j++) {
    delay_until(t_entry, ST_T1 + (j - 1) * ST_D1);
    if (elect_one()) {
      mbar_expect_tx(bar(B_FULL) + 8 * j, WEIGHTS ? 24576 : 16384);
      if (WEIGHTS) tma4d(SB + j * 40960 + 16384, &P.tm[M_WQKV], c * 64, j * 64, 0, 0, bar(B_FULL) + 8 * j);
      else tma4d(SB + j * 40960, &P.tm[M_X0], 0, row, j, par, bar(B_FULL) + 8 * j);
    }
    __syncwarp();
  }
  if (!WEIGHTS && lane == 0) {
#pragma unroll
    for (int j = 0; j < FIRST; j++) mbar_arrive(bar(B_EMPTY + 2 + j));
  }
  __syncwarp();
  auto word = [&](uint2 e) { return e.x + (((int)(e.y & 7) > c) + (e.y & 8 ? c : 0)) * (WEIGHTS ? 64 : 1); };
  uint32_t xn = __shfl_sync(0xffffffffu, word(nx), 0);
  const uint64_t maps = reinterpret_cast<uint64_t>(&P.tm[WEIGHTS ? M_WQKV : 0]);
  if ((uint32_t)maps > 0xfffffdffu) __trap();
  const uint32_t sb = uni(SB, lane), bars = uni(BARS, lane), zero = uni(0, lane), mlo = uni((uint32_t)maps, lane), mhi = uni(maps >> 32, lane);
#pragma unroll 1
  for (int base = 0; base < nop; base += 32) {
    const uint2 e = nx;
    nx = n2;
    n2 = __ldg(tab + base + 64 + lane);
    const uint32_t xw = word(lane ? e : nx), bytes = e.y & 0xe000, eb = (e.y >> 6) & 0x78;
    const int arr = e.y & 16 ? lane + 1 : 0, solo = e.y & 32 ? lane + 1 : 0;
#pragma unroll 1
    for (int j = 1; j <= 32; j++) {
      const uint32_t x = xn;
      xn = __shfl_sync(0xffffffffu, xw, j);
#define OP_WAIT(X) "{\n.reg .pred pe, pa, pn, ps, pw;\n.reg .u32 it;\n" \
                "elect.sync _|pe, 0xffffffff;\nsetp.eq.u32 pa, %0, %1;\nsetp.ne.and.u32 pn, %2, 0, pe;\n" X \
                "mov.u32 it, 0;\n" \
                "WAIT_%=:\n" \
                "mbarrier.try_wait.parity.shared::cta.b64 pw, [%3 + %9], %4;\n" \
                "@pw bra.uni GO_%=;\n" \
                "add.u32 it, it, 1;\nsetp.lt.u32 pw, it, 0x10000;\n" \
                "@pw bra.uni WAIT_%=;\n" \
                "trap;\n" \
                "GO_%=:\n"
#define OP_ARGS "r"(arr), "r"(j), "r"(x & (1 << 12)), "r"((x >> 21) & 0x3f8), "r"(x >> 31), "r"(((x >> 15) & 0x1f8) | bars), "r"(bytes), "r"((x & 0x3e000) | sb), \
                "l"(dsc(mhi, mlo + (WEIGHTS ? (x & 0x38) * 16 : x & 0x180))), "n"(BARS), "r"(x & (WEIGHTS ? 0xfc0 : 63)), "r"(x & (WEIGHTS ? 7 : 64))
      if (WEIGHTS)
        asm volatile(OP_WAIT("")
                     "@pn cp.async.bulk.tensor.4d.shared::cluster.global.mbarrier::complete_tx::bytes.L2::cache_hint [%7], [%8, {%12, %10, %13, %11}], [%5], %14;\n"
                     "@pa mbarrier.arrive.expect_tx.shared::cta.b64 _, [%5], %6;\n"
                     "}\n" ::OP_ARGS, "r"(c * 64), "r"(zero), "l"(pol) : "memory");
      else
        asm volatile(OP_WAIT(".reg .pred pf;\nsetp.ne.u32 pf, %11, 0;\nsetp.eq.u32 ps, %14, %1;\n")
                     "@pn cp.async.bulk.tensor.4d.shared::cluster.global.mbarrier::complete_tx::bytes [%7], [%8, {%17, %12, %10, %13}], [%5];\n"
                     "@pf fence.proxy.async.shared::cta;\n"
                     "@pa mbarrier.arrive.expect_tx.shared::cta.b64 _, [%5], %6;\n"
                     "@ps mbarrier.arrive.shared::cta.b64 _, [%15 + %16];\n"
                     "}\n" ::OP_ARGS, "r"(row), "r"(par), "r"(solo), "r"(eb), "n"(bar(B_EMPTY)), "r"(zero) : "memory");
    }
  }
}

template <int N, uint32_t LO> __device__ __forceinline__ void advance(uint32_t& x, uint32_t inc) {
  constexpr uint32_t LEN = (N == 192 ? NU : 24) * 512;
  x += inc; if (x >= LO + LEN) x -= LEN;
}
__device__ __forceinline__ bool full_test(uint32_t i8) {
  uint32_t ok;
  asm volatile("{\n.reg .pred p;\nmbarrier.test_wait.parity.shared::cta.b64 p, [%1 + %3], %2;\nselp.u32 %0, 1, 0, p;\n}\n" : "=r"(ok) : "r"(i8 & 0x78), "r"(i8 >> 7), "n"(bar(B_FULL)) : "memory");
  return ok;
}
__device__ __forceinline__ void full_wait(uint32_t i8) { mbar_wait(bar(B_FULL) + (i8 & 0x78), i8 >> 7); }
__device__ __forceinline__ void release(uint32_t i8, uint32_t p) {
  asm volatile("{\n.reg .pred q;\nsetp.ne.u32 q, %1, 0;\n@q mbarrier.arrive.shared::cta.b64 _, [%0 + %2];\n}\n" ::"r"(i8 & 0x78), "r"(p), "n"(bar(B_EMPTY)) : "memory");
}
template <int N, int RELK, int FIRSTK>
__device__ __forceinline__ bool kstep(float (&acc)[2][N / 2], uint32_t hiA, uint32_t hiB, uint32_t& a, uint32_t& b, uint32_t inc, uint32_t& i8, uint32_t x) {
  constexpr uint32_t MI = N == 192 ? 64 : 512;
  wgmma_fence();
  if (FIRSTK == 2) { wgmma_z(acc[0], dsc(hiA, a), dsc(hiB, b)); wgmma_z(acc[1], dsc(hiA, a + MI), dsc(hiB, b)); }
  else { wgmma(acc[0], dsc(hiA, a), dsc(hiB, b)); wgmma(acc[1], dsc(hiA, a + MI), dsc(hiB, b)); }
  i8 += 8;
  const bool ok = full_test(i8);
#pragma unroll
  for (int k = 1; k < 4; k++) {
    wgmma(acc[0], dsc(hiA, a + 2 * k), dsc(hiB, b + 128 * k)); wgmma(acc[1], dsc(hiA, a + MI + 2 * k), dsc(hiB, b + 128 * k));
    if (k == RELK || k == 3) wgmma_commit();
    if (k == 3) { advance<N, LO_A>(a, inc); advance<N, LO_B>(b, inc); }
    if (!FIRSTK && k == RELK) {
      wgmma_wait<1>();
      release(i8, x);
    }
  }
  return ok;
}
template <int MODE, int N, class F, class G>
__device__ __forceinline__ void mainloop(float (&acc)[2][N], uint32_t sig, int t, int wg, uint32_t& sp, F&& prepare, G&& first_half) {
  const uint32_t turn = bar(B_TURN) + 8 * (wg ^ 1);
  constexpr uint32_t hiA = MODE == 0 ? 0x40000080u : 0x40000040u, hiB = 0x40000040u;
  constexpr Seg S0 = GEN.s.seg[0];
  uint32_t i8 = S0.i8 & 0xffff, nxt = S0.end8 & 0xffff, a = S0.a, b = S0.b, inc = S0.end8 >> 16;
  if (MODE != 0 || t != 0) {
    if (MODE == 2 || (MODE == 0 ? t != 12 : t != 4 && t != 15)) mbar_wait(bar(B_TURN) + 8 * wg, (t - 1) >> 1);
    i8 = c_sched.seg[sp].i8 & 0xffff; nxt = c_sched.seg[sp].end8 & 0xffff; a = c_sched.seg[sp].a; b = c_sched.seg[sp].b; inc = c_sched.seg[sp].end8 >> 16;
  }
  const uint32_t hiA_ = hiA + (a >> 31);
  full_wait(i8);
  TL(t, 2);
  TS(i8, wg);
  bool ok = kstep<N * 2, 3, MODE == 2 ? 1 : 2>(acc, hiA_, hiB, a, b, inc, i8, 0);
  if (MODE == 2 && (t == 2 || t == 13)) bar_sync(NB_OGO, 256);
#pragma unroll 1
  while (true) {
    uint32_t act;
#pragma unroll 1
    while (true) {
      if (!ok) full_wait(i8);
      TS(i8, wg);
      ok = kstep<N * 2, MODE == 1 ? 1 : 3, 0>(acc, hiA_, hiB, a, b, inc, i8, sig);
      if (__builtin_expect(i8 == nxt, 0)) {
        act = c_sched.seg[sp++].i8 >> 16;
        if (MODE == 1) mbar_arrive_if(turn, sig & (act >> 1));
        if (act & (MODE == 0 ? A_END | A_DRAIN | A_SYNC : MODE == 1 ? A_END | A_DRAIN : A_END)) break;
        nxt = c_sched.seg[sp].end8 & 0xffff; a = c_sched.seg[sp].a; b = c_sched.seg[sp].b;
        if (MODE == 1) inc = c_sched.seg[sp].end8 >> 16;
      }
    }
    if (MODE == 2 || (act & A_END)) break;
    nxt = c_sched.seg[sp].end8 & 0xffff; a = c_sched.seg[sp].a; b = c_sched.seg[sp].b;
    if (MODE == 1) inc = c_sched.seg[sp].end8 >> 16;
    if (MODE == 0 && (act & A_SYNC)) bar_arrive(NB_PX, 256);
    wgmma_wait<0>();
    release(i8 + 8, sig);
    i8 = c_sched.seg[sp].i8 & 0xffff;
    if (MODE == 1 || (act & A_WAIT)) mbar_wait(bar(B_TURN) + 8 * wg, (t - 1) >> 1);
    full_wait(i8);
    if (MODE == 0 && (act & A_SYNC)) bar_sync(NB_PY, 256);
    TS(i8, wg);
    ok = kstep<N * 2, 3, 1>(acc, hiA_, hiB, a, b, inc, i8, 0);
  }
  if (MODE != 1) {
    constexpr int TL_ = MODE == 0 ? TAILQ : TAIL;
    uint32_t ta[TL_], tb[TL_];
#pragma unroll
    for (int x = 0; x < TL_; x++) {
      full_wait(i8 + 8 * x);
      TS(i8 + 8 * x, wg);
      ta[x] = a; tb[x] = b;
      advance<N * 2, LO_A>(a, inc); advance<N * 2, LO_B>(b, inc);
    }
#pragma unroll
    for (int h = 0; h < 2; h++) {
      const int mi = MODE == 0 ? 1 - h : h;
      wgmma_fence();
#pragma unroll
      for (int x = 0; x < TL_; x++)
#pragma unroll
        for (int k = 0; k < 4; k++) wgmma(acc[mi], dsc(hiA, ta[x] + mi * (MODE == 0 ? 64 : 512) + 2 * k), dsc(hiB, tb[x] + 128 * k));
      wgmma_commit();
      if (TL_ > 1 && h == 0) { wgmma_wait<1>(); release(i8 + 8, sig); prepare(); }
    }
    mbar_arrive_if(turn, sig);
    if (TL_ == 1) { wgmma_wait<2>(); release(i8 + 8, sig); prepare(); }
    wgmma_wait<1>();
    first_half();
    wgmma_wait<0>();
#pragma unroll
    for (int x = 0; x < TL_; x++) release(i8 + 16 + 8 * x, sig);
  } else {
    prepare();
    wgmma_wait<0>();
    release(i8 + 8, sig);
  }
}

template <int SWAP, int BY_SM>
__global__ void __launch_bounds__(384, 1) fused_kernel(Scratch* sc, const Ops* ops, const bf16* x0, bf16* out, const __grid_constant__ Params P) {
  extern __shared__ __align__(1024) uint8_t smem_raw[];
  const int tid = threadIdx.x;
  if (tid == 0) prefetch_tmap(&P.tm[M_X0]);
  if (tid == 128) prefetch_tmap(&P.tm[M_WQKV]);
  if (tid == 256) { mbar_init(bar(B_FULL), 2); fence_bar_init(); fence_proxy_async_smem(); }
  const int wg = __shfl_sync(0xffffffffu, tid >> 7, 0);
  const int w = __shfl_sync(0xffffffffu, (tid >> 5) & 3, 0);
  const int lane = tid & 31;
  const uint32_t t_entry = clock_now();
  int b = blockIdx.x;
  if (BY_SM) {
    uint32_t smid; asm volatile("mov.u32 %0, %%smid;" : "=r"(smid));
    const int tp = smid >> 1;
    const int q7 = (tp - 32) * 37 >> 8;
    const int v0 = (tp & 7) * 8 + (tp >> 3), v1 = tp * 8 - 244 - q7 * 55, v2 = tp < 62 ? tp + 4 : tp - 58;
    b = (tp < 32 ? v0 : tp < 60 ? v1 : v2) * 2 + (smid & 1);
  }
  const int mg = (b >> 5) & 3, m = mg * 4 + (b & 3);
  const int c = ((b >> 2) & 7) ^ (BY_SM ? 0 : (mg & 1) * 7);
  const int row0 = (m & 7) * 128, par = m >> 3;
  if (__builtin_expect(b >= NCTA, 0)) { helper_cta(P, sc, b - NCTA, wg, w); return; }
  if (wg == 2 && w == 0) {
    if (elect_one()) {
      tma4d(SB, &P.tm[M_X0], 0, row0, 0, par, bar(B_FULL));
      tma4d(SB + 16384, &P.tm[M_WQKV], c * 64, 0, 0, 0, bar(B_FULL));
      mbar_expect_tx(bar(B_FULL), 40960);
      mbar_arrive(bar(B_FULL));
    }
    __syncwarp();
    TLW(0, 1);
  } else {
    const int g = wg * 4 + w - (wg == 2);
    if (elect_one()) {
#pragma unroll
      for (int x = 1; x < 10; x++) mbar_init(bar(x) + g * 72, g < 4 ? 2 : g == 4 ? 4 : 1);
      fence_bar_init();
      fence_proxy_async_smem();
    }
    __syncwarp();
  }
  if (__builtin_expect(wg == 2, 0)) {
    reg_dealloc<40>();
    if (w < 2) {
      if (w == 0) producer<false>(P, ops->a, NOP0, lane, c, row0, par, t_entry);
      else producer<true>(P, ops->b, NOP1, lane, c, row0, par, t_entry);
    } else if (w == 2) {
      if (smem_u32(smem_raw) != SB) __trap();
      __syncthreads();
      const uint32_t tag = ld_epoch(sc->epoch + b);
      uint32_t* const flag = sc->flags[m * 8 + c];
      if (lane < 4) asm volatile("st.relaxed.gpu.global.v4.u32 [%0], {%1, %1, %1, %1};" ::"l"(flag + lane * 4), "r"(tag * 32 - 1) : "memory");
      __syncwarp();
      int ev = 0;
      uint32_t t_st = t_entry;
#pragma unroll 1
      for (int t = 0; t < 21; t++) {
        const int i = t >= 11 ? t - 11 : t;
        const bool od = i == 2 || i == 10;
        const uint32_t sig = c_sched.task[t].sig;
        const uint32_t pf = i == 0 ? 1 << M_OL | 1 << M_O | 1 << M_WO : i == 1 ? 1 << M_O24 | 1 << M_W13 | 1 << M_W13P | 1 << M_YL | 1 << M_Y : i == 3 ? 1 << M_HL :
                            i == 7 ? 1 << M_H | 1 << M_W2 : i == 10 ? 1 << M_WQKV | 1 << M_YL | 1 << M_Y : 0;
        if ((pf >> lane) & 1) prefetch_tmap(&P.tm[lane]);
        __syncwarp();
        if (od) {
          asm volatile("{\n.reg .pred pe, pw;\n.reg .u32 it;\nsetp.eq.u32 pe, %4, 1;\nmov.u32 it, 0;\n"
                       "WAIT_%=:\nmbarrier.try_wait.parity.shared::cta.b64 pw, [%0], %1;\n@pw bra.uni GO_%=;\n"
                       "add.u32 it, it, 1;\nsetp.lt.u32 pw, it, 0x10000;\n@pw bra.uni WAIT_%=;\ntrap;\n"
                       "GO_%=:\nfence.proxy.async.global;\nfence.acq_rel.gpu;\n"
                       "@pe red.relaxed.gpu.global.add.u32 [%2], %4;\n@pe mbarrier.arrive.shared::cta.b64 _, [%3];\n}\n"
                       ::"r"(bar(B_SIG + 1)), "r"(sig >> 1), "l"(&sc->cnt[mg][ev] + lane), "r"(bar(B_PUB) + 8 * ev), "r"(lane + 1) : "memory");
          ev++;
          TLW(t, 4);
        }
        if (i == 1) {
          mbar_wait(bar(B_SIG), sig);
          fence_proxy_async_smem();
#pragma unroll 1
          for (int r = 8; r < 128; r += 32) tma4d_store(&P.tm[M_O24], SM_STG + r * 128, row0 + r, 8 + c, par);
        } else {
          const CUtensorMap* mp = &P.tm[i == 0 ? M_OL : od ? M_YL : M_HL];
          const uint32_t src = od ? SB + ((c_sched.task[t].stg >> 8) & 31) * 8192 : SM_STG;
          const int blk = (od ? 1 : i ? i - 3 : 0) * 8 + c, gap = i == 0 ? GAP_O : od ? GAP_Y : i == 9 ? GAP_H6 : GAP_H;
          const int nr = i && !od ? 64 : 128;
#pragma unroll 1
          for (int r0 = 0; r0 < 128; r0 += nr) {
            const int s = od ? 3 : i ? r0 >> 6 : 1;
            mbar_wait(bar(B_SIG) + 8 * s, sig >> s);
            if (od) mbar_wait(bar(B_DEP - 1) + 8 * ev, 0);
            fence_proxy_async_smem();
            const uint32_t now = clock_now();
            if ((int)(now - t_st) > 0) t_st = now;
#pragma unroll 1
            for (int r = r0; r < r0 + nr; r += PROWS) {
              delay_until(t_st, 0);
              t_st += gap;
              tma4d_store(mp, src + r * 128, row0 + r, blk, par);
            }
          }
        }
        if (elect_one()) { bulk_commit(); bulk_wait(); }
        __syncwarp();
        if (i == 1) mbar_wait(bar(B_SIG + 1), sig >> 1);
        if (elect_one()) {
          mbar_arrive(od ? bar(B_SF) : bar(B_FREE));
          if (i < 3 || i > 6) {
            asm volatile("fence.proxy.async.global;" ::: "memory");
            st_release(flag, tag * 32 + ev);
            mbar_arrive(bar(B_PUB) + 8 * ev);
          }
        }
        __syncwarp();
        if (i < 3 || i > 6) ev++;
        if (!od) TLW(t, 4);
      }
      if (lane == 0) sc->epoch[b] = tag;
    } else {
      __syncthreads();
      const uint32_t tag = ld_epoch(sc->epoch + b);
      delay_until(t_entry, WARM_T);
      asm volatile("st.shared.u32 [%0], %1;" ::"r"(SM_TAG + 4), "r"(reinterpret_cast<const uint32_t*>(&c_sched)[min(lane * 16, (int)sizeof(Sched) / 4 - 1)]) : "memory");
      int ncs = 0;
#pragma unroll 1
      for (int it = 0; it < 20; it++) {
        const int l = it >= 11, i = it - l * 11, e = i < 2 ? 0 : i - 2, ev = l * E_N + e;
#pragma unroll 1
        for (; ncs < (it < 2 ? it + 1 : it < 6 ? 2 : 9); ncs++) {
          uint4 v[2];
          ld_tag_wait<300>(v, &sc->cs[ncs][c][lane], tag);
          const uint32_t a = SM_CS + (ncs < 2 ? ncs * 768 : 512 + ncs * 512) + ((lane & 17) | (lane & 6) << 1 | (lane & 8) >> 2) * 4;
#pragma unroll
          for (int j = 0; j < 2; j++) {
            sts4f(a + j * 128, __uint_as_float(v[j].x)); sts4f(a + j * 128 + 256, __uint_as_float(v[j].y));
            if (ncs < 2) sts4f(a + j * 128 + 512, __uint_as_float(v[j].z));
          }
          mbar_arrive_warp(bar(B_CS) + 8 * ncs);
        }
        if (i == 0 || i == 2) {
          const int u = l * 2 + (i >> 1);
          uint4 v[6] = {};
          mbar_wait(bar(B_QT), u);
          if (m & 7) ld_tag_wait<0>(v, &sc->halo[u][m - 1][c][0][lane], tag);
          const uint32_t xa = xch(i, 0) + lane * 16;
          sts16(xa, v[0].x, v[0].y, v[0].z, v[1].x); sts16(xa + 512, v[1].y, v[1].z, v[2].x, v[2].y);
          sts16(xa + 1024, v[2].z, v[3].x, v[3].y, v[3].z); sts16(xa + 1536, v[4].x, v[4].y, v[4].z, v[5].x);
          if (lane < 4) sts16(stat(l * 2) - 64 + lane * 16, v[5].y, 0, v[5].z, 0);
          mbar_arrive_warp(bar(B_XCH));
          continue;
        }
        const bool all = e == E_YA || e == E_XA;
        const uint32_t* fp = all ? &sc->cnt[mg][ev] : sc->flags[m * 8 + (lane & 7)];
        uint32_t want = tag * 32 + (all ? 0 : ev);
        asm volatile("" : "+l"(fp), "+r"(want));
        mbar_wait(bar(B_PUB) + 8 * ev, 0);
        wait_flags(fp, want);
        mbar_arrive_warp(bar(B_DEP) + 8 * ev);
        if (e == E_YB || e == E_XB) {
          const int p = e == E_XB ? 1 : l * 2;
          if (elect_one()) {
            mbar_expect_tx(bar(B_SF + 1), 8192);
            asm volatile("cp.async.bulk.shared::cluster.global.mbarrier::complete_tx::bytes [%0], [%1], 8192, [%2];" ::"r"(SM_STG), "l"(&sc->stat[p][m][0][0]), "r"(bar(B_SF + 1)) : "memory");
          }
          __syncwarp();
          mbar_wait(bar(B_SF + 1), p);
#pragma unroll 1
          for (int h = 0; h < 2; h++) {
            float s0 = 0.f, q0 = 0.f, s1 = 0.f, q1 = 0.f;
#pragma unroll 4
            for (int j = 0; j < 8; j++) {
              float x0, x1, x2, x3;
              lds16f(SM_STG + j * 1024 + h * 512 + lane * 16, x0, x1, x2, x3);
              s0 += x0; q0 += x1; s1 += x2; q1 += x3;
            }
            const float2 r0 = ln_finish(s0, q0), r1 = ln_finish(s1, q1);
            sts16(stat(p + 1) + (h * 64 + lane * 2) * 8, __float_as_uint(r0.x), __float_as_uint(r0.y), __float_as_uint(r1.x), __float_as_uint(r1.y));
          }
          mbar_arrive_warp(bar(B_STAT) + 8 * (p + 1));
        }
      }
    }
  } else {
    const int tw = tid & 127;
    reg_alloc<232>();
    uint32_t sig;
    asm volatile("mov.u32 %0, %1;" : "=r"(sig) : "r"((uint32_t)(tw == 0)));
    __syncthreads();

    if (wg == 1) {
      const uint32_t tag = ld_epoch(sc->epoch + b);
      uint4* const mine = &sc->stat0[m][c * 16 + w * 4 + (lane >> 3)];
      if ((lane & 7) == 0) st_tag(mine, 0, 0, 0, 0);
      __syncwarp();
      delay_until(t_entry, ST_ROWS);
      const bf16* xr = x0 + (size_t)((row0 + c * 16 + w * 4 + (lane >> 3)) * 2 + par) * D_ + (lane & 7) * 8;
      float sum = 0.f, sq = 0.f;
#pragma unroll 1
      for (int j0 = 0; j0 < 16; j0 += 4) {
        uint4 xv[4];
#pragma unroll
        for (int j = 0; j < 4; j++) xv[j] = ldcg16(xr + (j0 + j) * 64);
#pragma unroll
        for (int j = 0; j < 4; j++) {
          const uint32_t x[4] = {xv[j].x, xv[j].y, xv[j].z, xv[j].w};
#pragma unroll
          for (int e = 0; e < 8; e++) { const float d = e & 1 ? bf_hi(x[e >> 1]) : bf_lo(x[e >> 1]); sum += d; sq = fmaf(d, d, sq); }
        }
      }
#pragma unroll
      for (int o = 4; o > 0; o >>= 1) { sum += __shfl_xor_sync(0xffffffffu, sum, o); sq += __shfl_xor_sync(0xffffffffu, sq, o); }
      const float2 fin = ln_finish(sum, sq);
      if ((lane & 7) == 0) st_tag(mine, __float_as_uint(fin.x), __float_as_uint(fin.y), 0, tag);
      __syncwarp();
      TL(22, 5);
      uint4 v[1];
      ld_tag_wait<200>(v, &sc->stat0[m][tw], tag);
      sts8f(stat(0) + tw * 8, __uint_as_float(v[0].x), __uint_as_float(v[0].y));
      if (tw == 0) { asm volatile("st.shared.u32 [%0], %1;" ::"r"(SM_TAG), "r"(tag) : "memory"); sts16(SM_ZERO, 0, 0, 0, 0); }
      mbar_arrive_warp(bar(B_STAT));
      TL(22, 6);
    }

    uint32_t sp = wg * NSEG;
#pragma unroll 1
    for (int t = wg; t < 22; t += 2) {
      const int l = t >= 11, i = t - l * 11;
      if (t == 0) TL(t, 0);
      if (i < 2) {
        float acc[2][96];
        if (w == 3 && (m & 7) < 7) {
#pragma unroll
          for (int j = 0; j < 6; j++) st_tag(&sc->halo[l * 2 + i][m][c][j][lane_now()], 0, 0, 0, 0);
        }
        uint32_t Q[4][8], K[4][8], V[4][8], sta, csa;
        float2 st[4];
        auto fix = [&](int g, int j, float2 cs) {
          const int mi = g & 1, half = g >> 1;
          return pack_bf16_v(fmaf(st[g].y, cs.x, acc[mi][j * 4 + half * 2]), fmaf(st[g].y, cs.y, acc[mi][j * 4 + half * 2 + 1]));
        };
        mainloop<0>(acc, sig, t, wg, sp, [&]() {
          const int lane = lane_now();
          mbar_wait(bar(B_FREE), l * 9 + i - 1);
          mbar_wait(bar(B_STAT) + l * 16, 0);
          mbar_wait(bar(B_CS) + i * 8, 0);
          sta = stat(l * 2) + w * 256;
          csa = SM_CS + i * 768 + (lane & 3) * 16;
          st[1] = lds8f(sta + (8 + (lane >> 2)) * 8); st[3] = lds8f(sta + (24 + (lane >> 2)) * 8);
        }, [&]() {
          const int lane = lane_now();
          mbar_arrive_if(bar(B_QT), sig);
#pragma unroll
          for (int j = 0; j < 8; j += 2) {
            float2 c0, c1;
            lds16f(csa + (16 + j) * 32, c0.x, c0.y, c1.x, c1.y);
            V[3][j] = movmat(fix(3, 16 + j, c0)); V[3][j + 1] = movmat(fix(3, 17 + j, c1));
            lds16f(csa + (8 + j) * 32, c0.x, c0.y, c1.x, c1.y);
            K[3][j] = fix(3, 8 + j, c0); K[3][j + 1] = fix(3, 9 + j, c1);
          }
          if (w < 3) {
            const uint32_t xa = xch(i, w + 1) + lane * 16;
            sts16(xa, K[3][0], K[3][1], K[3][2], K[3][3]); sts16(xa + 512, K[3][4], K[3][5], K[3][6], K[3][7]);
            sts16(xa + 1024, V[3][0], V[3][1], V[3][2], V[3][3]); sts16(xa + 1536, V[3][4], V[3][5], V[3][6], V[3][7]);
            mbar_arrive_warp(bar(B_XCH));
          } else if ((m & 7) < 7) {
            const uint32_t tag = lds4(SM_TAG), r0 = lds4(sta + (24 + 2 * (lane & 3)) * 8), r1 = lds4(sta + (25 + 2 * (lane & 3)) * 8);
            uint4* const p = &sc->halo[l * 2 + i][m][c][0][lane];
            st_tag(p, K[3][0], K[3][1], K[3][2], tag); st_tag(p + 32, K[3][3], K[3][4], K[3][5], tag); st_tag(p + 64, K[3][6], K[3][7], V[3][0], tag);
            st_tag(p + 96, V[3][1], V[3][2], V[3][3], tag); st_tag(p + 128, V[3][4], V[3][5], V[3][6], tag); st_tag(p + 160, V[3][7], r0, r1, tag);
          }
        });
        TL(t, 3);
        const int lane = lane_now(), q = lane & 3, r8 = lane >> 2;
        st[0] = lds8f(sta + r8 * 8); st[2] = lds8f(sta + (16 + r8) * 8);
#pragma unroll
        for (int j0 = 22; j0 >= 0; j0 -= 2) {
          float2 cs[2];
          lds16f(csa + j0 * 32, cs[0].x, cs[0].y, cs[1].x, cs[1].y);
#pragma unroll
          for (int j = j0; j < j0 + 2; j++)
#pragma unroll
            for (int g = 0; g < (j < 8 ? 4 : 3); g++) {
              const uint32_t pk = fix(g, j, cs[j - j0]);
              if (j < 8) Q[g][j] = pk; else if (j < 16) K[g][j - 8] = pk; else V[g][j - 16] = movmat(pk);
            }
        }
        const bool up0 = (2 * q) > r8, up1 = (2 * q + 1) > r8;
        const uint32_t mskP = (up0 ? 0xffffu : 0u) | (up1 ? 0xffff0000u : 0u);
        uint32_t ka0 = sta + q * 16 - (up0 ? 64 : 0), ka1 = sta + q * 16 + (up1 ? -56 : 8);
        asm volatile("" : "+r"(ka0), "+r"(ka1));
        TL(t, 5);
        uint32_t Kp[8] = {}, Vp[8] = {}, PS[2][4] = {}, PP[2][4] = {};
        float sS[2][4][2], sP[2][4][2] = {}, O[2][4][4][2], z0, z1, z2, z3;
        auto receive = [&]() {
          const uint32_t xa = xch(i, w) + lane * 16;
          mbar_wait(bar(B_XCH), i);
          lds16(xa, Kp[0], Kp[1], Kp[2], Kp[3]); lds16(xa + 512, Kp[4], Kp[5], Kp[6], Kp[7]);
          lds16(xa + 1024, Vp[0], Vp[1], Vp[2], Vp[3]); lds16(xa + 1536, Vp[4], Vp[5], Vp[6], Vp[7]);
          TL(i == 0 ? 22 : 23, t < 11 ? 3 : 4);
        };
        auto score = [&](float& s0, float& s1, float& s2, float& s3, int g, const uint32_t (&k)[8], int j, bool first) {
          mma16816(s0, s1, s2, s3, Q[g][j], Q[g + 1][j], Q[g][j + 1], Q[g + 1][j + 1], k[j], k[j + 1], first ? z0 : s0, first ? z1 : s1, first ? z2 : s2, first ? z3 : s3);
        };
        auto score0 = [&]() {
          float d[2][2];
#pragma unroll
          for (int x = 0; x < 4; x++) score(sP[x & 1][0][0], sP[x & 1][0][1], d[x & 1][0], d[x & 1][1], 0, Kp, (x & 1) * 4 + (x & 2), x < 2);
        };
        auto softmax = [&](int g) {
          const float rk0 = lds4f(ka0 + g * 64), rk1 = lds4f(ka1 + g * 64);
          const float f = st[g].x * (0.17677669529663687f * LOG2E), f0 = f * rk0, f1 = f * rk1;
          const bool noprev = g == 0 && (m & 7) == 0 && w == 0;
#pragma unroll
          for (int h = 0; h < 2; h++) {
            float v0 = (up0 ? sP[h][g][0] : sS[h][g][0]) * f0, v1 = (up1 ? sP[h][g][1] : sS[h][g][1]) * f1;
            if (noprev && up0) v0 = -1e9f * LOG2E;
            if (noprev && up1) v1 = -1e9f * LOG2E;
            float mx = fmaxf(v0, v1);
            mx = fmaxf(mx, __shfl_xor_sync(0xffffffffu, mx, 1)); mx = fmaxf(mx, __shfl_xor_sync(0xffffffffu, mx, 2));
            const float e0 = ex2f(v0 - mx), e1 = ex2f(v1 - mx);
            float sum = e0 + e1;
            sum += __shfl_xor_sync(0xffffffffu, sum, 1); sum += __shfl_xor_sync(0xffffffffu, sum, 2);
            const float inv = rcpf(sum);
            const uint32_t pk = pack_bf16_v(e0 * rk0 * inv, e1 * rk1 * inv);
            PS[h][g] = pk & ~mskP; PP[h][g] = pk & mskP;
          }
        };
        const uint32_t sa = SM_STG + (w * 32 + (lane & 7)) * 128 + (((lane >> 3) ^ (lane & 7)) << 4);
        auto stage = [&](int g) {
#pragma unroll
          for (int h = 0; h < 2; h++)
            stsm4t((sa ^ (h * 64)) + g * 1024, pack_bf16_v(O[h][g][0][0], O[h][g][0][1]), pack_bf16_v(O[h][g][1][0], O[h][g][1][1]),
                  pack_bf16_v(O[h][g][2][0], O[h][g][2][1]), pack_bf16_v(O[h][g][3][0], O[h][g][3][1]));
        };
        if (i == 0) { receive(); bar_sync(NB_PX, 256); }
        lds16f(SM_ZERO, z0, z1, z2, z3);
        if (i == 0) score0();
        {
          float d[2][2];
#pragma unroll
          for (int x = 0; x < 4; x++) {
            const int h = x & 1, j = h * 4 + (x & 2);
#pragma unroll
            for (int g = 0; g < 3; g++) score(sS[h][g][0], sS[h][g][1], sP[h][g + 1][0], sP[h][g + 1][1], g, K[g], j, x < 2);
            score(d[h][0], d[h][1], sS[h][3][0], sS[h][3][1], 2, K[3], j, x < 2);
          }
        }
        if (i == 0) { bar_arrive(NB_PY, 256); softmax(0); }
#pragma unroll
        for (int g = 1; g < 4; g++) softmax(g);
        TL(23, i == 0 ? (t < 11 ? 5 : 6) : 7);
        if (i == 0) bar_sync(NB_PX + ((PS[0][1] | PS[0][2] | PS[0][3] | PS[1][1] | PS[1][2] | PS[1][3]) & __float_as_uint(z0)), 256);
        lds16f(SM_ZERO, z0, z1, z2, z3);
        auto pv = [&](int g, const uint32_t (&vp)[8]) {
#pragma unroll
          for (int x = 0; x < 8; x += 2) {
            const int h = x >> 2, j = x & 3;
            mma16816(O[h][g][j][0], O[h][g][j][1], O[h][g][j + 1][0], O[h][g][j + 1][1], vp[x], vp[x + 1], V[g][x], V[g][x + 1], PP[h][g], PS[h][g], z0, z1, z2, z3);
          }
        };
        pv(1, V[0]); pv(3, V[2]); pv(2, V[1]);
        if (i) {
          stage(1); stage(2); stage(3);
          mbar_arrive_warp(bar(B_SIG));
          receive(); score0(); softmax(0);
        }
        pv(0, Vp);
        if (i == 0) { bar_arrive(NB_PY, 256); stage(1); stage(2); stage(3); stage(0); }
        else { stage(0); copy_out<2>(SM_STG + w * 4096, sc->o, par * (S_ * D_) + (row0 + w * 32) * 128 + (8 + c) * PANEL, 128, lane); }
        mbar_arrive_warp(bar(B_SIG + 1));
        if (i) bar_arrive(NB_OGO, 256);
        TL(t, 6);
      } else if (i > 2 && i < 10) {
        float acc[2][64];
        float2 cs[16];
        float hr[4];
        uint32_t so, sta;
        mainloop<1>(acc, sig, t, wg, sp, [&]() {
          const int lane = lane_now();
          so = SM_STG + (w * 16 + (lane & 7)) * 128 + (((lane >> 3) ^ (lane & 7)) << 4);
          sta = stat(l * 2 + 1) + (w * 16 + (lane >> 2)) * 8;
          mbar_wait(bar(B_STAT + 1) + l * 16, 0);
          mbar_wait(bar(B_CS - 1) + 8 * i, 0);
#pragma unroll
          for (int j = 0; j < 16; j += 2) lds16f(SM_CS + i * 512 + (lane & 3) * 16 + j * 32, cs[j].x, cs[j].y, cs[j + 1].x, cs[j + 1].y);
#pragma unroll
          for (int j = 0; j < 4; j++) hr[j] = 0.5f * lds4f(sta + (j >> 1) * 512 + (j & 1) * 64);
          mbar_wait(bar(B_FREE), l * 9 + i - 2);
        }, []() {});
        TL(t, 3);
        float mn[8];
#pragma unroll
        for (int x = 0; x < 2; x++) mn[x] = __uint_as_float(lds4(sta + 4 + (x >> 2) * 512 + ((x >> 1) & 1) * 64));
#pragma unroll
        for (int x = 0; x < 8; x++) {
          const int mi = x >> 2, half = (x >> 1) & 1, g = x & 1;
          uint32_t v[4];
#pragma unroll
          for (int j = 0; j < 4; j++) {
            const int jg = g * 4 + j + SWAP * 8, ju = jg ^ 8;
            const float2 cg = cs[jg], cu = cs[ju];
            const float g0 = fmaf(mn[x], cg.x, acc[mi][jg * 4 + half * 2]), g1 = fmaf(mn[x], cg.y, acc[mi][jg * 4 + half * 2 + 1]);
            const float u0 = fmaf(mn[x], cu.x, acc[mi][ju * 4 + half * 2]), u1 = fmaf(mn[x], cu.y, acc[mi][ju * 4 + half * 2 + 1]);
            const float a0 = g0 * hr[x >> 1], a1 = g1 * hr[x >> 1];
            v[j] = pack_bf16(fmaf(a0, tanhf_(a0), a0) * u0, fmaf(a1, tanhf_(a1), a1) * u1);
          }
          stsm4((so ^ (g * 64)) + (mi * 64 + half * 8) * 128, v[0], v[1], v[2], v[3]);
          if ((x & 3) == 3) mbar_arrive_warp(bar(B_SIG + mi));
          if (x + 2 < 8) mn[x + 2] = __uint_as_float(lds4(sta + 4 + ((x + 2) >> 2) * 512 + (((x + 2) >> 1) & 1) * 64));
        }
        TL(t, 6);
      } else {
        float acc[2][64], rsc[4];
        {
          const int lane = lane_now();
          const uint32_t e = c_sched.task[t].res;
          const uint32_t ra = SB + (w * 16 + (lane & 7)) * 128 + (((lane >> 3) ^ (lane & 7)) << 4);
          float sd[4];
#pragma unroll
          for (int j = 0; j < 4; j++) {
            rsc[j] = i == 10 ? lds4f(stat(l * 2 + 1) + ((j >> 1) * 64 + w * 16 + (j & 1) * 8 + (lane >> 2)) * 8) : 1.f;
            sd[j] = rcpf(rsc[j]);
          }
          const uint32_t zero = lds4(SM_ZERO);
          mbar_wait(bar(B_RES), i == 10);
          uint32_t dep[16];
#pragma unroll
          for (int x = 0; x < 16; x++) {
            const int mi = x >> 3, half = (x >> 2) & 1, g = x & 3;
            uint32_t v[4];
            ldsm4(((e >> ((g >> 1) * 8)) & 31) * 8192 + ((ra ^ ((g & 1) * 64)) | (x ? dep[x - 1] : 0)) + (mi * 64 + half * 8) * 128, v[0], v[1], v[2], v[3]);
#pragma unroll
            for (int j = 0; j < 4; j++) {
              asm volatile("shl.b32 %0, %1, 16;" : "=f"(acc[mi][(g * 4 + j) * 4 + half * 2]) : "r"(v[j]));
              asm volatile("and.b32 %0, %1, 0xffff0000;" : "=f"(acc[mi][(g * 4 + j) * 4 + half * 2 + 1]) : "r"(v[j]));
              acc[mi][(g * 4 + j) * 4 + half * 2] *= sd[mi * 2 + half]; acc[mi][(g * 4 + j) * 4 + half * 2 + 1] *= sd[mi * 2 + half];
            }
            asm("and.b32 %0, %1, %2;" : "=r"(dep[x]) : "f"(acc[mi][(g * 4 + 3) * 4 + half * 2 + 1]), "r"(zero));
          }
          mbar_arrive_warp(bar(B_RF));
        }
        auto stage = [&](int mi, int hi) {
          const int lane = lane_now();
          const uint32_t sw = SB + ((c_sched.task[t].stg >> (8 * hi)) & 31) * 8192 + (mi * 64 + w * 16) * 128, so = sw + (lane & 7) * 128 + (((lane >> 3) ^ (lane & 7)) << 4);
#pragma unroll
          for (int half = 0; half < 2; half++)
#pragma unroll
            for (int g = 0; g < 2; g++) {
              uint32_t v[4];
#pragma unroll
              for (int j = 0; j < 4; j++) {
                acc[mi][(hi * 8 + g * 4 + j) * 4 + half * 2] *= rsc[mi * 2 + half]; acc[mi][(hi * 8 + g * 4 + j) * 4 + half * 2 + 1] *= rsc[mi * 2 + half];
                v[j] = pack_bf16(acc[mi][(hi * 8 + g * 4 + j) * 4 + half * 2], acc[mi][(hi * 8 + g * 4 + j) * 4 + half * 2 + 1]);
              }
              stsm4((so ^ (g * 64)) + half * 1024, v[0], v[1], v[2], v[3]);
            }
          if (mi && !hi) mbar_arrive_warp(bar(B_SIG));
          if (hi == 0 || t == 21) {
            const int pitch = t == 21 ? D_ * 4 : 128;
            copy_out<4>(sw, t == 21 ? out : sc->y, (row0 + mi * 64 + w * 16) * pitch + (t == 21 ? par * (D_ * 2) + (hi * 8 + c) * 128 : par * (S_ * D_) + c * PANEL), pitch, lane);
          }
        };
        mainloop<2>(acc, sig, t, wg, sp, []() {}, [&]() { stage(0, 0); stage(0, 1); });
        TL(t, 3);
        stage(1, 0); mbar_arrive_warp(bar(B_SIG + 1));
        TL(t, 6);
        stage(1, 1); mbar_arrive_warp(bar(B_SIG + 2));
        if (t < 21) {
          const int lane = lane_now(), q = lane & 3;
          const uint32_t zero = lds4(SM_ZERO);
          float s[4], s2[4];
#pragma unroll
          for (int x = 0; x < 4; x++) {
            float a0 = x ? __uint_as_float(__float_as_uint(s[x - 1]) & zero) : 0.f, b0 = x ? __uint_as_float(__float_as_uint(s2[x - 1]) & zero) : 0.f;
#pragma unroll
            for (int j = 0; j < 32; j++) { const float d = acc[x >> 1][(j >> 1) * 4 + (x & 1) * 2 + (j & 1)]; a0 += d; b0 = fmaf(d, d, b0); }
            s[x] = a0; s2[x] = b0;
          }
#pragma unroll
          for (int x = 0; x < 2; x++) {
            s[x] = (q & 2 ? s[x + 2] : s[x]) + __shfl_xor_sync(0xffffffffu, q & 2 ? s[x] : s[x + 2], 2);
            s2[x] = (q & 2 ? s2[x + 2] : s2[x]) + __shfl_xor_sync(0xffffffffu, q & 2 ? s2[x] : s2[x + 2], 2);
          }
          const float r = (q & 1 ? s[1] : s[0]) + __shfl_xor_sync(0xffffffffu, q & 1 ? s[0] : s[1], 1);
          const float r2 = (q & 1 ? s2[1] : s2[0]) + __shfl_xor_sync(0xffffffffu, q & 1 ? s2[0] : s2[1], 1);
          asm volatile("st.global.v2.f32 [%0], {%1, %2};" ::"l"(&sc->stat[i == 10 ? 1 : l * 2][m][c][(q >> 1) * 64 + w * 16 + (q & 1) * 8 + (lane >> 2)]), "f"(r), "f"(r2) : "memory");
          mbar_arrive_warp(bar(B_SIG + 3));
        }
      }
    }
  }
}

typedef CUresult (*PFN_encodeTiled)(CUtensorMap*, CUtensorMapDataType, cuuint32_t, void*, const cuuint64_t*, const cuuint64_t*, const cuuint32_t*,
                                    const cuuint32_t*, CUtensorMapInterleave, CUtensorMapSwizzle, CUtensorMapL2promotion, CUtensorMapFloatOOBfill);

void make_map(PFN_encodeTiled enc, CUtensorMap* mp, const void* ptr, int rank, const cuuint64_t* gd, const cuuint64_t* gs, const cuuint32_t* bd) {
  const cuuint32_t es[4] = {1, 1, 1, 1};
  enc(mp, CU_TENSOR_MAP_DATA_TYPE_BFLOAT16, rank, const_cast<void*>(ptr), gd, gs, bd, es, CU_TENSOR_MAP_INTERLEAVE_NONE, CU_TENSOR_MAP_SWIZZLE_128B,
      CU_TENSOR_MAP_L2_PROMOTION_L2_128B, CU_TENSOR_MAP_FLOAT_OOB_FILL_NONE);
}
void make_map_act(PFN_encodeTiled enc, CUtensorMap* mp, const void* ptr, uint64_t cols, uint64_t s1, uint64_t s2, uint64_t s3, uint32_t rows) {
  const cuuint64_t gd[4] = {64, S_ / 2, cols / 64, 2}, gs[3] = {s1, s2, s3};
  const cuuint32_t bd[4] = {64, rows, 1, 1};
  make_map(enc, mp, ptr, 4, gd, gs, bd);
}
void make_map_w(PFN_encodeTiled enc, CUtensorMap* mp, const void* ptr, uint64_t rows, uint64_t cols, uint32_t np, uint64_t sp, uint64_t tiles, uint32_t nt) {
  const cuuint64_t gd[4] = {512, rows, np, tiles}, gs[3] = {cols * 2, sp, 1024};
  const cuuint32_t bd[4] = {64, 64, np, nt};
  make_map(enc, mp, ptr, 4, gd, gs, bd);
}

}

extern "C" void kernel_launch(void* const* d_in, const int* in_sizes, int n_in, void* d_out, int out_size) {
  (void)in_sizes; (void)n_in; (void)out_size;
  static PFN_encodeTiled enc = nullptr;
  static void *p_sc, *p_ops, *p_w;
  static int by_sm = 0;
  void (*const kernels[4])(Scratch*, const Ops*, const bf16*, bf16*, Params) = {fused_kernel<0, 0>, fused_kernel<1, 0>, fused_kernel<0, 1>, fused_kernel<1, 1>};
  if (!enc) {
    void* fn = nullptr; cudaDriverEntryPointQueryResult qr;
    cudaGetDriverEntryPoint("cuTensorMapEncodeTiled", &fn, cudaEnableDefault, &qr);
    enc = (PFN_encodeTiled)fn;
    cudaGetSymbolAddress(&p_sc, g_sc); cudaGetSymbolAddress(&p_ops, g_ops); cudaGetSymbolAddress(&p_w, g_w13);
    for (int i = 0; i < 4; i++) cudaFuncSetAttribute(kernels[i], cudaFuncAttributeMaxDynamicSharedMemorySize, SM_TOTAL);
    int dev = 0, sms = 0;
    cudaGetDevice(&dev);
    cudaDeviceGetAttribute(&sms, cudaDevAttrMultiProcessorCount, dev);
    by_sm = sms == NCTA + NHELP;
    for (int i = 1; i < 4 && by_sm; i++) {
      cudaLaunchConfig_t cfg = {};
      cudaLaunchAttribute at;
      at.id = cudaLaunchAttributeClusterDimension; at.val.clusterDim.x = 1 << i; at.val.clusterDim.y = at.val.clusterDim.z = 1;
      cfg.gridDim = dim3(NCTA); cfg.blockDim = dim3(384); cfg.dynamicSmemBytes = SM_TOTAL; cfg.attrs = &at; cfg.numAttrs = 1;
      int n = 0;
      if (cudaOccupancyMaxActiveClusters(&n, kernels[0], &cfg) != cudaSuccess) { (void)cudaGetLastError(); n = 0; }
      by_sm = n == (i == 1 ? 66 : i == 2 ? 30 : 15);
    }
  }
  Params P;
  Scratch* const sc = (Scratch*)p_sc;
  make_map_act(enc, &P.tm[M_X0], d_in[0], D_, D_ * 4, 128, D_ * 2, 128);
  make_map_act(enc, &P.tm[M_O], sc->o, D_, 128, PANEL, S_ * D_, 128);
  make_map_act(enc, &P.tm[M_Y], sc->y, D_, 128, PANEL, S_ * D_, 128);
  make_map_act(enc, &P.tm[M_H], sc->h, F_, 128, PANEL, S_ * F_, 128);
  make_map_act(enc, &P.tm[M_OL], sc->o, D_, 128, PANEL, S_ * D_, PROWS);
  make_map_act(enc, &P.tm[M_YL], sc->y, D_, 128, PANEL, S_ * D_, PROWS);
  make_map_act(enc, &P.tm[M_HL], sc->h, F_, 128, PANEL, S_ * F_, PROWS);
  make_map_act(enc, &P.tm[M_O24], sc->o, D_, 128, PANEL, S_ * D_, 24);
  make_map_w(enc, &P.tm[M_WQKV], d_in[1], D_, 3 * D_, 3, D_ * 2, 2, 1);
  make_map_w(enc, &P.tm[M_WO], d_in[2], D_, D_, 2, 1024, 1, 1);
  make_map_w(enc, &P.tm[M_W2], d_in[6], F_, D_, 2, 1024, 1, 1);
  const char *w1 = (const char*)d_in[4], *w3 = (const char*)d_in[5];
  if (w1 == w3 || (uint64_t)(w1 < w3 ? w3 - w1 : w1 - w3) >> 39) {
    cudaMemcpyAsync(p_w, w1, (size_t)D_ * F_ * 2, cudaMemcpyDeviceToDevice);
    cudaMemcpyAsync((bf16*)p_w + D_ * F_, w3, (size_t)D_ * F_ * 2, cudaMemcpyDeviceToDevice);
    w1 = (const char*)p_w; w3 = w1 + (size_t)D_ * F_ * 2;
  }
  const bool swap = w3 < w1;
  make_map_w(enc, &P.tm[M_W13], swap ? w3 : w1, D_, F_, 2, swap ? w1 - w3 : w3 - w1, 7, 1);
  make_map_w(enc, &P.tm[M_W13P], swap ? w3 : w1, D_, F_, 2, swap ? w1 - w3 : w3 - w1, 7, 2);
  kernels[by_sm * 2 + swap]<<<NCTA + NHELP, 384, SM_TOTAL>>>(sc, (const Ops*)p_ops, (const bf16*)d_in[0], (bf16*)d_out, P);
}
```

```cpp
#include <cuda_runtime.h>
#include <cuda_bf16.h>
#include <cuda.h>
#include <stdint.h>
#include <stddef.h>

typedef __nv_bfloat16 bf16;
#define GU_E 4
#define G_N1 8
#define Q_P1 4
#define Q_P2 6
#define Q_P0 1
#define RES_O 3
#define RES_D 2
#define HOLD_O 6
#define PROWS 16
#define GAP_O 150
#define GAP_Y 100
#define GAP_H 350
#define GAP_H6 1000
#define ST_T1 600
#define ST_D1 700
#define ST_ROWS 3500
#define WARM_T 4000
#define G_HOLD 2
#define D_PAD 0
#define GAP_H0 150
#define RLA 3
constexpr int TAILQ = 1, TAIL = 2;

namespace {

constexpr int S_ = 2048, D_ = 1024, F_ = 3584;
constexpr int PANEL = S_ / 2 * 128;
constexpr int NCTA = 128;
constexpr int NHELP = 4;

constexpr uint32_t SB = 1024;
constexpr int NU = 25;
constexpr uint32_t SM_STG  = SB + NU * 8192;
__host__ __device__ constexpr uint32_t xch(int i, int w) { return i ? SM_STG - 8192 + w * 2048 : SM_STG + w * 4096; }
constexpr uint32_t BARS    = SM_STG + 16384;
constexpr uint32_t SM_STAT = BARS + 896;
__host__ __device__ constexpr uint32_t stat(int set) { return SM_STAT + set * 1088 + 64; }
constexpr uint32_t SM_CS   = SM_STAT + 4352;
constexpr uint32_t SM_END  = SM_CS + 5120;
constexpr int SM_TOTAL = SM_END - SB;
static_assert(BARS % 1024 == 0 && SM_TOTAL <= 232448, "smem");
constexpr int B_FULL = 0, B_EMPTY = 16, B_SIG = 37, B_XCH = 41, B_RF = 42, B_STAT = 45, B_TURN = 49, B_RES = 51, B_FREE = 52, B_SF = 53, B_QT = 55, B_PASS = 56,
              B_CS = 57, B_DEP = 66, B_PUB = 82, B_FR0 = 98, B_N = 100;
__host__ __device__ constexpr uint32_t bar(int i) { return BARS + 8 * i; }
constexpr uint32_t SM_TAG = BARS + 8 * B_N, SM_ZERO = SM_TAG + 16;
constexpr int NB_PX = 1, NB_PY = 2, NB_OGO = 3, NB_END = 4;

constexpr int E_O0 = 0, E_O1 = 1, E_YA = 2, E_YB = 3, E_H4 = 4, E_XA = 7, E_XB = 8, E_N = 9;

constexpr int M_X0 = 0, M_O = 1, M_Y = 2, M_H = 3;
constexpr int M_WQKV = 4, M_WO = 5, M_W13 = 6, M_W1 = 7, M_W3 = 8, M_W2 = 9;
constexpr int M_OL = 10, M_YL = 11, M_HL = 12, M_O24 = 13, M_N = 14;

constexpr int FIRST = 5;
constexpr int NOPA = 416, NOPB = 416, NSEG = 48;
constexpr uint32_t A_END = 1, A_TURN = 2, A_DRAIN = 4, A_WAIT = 8, A_SYNC = 16;
constexpr uint32_t A_MARK = 0;
constexpr uint32_t phases(bool turn) {
  uint32_t r = 0, n[2] = {turn ? 0u : 1u, 0};
  for (int t = turn; t < 22; t++) if (turn ? t % 11 < 8 || t % 11 == 10 : t % 11 < 8 && t % 11 != 2) r |= (n[turn ? t & 1 : 0]++ & 1) << t;
  return r;
}
constexpr uint32_t TURN_PH = phases(true), FREE_PH = phases(false);
struct Task { uint32_t stg, res, sig; };
struct Seg { uint32_t i8, end8, a, b; };
constexpr uint32_t LO_A = 0x10000 + SB / 16, LO_B = 0x2000000 + SB / 16;
struct Sched { Seg seg[2 * NSEG]; Task task[22]; };
struct Ops { uint2 a[NOPA + 64], b[NOPB + 64]; };
struct Gen {
  Sched s{}; Ops o{};
  int n[2] = {0, 0}, nseg[2] = {0, NSEG}, cur = -1, pos = 0, err = 0, res = 0, nres = 0, single = 0;
  int mask[400] = {}, sa[400] = {}, sb[400][2] = {}, own[NU][2] = {}, tok[NU] = {}, known[2][2] = {{-1, -1}, {-1, -1}};
  constexpr void emit(int p, int wait, int par, int dst, int map, int kb8, int arr, int load, int y) {
    if (cur < FIRST) return;
    const uint2 e{(uint32_t)((p ? ((y >> 10) & 7) | (y >> 13) << 22 | (load ? map - M_WQKV : 0) << 3 | (y & 63) << 6 : (y & 63) | (y >> 10) << 6 | map << 7) | load << 12 | dst << 13 | (res ? B_RES : B_FULL + (cur & 15)) << 18 | wait << 24) | (uint32_t)(par & 1) << 31,
                  (uint32_t)(((y >> 6) & 15) | arr << 4 | (!p && arr && mask[cur] != 3 && !res) << 5 | ((cur + 2) & 15) << 9 | kb8 << 13)};
    if (p) o.b[n[1]++] = e; else o.a[n[0]++] = e;
  }
  constexpr bool done(int p, int x) const { return x < 0 || ((!(mask[x] & 1) || known[p][0] >= x) && (!(mask[x] & 2) || known[p][1] >= x)); }
  constexpr void op(int p, int dst, int nu, int map, int kb8, int arr, int y, int xw = -1, int xp = 0) {
    int w[8] = {}, wp[8] = {}, nw = 0;
    if (xw >= 0) { w[nw] = xw; wp[nw++] = xp; }
    for (int u = dst; u < dst + nu; u++) if (tok[u] && (u == dst || tok[u] != tok[u - 1])) { w[nw] = (tok[u] - 1) >> 1; wp[nw++] = tok[u] - 1; }
    for (int x = cur - 1; x >= 0; x--) {
      bool need = x <= cur - 12;
      for (int u = dst; u < dst + nu; u++) need = need || own[u][0] == x + 1 || own[u][1] == x + 1;
      if (!need || done(p, x)) continue;
      if (cur - x >= 16 || !done(p, x - 16)) err |= 1;
      w[nw] = B_EMPTY + ((x + 2) & 15); wp[nw++] = x >> 4;
      for (int g = 0; g < 2; g++) if (((mask[x] >> g) & 1) && known[p][g] < x) known[p][g] = x;
    }
    for (; nw > 1; nw--) emit(p, w[nw - 1], wp[nw - 1], 0, 0, 0, 0, 0, 0);
    emit(p, nw ? w[0] : B_PASS, nw ? wp[0] : 1, dst, map, kb8, arr, nu > 0, y);
    for (int u = dst; u < dst + nu; u++) { own[u][0] = cur + 1; own[u][1] = 0; tok[u] = 0; }
  }
  constexpr int step(int m) { mask[++cur] = m; return cur; }
  constexpr int slot() { int u = (pos + 1) & ~1; if (u >= 24) u = 0; pos = u + 2; return u; }
  constexpr int alloc(int nu) { if (pos + nu > 24) pos = 0; pos += nu; return pos - nu; }
  constexpr int qslot() { int u = (pos + 4) / 5 * 5; if (u >= NU) u = 0; pos = u + 5; return u; }
  constexpr void stage(int u, int first, int t) {
    first -= TAIL;
    for (int x = u; x < u + 2; x++) { if (own[x][0] > first || own[x][1] > first || tok[x]) err |= 2; own[x][0] = cur + 1; own[x][1] = 0; tok[x] = t; }
  }
  static constexpr int kown(int hi) { return hi * 8 | 1 << 9; }
  static constexpr int kskip(int hi, int j) { return (hi * 8 + j) | (j + 1) << 6; }
  static constexpr int kpos(int p) { return p < 2 ? kown(p) : p < 9 ? kskip(0, p - 2) : kskip(1, p - 9); }
  constexpr void segs(int t, const int* st, const uint32_t* act, int cnt, int tail, int inc0) {
    const int g = t & 1, wrap = inc0 == 5 ? NU : 24;
    int j0 = 0;
    for (int j = 0; j < cnt; j++) {
      const int x = st[j], inc = inc0 ? inc0 : j0 + 1 < cnt ? (sa[st[j0 + 1]] - sa[st[j0]] + wrap) % wrap : 0;
      const bool next = j + 1 < cnt && st[j + 1] == x + 1 && sa[x + 1] == (sa[x] + inc) % wrap && sb[x + 1][g] == (sb[x][g] + inc) % wrap;
      if (j >= cnt - tail - 1 && j + 1 < cnt && !next) err |= 4;
      if (j + 1 < cnt && st[j + 1] != x + 1 && !(act[j] & A_DRAIN)) err |= 8;
      if (j >= cnt - tail || (next && !act[j] && j != cnt - tail - 1)) continue;
      if (j == j0 && (j == 0 || (inc0 != 4 && (act[j - 1] & (A_DRAIN | A_SYNC))))) { if (inc0 || act[j]) err |= 16; single |= t % 11 == 7 ? 1 : 2; }
      const int y = st[j0];
      s.seg[nseg[g]++] = Seg{(uint32_t)y * 8 | (act[j] | (j == cnt - tail - 1 ? A_END : 0)) << 16, (uint32_t)(x + 1) * 8 | inc * 512 << 16, LO_A + sa[y] * 512, LO_B + sb[y][g] * 512};
      j0 = j + 1;
    }
  }
  constexpr void residual(int t, int map, bool q) {
    const int u0 = q ? qslot() : slot(), u1 = q ? u0 + 2 : slot();
    res = 1;
    op(0, u0, 2, map, 4, 1, kown(0)); op(0, u1, 2, map, 0, 0, kown(1));
    res = 0;
    for (int x = 0; x < 4; x++) { const int u = (x < 2 ? u0 : u1) + (x & 1); own[u][0] = 0; tok[u] = 1 + B_RF * 2 + (nres & 1); }
    nres++;
    s.task[t].res = u0 | u1 << 8;
  }
  constexpr Gen() {
    int cs[4] = {};
    for (int t = 0; t < 22; t++) {
      const int i = t % 11, use = i == 0 ? 2 : i == 1 || i == 7 ? 3 : i == 3 || i == 5 ? 9 : i == 8 || i == 9 ? 0 : 15;
      for (int x = 0; x < 4; x++) if ((use >> x) & 1) s.task[t].sig |= (cs[x]++ & 1) << x;
    }
    for (int l = 0; l < 2; l++) {
      const int T = l * 11, dep = B_DEP + l * E_N;
      int st[7][56] = {};
      uint32_t act[7][56] = {};
      if (l == 1) {
        const int first = cur + 1;
        for (int j = 0; j < 4; j++) {
          const int x = st[j >> 1][j & 1] = step(1 << ((T + (j >> 1)) & 1)), u = qslot();
          sb[x][0] = sb[x][1] = u + 2;
          if (j < 2) {
            sa[x] = (u + 5) % NU; stage(sa[x], first, j ? 1 + B_SF * 2 + 1 : 0); s.task[10].stg |= sa[x] << (8 * j);
            op(0, 0, 0, 0, 0, 1, 1 << 10, B_SIG + 2 * j, s.task[10].sig >> (2 * j));
          }
          else { sa[x] = sa[x - 2]; own[sa[x]][1] = own[sa[x] + 1][1] = x + 1; op(0, 0, 0, 0, 0, 1, 0); }
          op(1, u + 2, 3, M_WQKV, 3, 1, kown(j & 1) | (j >> 1) << 10);
        }
        act[0][1] = A_DRAIN; act[1][1] = A_DRAIN | A_WAIT;
      }
      for (int i = 0; i < 2; i++) {
        for (int j = 2 * l; j < 16; j++) {
          if (i && j == 16 - RES_O) residual(T + 2, l ? M_Y : M_X0, true);
          const int x = st[i][j] = step(1 << ((T + i) & 1)), u = qslot(), k = l ? kpos(j) : j;
          sa[x] = u; sb[x][0] = sb[x][1] = u + 2;
          op(0, u, 2, l ? M_Y : M_X0, 2, 1, k, l && i == 0 && (j == 2 || j == 9) ? B_DEP + (j == 2 ? E_XA : E_XB) : -1);
          op(1, u + 2, 3, M_WQKV, 3, 1, k | i << 10);
        }
        if (i) act[1][Q_P1 - 1 + (l ? 2 : Q_P0)] = act[1][Q_P2 - 1 + (l ? 2 : Q_P0)] = A_SYNC;
        if (i && own[NU - 1][0] > cur - TAILQ) err |= 256;
        segs(T + i, st[i], act[i], 16, TAILQ, 5);
      }
      for (int j = 0; j < 16; j++) {
        const int x = st[0][j] = step(1 << (T & 1)), k = j < 8 ? j : j == 8 ? kown(1) : kskip(1, j - 9), hold = j == HOLD_O ? B_PUB + l * E_N + E_O1 : -1;
        act[0][j] = j == 8 ? A_MARK : 0;
        if (j != 8) { sa[x] = slot(); op(0, sa[x], 2, M_O, 2, 1, k, j == 0 ? dep + E_O0 : j == 9 ? dep + E_O1 : hold); }
        else { sa[x] = NU; op(0, 0, 0, 0, 0, 1, 1 << 10, B_SIG + 1, s.task[T + 1].sig >> 1); }
        sb[x][0] = sb[x][1] = slot();
        op(1, sb[x][0], 2, M_WO, 2, 1, k, hold);
      }
      segs(T + 2, st[0], act[0], 16, TAIL, 4);
      int beg[6] = {0, 16}, end[5] = {16, 32 - G_N1}, cnt[5] = {}, ord = 0, pm = 0;
      for (int j = 2; j < 5; j++) { beg[j] = end[j - 2] + GU_E; end[j] = beg[j] + 16; }
      beg[5] = end[4];
      const int first = cur + 1;
      for (int j = 0; j < end[4]; j++) {
        int tl[2] = {-1, -1}, m = 0;
        for (int v = 0; v < 5; v++) if ((j >= beg[v] && j < end[v]) || (v == 1 && j < G_N1)) { const int g = (T + 3 + v) & 1; if (tl[g] >= 0) err |= 32; tl[g] = v; m |= 1 << g; }
        if (!m) err |= 32;
        if (j == end[4] - RES_D) residual(T + 10, M_Y, false);
        const int x = step(m), k = kpos(j < 16 ? j : (j + G_N1) & 15), v0 = m == 3 ? (tl[0] < tl[1] ? tl[0] : tl[1]) : tl[m >> 1];
        if (m != pm) {
          ord = 0;
          if (m == 3 && v0 < 3) { if ((0x92 >> (pos & 7)) & 1) pos++; ord = (pos & 7) == 5 ? 1 : (pos & 7) == 2 ? 2 : 0; }
          if (v0 == 4) { pos = (pos + 1) & ~1; for (int y = 0; y < (l ? 0 : D_PAD); y++) slot(); }
          pm = m;
        }
        int ub[2] = {}, n8 = 0;
        for (int y = 0, q = 0; y < (m == 3 ? 3 : 2); y++) {
          if (y == ord) sa[x] = alloc(2);
          else { const int nu = v0 + q < 4 ? 3 : 2; ub[q++] = alloc(nu); n8 += nu; }
        }
        if (j < 2) { stage(sa[x], first, j ? 1 + B_SF * 2 : 0); s.task[T + 2].stg |= sa[x] << (8 * j); op(0, 0, 0, 0, 0, 1, 1 << 10, B_SIG + 2 * j, s.task[T + 2].sig >> (2 * j)); }
        else op(0, sa[x], 2, M_Y, 2, 1, k, j == 2 ? dep + E_YA : j == 9 ? dep + E_YB : -1);
        for (int q = 0; q < (m == 3 ? 2 : 1); q++) {
          const int v = v0 + q, blk = (v >> 1) * 3 + (v & 1) * 2;
          op(1, ub[q], v < 4 ? 3 : 2, M_W13, q ? 0 : n8, !q, k | blk << 10 | (v < 4 ? 1 + (v & 1) : 0) << 13, j == G_HOLD && !q ? B_PUB + l * E_N + E_YA : -1);
          sb[x][(T + 3 + v) & 1] = ub[q];
          act[v][cnt[v]] = j == beg[v + 1] - 1 ? A_TURN : v == 1 && j == G_N1 - 1 ? A_DRAIN | A_WAIT : v == 0 && j == 1 ? A_MARK : 0;
          st[v][cnt[v]++] = x;
        }
      }
      for (int v = 0; v < 5; v++) { if (cnt[v] != 16) err |= 64; segs(T + 3 + v, st[v], act[v], 16, 0, 0); }
      for (int j = 0; j < 56; j++) {
        const int x = st[0][j] = step(1 << (T & 1));
        act[0][j] = 0;
        sa[x] = slot(); op(0, sa[x], 2, M_H, 2, 1, j, j == 0 ? dep + E_H4 : j == 32 ? dep + E_H4 + 1 : j == 48 ? dep + E_H4 + 2 : -1);
        sb[x][0] = sb[x][1] = slot(); op(1, sb[x][0], 2, M_W2, 2, 1, j);
      }
      segs(T + 10, st[0], act[0], 56, TAIL, 4);
    }
    { const int u0 = slot(), u1 = slot(); stage(u0, cur + 1, 0); stage(u1, cur + 1, 0); s.task[21].stg = u0 | u1 << 8; }
    if (n[0] > NOPA || n[1] > NOPB || nseg[0] >= NSEG || nseg[1] >= 2 * NSEG) err |= 128;
    for (int x = n[0]; x < NOPA + 64; x++) o.a[x] = uint2{B_PASS << 24 | 1u << 31, 0};
    for (int x = n[1]; x < NOPB + 64; x++) o.b[x] = uint2{B_PASS << 24 | 1u << 31, 0};
  }
};
constexpr Gen GEN{};
static_assert(GEN.err == 0, "schedule");
constexpr int NOP0 = (GEN.n[0] + 31) / 32 * 32, NOP1 = (GEN.n[1] + 31) / 32 * 32;

struct __align__(64) Params {
  CUtensorMap tm[M_N];
};

}

__constant__ Sched c_sched = GEN.s;
__device__ const Ops g_ops = GEN.o;
struct __align__(1024) Scratch {
  float2 stat[3][16][8][128];
  uint4 stat0[16][128];
  uint4 halo[4][16][8][6][32];
  uint4 cs[9][8][64];
  uint32_t flags[NCTA][32];
  uint32_t cnt[4][32];
  uint32_t epoch[NCTA + NHELP];
  __align__(1024) bf16 o[S_ * D_];
  bf16 y[S_ * D_], h[S_ * F_];
};
__device__ Scratch g_sc;
__device__ __align__(1024) bf16 g_w13[2 * D_ * F_];

#define TL(t, i) do {} while (0)
#define TS(i8, wg) do {} while (0)
#define TLW(t, i) do {} while (0)
#define MB_LIMIT (1 << 16)
#define FL_LIMIT (1 << 21)

namespace {

__device__ __forceinline__ uint32_t smem_u32(const void* p) { return (uint32_t)__cvta_generic_to_shared(p); }
__device__ __forceinline__ void mbar_init(uint32_t br, uint32_t cnt) { asm volatile("mbarrier.init.shared::cta.b64 [%0], %1;" ::"r"(br), "r"(cnt)); }
__device__ __forceinline__ void mbar_expect_tx(uint32_t br, uint32_t bytes) { asm volatile("mbarrier.arrive.expect_tx.shared::cta.b64 _, [%0], %1;" ::"r"(br), "r"(bytes) : "memory"); }
__device__ __forceinline__ void mbar_arrive(uint32_t br) { asm volatile("mbarrier.arrive.shared::cta.b64 _, [%0];" ::"r"(br) : "memory"); }
__device__ __forceinline__ void mbar_arrive_if(uint32_t br, uint32_t p) {
  asm volatile("{\n.reg .pred q;\nsetp.ne.u32 q, %1, 0;\n@q mbarrier.arrive.shared::cta.b64 _, [%0];\n}\n" ::"r"(br), "r"(p) : "memory");
}
__device__ __forceinline__ void mbar_arrive_warp(uint32_t br) {
  asm volatile("{\n.reg .pred q;\nbar.warp.sync 0xffffffff;\nelect.sync _|q, 0xffffffff;\n@q mbarrier.arrive.shared::cta.b64 _, [%0];\n}\n" ::"r"(br) : "memory");
}
__device__ __forceinline__ bool mbar_try_wait(uint32_t br, uint32_t parity) {
  uint32_t ok;
  asm volatile("{\n.reg .pred p;\nmbarrier.try_wait.parity.shared::cta.b64 p, [%1], %2;\nselp.u32 %0, 1, 0, p;\n}\n" : "=r"(ok) : "r"(br), "r"(parity) : "memory");
  return ok;
}
__device__ __forceinline__ void mbar_wait(uint32_t br, uint32_t parity) {
#pragma unroll 1
  for (int it = 0; it < MB_LIMIT; ++it) { if (mbar_try_wait(br, parity)) return; }
  __trap();
}
__device__ __forceinline__ bool elect_one() { uint32_t p; asm volatile("{\n.reg .pred P;\nelect.sync _|P, 0xffffffff;\nselp.u32 %0, 1, 0, P;\n}\n" : "=r"(p)); return p; }
__device__ __forceinline__ void fence_proxy_async_smem() { asm volatile("fence.proxy.async.shared::cta;" ::: "memory"); }
__device__ __forceinline__ void tma4d(uint32_t dst, const CUtensorMap* m, int c0, int c1, int c2, int c3, uint32_t br) {
  asm volatile("cp.async.bulk.tensor.4d.shared::cluster.global.mbarrier::complete_tx::bytes [%0], [%1, {%3, %4, %5, %6}], [%2];" ::"r"(dst), "l"(m), "r"(br), "r"(c0), "r"(c1), "r"(c2), "r"(c3) : "memory");
}
__device__ __forceinline__ void tma4d_store(const CUtensorMap* m, uint32_t src, int c1, int c2, int c3) {
  asm volatile("{\n.reg .pred p;\nelect.sync _|p, 0xffffffff;\n@p cp.async.bulk.tensor.4d.global.shared::cta.bulk_group [%0, {%5, %2, %3, %4}], [%1];\n}\n" ::"l"(m), "r"(src), "r"(c1), "r"(c2), "r"(c3), "r"(0) : "memory");
}
__device__ __forceinline__ void stsm4(uint32_t a, uint32_t x, uint32_t y, uint32_t z, uint32_t w) {
  asm volatile("stmatrix.sync.aligned.m8n8.x4.shared.b16 [%0], {%1,%2,%3,%4};" ::"r"(a), "r"(x), "r"(y), "r"(z), "r"(w) : "memory");
}
__device__ __forceinline__ void stsm4t(uint32_t a, uint32_t x, uint32_t y, uint32_t z, uint32_t w) {
  asm volatile("stmatrix.sync.aligned.m8n8.x4.trans.shared.b16 [%0], {%1,%2,%3,%4};" ::"r"(a), "r"(x), "r"(y), "r"(z), "r"(w) : "memory");
}
__device__ __forceinline__ void ldsm4(uint32_t a, uint32_t& x, uint32_t& y, uint32_t& z, uint32_t& w) {
  asm volatile("ldmatrix.sync.aligned.m8n8.x4.shared.b16 {%0,%1,%2,%3}, [%4];" : "=r"(x), "=r"(y), "=r"(z), "=r"(w) : "r"(a) : "memory");
}
__device__ __forceinline__ void st_tag(uint4* p, uint32_t a, uint32_t b, uint32_t c, uint32_t tag) {
  asm volatile("{\n.reg .b64 x, y;\n.reg .b128 z;\nmov.b64 x, {%1, %2};\nmov.b64 y, {%3, %4};\nmov.b128 z, {x, y};\nst.relaxed.gpu.global.b128 [%0], z;\n}\n" ::"l"(p), "r"(a), "r"(b), "r"(c), "r"(tag) : "memory");
}
__device__ __forceinline__ uint4 ld_tag(const uint4* p) {
  uint4 v;
  asm volatile("{\n.reg .b64 x, y;\n.reg .b128 z;\nld.relaxed.gpu.global.b128 z, [%4];\nmov.b128 {x, y}, z;\nmov.b64 {%0, %1}, x;\nmov.b64 {%2, %3}, y;\n}\n" : "=r"(v.x), "=r"(v.y), "=r"(v.z), "=r"(v.w) : "l"(p) : "memory");
  return v;
}
template <int NAP, int N> __device__ __forceinline__ void ld_tag_wait(uint4 (&v)[N], const uint4* p, uint32_t tag) {
#pragma unroll 1
  for (int it = 0; it < FL_LIMIT; ++it) {
    uint32_t bad = 0;
#pragma unroll
    for (int j = 0; j < N; j++) v[j] = ld_tag(p + j * 32);
#pragma unroll
    for (int j = 0; j < N; j++) bad |= v[j].w ^ tag;
    if (__all_sync(0xffffffffu, bad == 0)) return;
    if (NAP) __nanosleep(NAP);
  }
  __trap();
}
__device__ __forceinline__ void prefetch_tmap(const CUtensorMap* m) { asm volatile("prefetch.tensormap [%0];" ::"l"(m) : "memory"); }
__device__ __forceinline__ void wgmma_fence() { asm volatile("wgmma.fence.sync.aligned;" ::: "memory"); }
__device__ __forceinline__ void wgmma_commit() { asm volatile("wgmma.commit_group.sync.aligned;" ::: "memory"); }
template <int N> __device__ __forceinline__ void wgmma_wait() { asm volatile("wgmma.wait_group.sync.aligned %0;" ::"n"(N) : "memory"); }
template <int R> __device__ __forceinline__ void reg_alloc() { asm volatile("setmaxnreg.inc.sync.aligned.u32 %0;" ::"n"(R)); }
template <int R> __device__ __forceinline__ void reg_dealloc() { asm volatile("setmaxnreg.dec.sync.aligned.u32 %0;" ::"n"(R)); }
__device__ __forceinline__ void bar_sync(int id, int n) { asm volatile("bar.sync %0, %1;" ::"r"(id), "r"(n) : "memory"); }
__device__ __forceinline__ void bar_arrive(int id, int n) { asm volatile("bar.arrive %0, %1;" ::"r"(id), "r"(n) : "memory"); }
__device__ __forceinline__ uint32_t ld_acquire(const uint32_t* p) { uint32_t v; asm volatile("ld.acquire.gpu.global.u32 %0, [%1];" : "=r"(v) : "l"(p) : "memory"); return v; }
__device__ __forceinline__ void st_release(uint32_t* p, uint32_t v) { asm volatile("st.release.gpu.global.u32 [%0], %1;" ::"l"(p), "r"(v) : "memory"); }
__device__ __forceinline__ uint4 ldcg16(const void* p) { uint4 v; asm volatile("ld.global.cg.v4.u32 {%0,%1,%2,%3}, [%4];" : "=r"(v.x), "=r"(v.y), "=r"(v.z), "=r"(v.w) : "l"(p) : "memory"); return v; }
__device__ __forceinline__ float2 lds8f(uint32_t a) { float2 v; asm volatile("ld.shared.v2.f32 {%0,%1}, [%2];" : "=f"(v.x), "=f"(v.y) : "r"(a)); return v; }
__device__ __forceinline__ float lds4f(uint32_t a) { float v; asm volatile("ld.shared.f32 %0, [%1];" : "=f"(v) : "r"(a)); return v; }
__device__ __forceinline__ uint32_t lds4(uint32_t a) { uint32_t v; asm volatile("ld.shared.u32 %0, [%1];" : "=r"(v) : "r"(a) : "memory"); return v; }
__device__ __forceinline__ void lds16f(uint32_t a, float& x, float& y, float& z, float& w) { asm volatile("ld.shared.v4.f32 {%0,%1,%2,%3}, [%4];" : "=f"(x), "=f"(y), "=f"(z), "=f"(w) : "r"(a) : "memory"); }
__device__ __forceinline__ void sts8f(uint32_t a, float x, float y) { asm volatile("st.shared.v2.f32 [%0], {%1,%2};" ::"r"(a), "f"(x), "f"(y) : "memory"); }
__device__ __forceinline__ void sts4f(uint32_t a, float x) { asm volatile("st.shared.f32 [%0], %1;" ::"r"(a), "f"(x) : "memory"); }
__device__ __forceinline__ void sts16(uint32_t a, uint32_t x, uint32_t y, uint32_t z, uint32_t w) { asm volatile("st.shared.v4.u32 [%0], {%1,%2,%3,%4};" ::"r"(a), "r"(x), "r"(y), "r"(z), "r"(w) : "memory"); }
__device__ __forceinline__ void lds16(uint32_t a, uint32_t& x, uint32_t& y, uint32_t& z, uint32_t& w) { asm volatile("ld.shared.v4.u32 {%0,%1,%2,%3}, [%4];" : "=r"(x), "=r"(y), "=r"(z), "=r"(w) : "r"(a) : "memory"); }
__device__ __forceinline__ uint32_t pack_bf16(float a, float b) { uint32_t r; asm("cvt.rn.bf16x2.f32 %0, %1, %2;" : "=r"(r) : "f"(b), "f"(a)); return r; }
__device__ __forceinline__ uint32_t pack_bf16_v(float a, float b) { uint32_t r; asm volatile("cvt.rn.bf16x2.f32 %0, %1, %2;" : "=r"(r) : "f"(b), "f"(a)); return r; }
__device__ __forceinline__ float bf_lo(uint32_t v) { return __uint_as_float(v << 16); }
__device__ __forceinline__ float bf_hi(uint32_t v) { return __uint_as_float(v & 0xffff0000u); }
constexpr float LOG2E = 1.4426950408889634f;
__device__ __forceinline__ float ex2f(float x) { float y; asm("ex2.approx.ftz.f32 %0, %1;" : "=f"(y) : "f"(x)); return y; }
__device__ __forceinline__ float tanhf_(float x) { float y; asm("tanh.approx.f32 %0, %1;" : "=f"(y) : "f"(x)); return y; }
__device__ __forceinline__ float rcpf(float x) { float y; asm("rcp.approx.ftz.f32 %0, %1;" : "=f"(y) : "f"(x)); return y; }
__device__ __forceinline__ float bf_round(float a) { return bf_lo(pack_bf16(a, 0.f)); }
__device__ __forceinline__ uint32_t movmat(uint32_t a) { uint32_t d; asm volatile("movmatrix.sync.aligned.m8n8.trans.b16 %0, %1;" : "=r"(d) : "r"(a)); return d; }
__device__ __forceinline__ void mma16816(float& d0, float& d1, float& d2, float& d3, uint32_t a0, uint32_t a1, uint32_t a2, uint32_t a3, uint32_t b0, uint32_t b1,
                                         float c0, float c1, float c2, float c3) {
  asm volatile("mma.sync.aligned.m16n8k16.row.col.f32.bf16.bf16.f32 {%0,%1,%2,%3}, {%4,%5,%6,%7}, {%8,%9}, {%10,%11,%12,%13};"
               : "=f"(d0), "=f"(d1), "=f"(d2), "=f"(d3) : "r"(a0), "r"(a1), "r"(a2), "r"(a3), "r"(b0), "r"(b1), "f"(c0), "f"(c1), "f"(c2), "f"(c3));
}
template <int N> __device__ __forceinline__ void copy_out(uint32_t a, void* base, uint32_t ofs, int pitch, int lane) {
  a += (lane >> 3) * 128 + (((lane ^ (lane >> 3)) & 7) << 4);
  char* const g = static_cast<char*>(base) + (ofs + (lane >> 3) * pitch + (lane & 7) * 16);
  uint32_t v[N][4];
  __syncwarp();
#pragma unroll
  for (int j = 0; j < N; j++) lds16((a ^ ((j & 1) * 64)) + j * 512, v[j][0], v[j][1], v[j][2], v[j][3]);
#pragma unroll
  for (int j = 0; j < N; j++) asm volatile("st.global.v4.u32 [%0], {%1, %2, %3, %4};" ::"l"(g + j * 4 * pitch), "r"(v[j][0]), "r"(v[j][1]), "r"(v[j][2]), "r"(v[j][3]) : "memory");
}
__device__ __forceinline__ int lane_now() { int v; asm volatile("mov.u32 %0, %%laneid;" : "=r"(v)); return v; }
__device__ __forceinline__ uint32_t uni(uint32_t x, int lane) { return __shfl_sync(0xffffffffu, x + lane, 0); }
__device__ __forceinline__ uint64_t dsc(uint32_t hi, uint32_t lo) { return ((uint64_t)hi << 32) | lo; }

#define R8(a, o) "+f"(a[o]), "+f"(a[o + 1]), "+f"(a[o + 2]), "+f"(a[o + 3]), "+f"(a[o + 4]), "+f"(a[o + 5]), "+f"(a[o + 6]), "+f"(a[o + 7])
#define R32(a, o) R8(a, o), R8(a, o + 8), R8(a, o + 16), R8(a, o + 24)
#define REG64 "%0, %1, %2, %3, %4, %5, %6, %7, %8, %9, %10, %11, %12, %13, %14, %15, %16, %17, %18, %19, %20, %21, %22, %23, %24, %25, %26, %27, %28, %29, %30, %31, " \
              "%32, %33, %34, %35, %36, %37, %38, %39, %40, %41, %42, %43, %44, %45, %46, %47, %48, %49, %50, %51, %52, %53, %54, %55, %56, %57, %58, %59, %60, %61, %62, %63"
#define REG96 REG64 ", %64, %65, %66, %67, %68, %69, %70, %71, %72, %73, %74, %75, %76, %77, %78, %79, %80, %81, %82, %83, %84, %85, %86, %87, %88, %89, %90, %91, %92, %93, %94, %95"
__device__ __forceinline__ void wgmma(float (&d)[64], uint64_t da, uint64_t db) {
  asm volatile("wgmma.mma_async.sync.aligned.m64n128k16.f32.bf16.bf16 {" REG64 "}, %64, %65, 1, 1, 1, 0, 1;\n"
               : R32(d, 0), R32(d, 32) : "l"(da), "l"(db));
}
__device__ __forceinline__ void wgmma(float (&d)[96], uint64_t da, uint64_t db) {
  asm volatile("wgmma.mma_async.sync.aligned.m64n192k16.f32.bf16.bf16 {" REG96 "}, %96, %97, 1, 1, 1, 0, 1;\n"
               : R32(d, 0), R32(d, 32), R32(d, 64) : "l"(da), "l"(db));
}
#define W8(a, o) "=f"(a[o]), "=f"(a[o + 1]), "=f"(a[o + 2]), "=f"(a[o + 3]), "=f"(a[o + 4]), "=f"(a[o + 5]), "=f"(a[o + 6]), "=f"(a[o + 7])
#define W32(a, o) W8(a, o), W8(a, o + 8), W8(a, o + 16), W8(a, o + 24)
__device__ __forceinline__ void wgmma_z(float (&d)[64], uint64_t da, uint64_t db) {
  asm volatile("wgmma.mma_async.sync.aligned.m64n128k16.f32.bf16.bf16 {" REG64 "}, %64, %65, 0, 1, 1, 0, 1;\n"
               : W32(d, 0), W32(d, 32) : "l"(da), "l"(db));
}
__device__ __forceinline__ void wgmma_z(float (&d)[96], uint64_t da, uint64_t db) {
  asm volatile("wgmma.mma_async.sync.aligned.m64n192k16.f32.bf16.bf16 {" REG96 "}, %96, %97, 0, 1, 1, 0, 1;\n"
               : W32(d, 0), W32(d, 32), W32(d, 64) : "l"(da), "l"(db));
}

__device__ __forceinline__ void wgmma_cs(float (&d)[4], uint64_t da, uint64_t db) {
  asm volatile("wgmma.mma_async.sync.aligned.m64n8k16.f32.bf16.bf16 {%0, %1, %2, %3}, %4, %5, 1, 1, 1, 1, 0;\n" : "+f"(d[0]), "+f"(d[1]), "+f"(d[2]), "+f"(d[3]) : "l"(da), "l"(db));
}
__device__ __forceinline__ void bulk_commit() { asm volatile("cp.async.bulk.commit_group;" ::: "memory"); }
__device__ __forceinline__ void bulk_wait() { asm volatile("cp.async.bulk.wait_group 0;" ::: "memory"); }
__device__ __forceinline__ void fence_bar_init() { asm volatile("fence.mbarrier_init.release.cluster;" ::: "memory"); }

__device__ __forceinline__ uint32_t clock_now() { uint32_t v; asm volatile("mov.u32 %0, %%clock;" : "=r"(v)); return v; }
__device__ __forceinline__ void delay_until(uint32_t t0, int cycles) {
#pragma unroll 1
  for (int it = 0; it < 1000 && (int)(clock_now() - t0) < cycles; it++) __nanosleep(40);
}
__device__ __forceinline__ uint32_t ld_epoch(const uint32_t* p) { uint32_t v; asm volatile("ld.global.u32 %0, [%1];" : "=r"(v) : "l"(p) : "memory"); return v + 1; }
__device__ __forceinline__ void wait_flags(const uint32_t* f, uint32_t tag) {
#pragma unroll 1
  for (int it = 0; it < FL_LIMIT; ++it) if (__all_sync(0xffffffffu, (int)(ld_acquire(f) - tag) >= 0)) return;
  __trap();
}

__device__ __forceinline__ float2 ln_finish(float sum, float sq) {
  const float mean = sum * (1.f / D_), var = fmaxf(fmaf(-mean, mean, sq * (1.f / D_)), 0.f);
  const float mb = bf_round(mean);
  const float vb = bf_round(var);
  const float sd = bf_round(sqrtf(bf_round(vb + 1e-5f)));
  return make_float2(1.0f / sd, -mb);
}

__device__ __forceinline__ void helper_cta(const Params& P, Scratch* sc, int e, int wg, int w) {
  const int tid = threadIdx.x;
  if (tid == 256) {
#pragma unroll
    for (int i = 0; i < 16; i++) mbar_init(bar(i), 1);
    fence_bar_init();
  }
  if (tid < 64) sts16(SM_STG + tid * 16, 0x3f803f80u, 0x3f803f80u, 0x3f803f80u, 0x3f803f80u);
  fence_proxy_async_smem();
  __syncthreads();
  if (wg == 2) {
    if (w == 0) {
#pragma unroll 1
      for (int n = 0; n < 9 * 32; n++) {
        const int job = n >> 5;
        const uint32_t fb = bar(n & 7), dst = SB + (n & 7) * 24576;
        mbar_wait(bar(8 + (n & 7)), (n >> 3) + 1);
        if (elect_one()) {
          mbar_expect_tx(fb, job < 2 ? 24576 : 16384);
          tma4d(dst, &P.tm[job < 2 ? M_WQKV : M_W13], (e * 2 + (n & 1)) * 64, (n & 30) * 32, 0, job < 2 ? job : job - 2, fb);
        }
        __syncwarp();
      }
    }
  } else {
    const uint32_t tag = ld_epoch(sc->epoch + NCTA + e);
    const int lane = tid & 31;
#pragma unroll 1
    for (int job = 0; job < 9; job++) {
      float s[3][4] = {};
#pragma unroll 1
      for (int n = job * 32 + wg; n < job * 32 + 32; n += 2) {
        mbar_wait(bar(n & 7), n >> 3);
        wgmma_fence();
        const uint32_t a = ((SB + (n & 7) * 24576) >> 4) + 0x2000000;
#pragma unroll
        for (int k = 0; k < 8; k++) wgmma_cs(s[k & 1], dsc(0x40000040u, a + (k & 1) * 512 + (k >> 1) * 128), dsc(0x40000040u, (SM_STG >> 4) + 0x10000));
        if (job < 2) {
          wgmma_fence();
#pragma unroll
          for (int k = 0; k < 4; k++) wgmma_cs(s[2], dsc(0x40000040u, a + 1024 + k * 128), dsc(0x40000040u, (SM_STG >> 4) + 0x10000));
        }
        wgmma_commit();
        wgmma_wait<0>();
        mbar_arrive_if(bar(8 + (n & 7)), (tid & 127) == 0);
      }
      if (!(lane & 2))
        st_tag(&sc->cs[job][e * 2 + wg][w * 16 + (lane & 1) * 8 + (lane >> 2)], __float_as_uint(lane & 1 ? s[0][2] : s[0][0]), __float_as_uint(lane & 1 ? s[1][2] : s[1][0]),
               __float_as_uint(lane & 1 ? s[2][2] : s[2][0]), tag);
      __syncwarp();
    }
    bar_sync(NB_END, 256);
    if (tid == 0) sc->epoch[NCTA + e] = tag;
  }
}

template <bool WEIGHTS>
__device__ __forceinline__ void producer(const Params& P, const uint2* tab, int nop, int lane, int c, int row, int par, uint32_t t_entry) {
  uint64_t pol;
  asm volatile("createpolicy.fractional.L2::evict_first.b64 %0, 1.0;" : "=l"(pol));
  __syncthreads();
  uint2 nx = __ldg(tab + lane), n2 = __ldg(tab + 32 + lane);
#pragma unroll 1
  for (int j = 1; j < FIRST; j++) {
    delay_until(t_entry, ST_T1 + (j - 1) * ST_D1);
    if (elect_one()) {
      mbar_expect_tx(bar(B_FULL) + 8 * j, WEIGHTS ? 24576 : 16384);
      if (WEIGHTS) tma4d(SB + j * 40960 + 16384, &P.tm[M_WQKV], c * 64, j * 64, 0, 0, bar(B_FULL) + 8 * j);
      else tma4d(SB + j * 40960, &P.tm[M_X0], 0, row, j, par, bar(B_FULL) + 8 * j);
    }
    __syncwarp();
  }
  if (!WEIGHTS && lane == 0) {
#pragma unroll
    for (int j = 0; j < FIRST; j++) mbar_arrive(bar(B_EMPTY + 2 + j));
  }
  __syncwarp();
  auto word = [&](uint2 e) { return e.x + (((int)(e.y & 7) > c) + (e.y & 8 ? c : 0)) * (WEIGHTS ? 64 : 1); };
  uint32_t xn = __shfl_sync(0xffffffffu, word(nx), 0);
  const uint64_t maps = reinterpret_cast<uint64_t>(&P.tm[WEIGHTS ? M_WQKV : 0]);
  if ((uint32_t)maps > 0xfffffcffu) __trap();
  const uint32_t sb = uni(SB, lane), bars = uni(BARS, lane), zero = uni(0, lane), mlo = uni((uint32_t)maps, lane), mhi = uni(maps >> 32, lane);
#pragma unroll 1
  for (int base = 0; base < nop; base += 32) {
    const uint2 e = nx;
    nx = n2;
    n2 = __ldg(tab + base + 64 + lane);
    const uint32_t xw = word(lane ? e : nx), bytes = e.y & 0xe000, eb = (e.y >> 6) & 0x78;
    const int arr = e.y & 16 ? lane + 1 : 0, solo = e.y & 32 ? lane + 1 : 0;
#pragma unroll 1
    for (int j = 1; j <= 32; j++) {
      const uint32_t x = xn;
      xn = __shfl_sync(0xffffffffu, xw, j);
#define OP_WAIT(X) "{\n.reg .pred pe, pa, pn, ps, pw;\n.reg .u32 it;\n" \
                "elect.sync _|pe, 0xffffffff;\nsetp.eq.u32 pa, %0, %1;\nsetp.ne.and.u32 pn, %2, 0, pe;\n" X \
                "mov.u32 it, 0;\n" \
                "WAIT_%=:\n" \
                "mbarrier.try_wait.parity.shared::cta.b64 pw, [%3 + %9], %4;\n" \
                "@pw bra.uni GO_%=;\n" \
                "add.u32 it, it, 1;\nsetp.lt.u32 pw, it, 0x10000;\n" \
                "@pw bra.uni WAIT_%=;\n" \
                "trap;\n" \
                "GO_%=:\n"
#define OP_ARGS "r"(arr), "r"(j), "r"(x & (1 << 12)), "r"((x >> 21) & 0x3f8), "r"(x >> 31), "r"(((x >> 15) & (WEIGHTS ? 0x78 : 0x1f8)) | bars), "r"(bytes), "r"((x & 0x3e000) | sb), \
                "l"(dsc(mhi, mlo + (WEIGHTS ? (x & 0x38) * 16 : x & 0x180))), "n"(BARS), "r"(x & (WEIGHTS ? 0xfc0 : 63)), "r"(x & (WEIGHTS ? 7 : 64))
      if (WEIGHTS)
        asm volatile(OP_WAIT("setp.ne.and.u32 ps, %17, 0, pe;\n")
                     "@pn cp.async.bulk.tensor.4d.shared::cluster.global.mbarrier::complete_tx::bytes.L2::cache_hint [%7], [%8, {%12, %10, %13, %11}], [%5], %14;\n"
                     "@ps cp.async.bulk.tensor.4d.shared::cluster.global.mbarrier::complete_tx::bytes.L2::cache_hint [%15], [%16, {%12, %10, %13, %11}], [%5], %14;\n"
                     "@pa mbarrier.arrive.expect_tx.shared::cta.b64 _, [%5], %6;\n"
                     "}\n" ::OP_ARGS, "r"(c * 64), "r"(zero), "l"(pol), "r"(((x & 0x3e000) | sb) + 16384),
                     "l"(dsc(mhi, mlo + (M_W13 - M_WQKV) * 128 + ((x >> 15) & 0x180))), "r"((x >> 15) & 0x180) : "memory");
      else
        asm volatile(OP_WAIT(".reg .pred pf;\nsetp.ne.u32 pf, %11, 0;\nsetp.eq.u32 ps, %14, %1;\n")
                     "@pn cp.async.bulk.tensor.4d.shared::cluster.global.mbarrier::complete_tx::bytes [%7], [%8, {%17, %12, %10, %13}], [%5];\n"
                     "@pf fence.proxy.async.shared::cta;\n"
                     "@pa mbarrier.arrive.expect_tx.shared::cta.b64 _, [%5], %6;\n"
                     "@ps mbarrier.arrive.shared::cta.b64 _, [%15 + %16];\n"
                     "}\n" ::OP_ARGS, "r"(row), "r"(par), "r"(solo), "r"(eb), "n"(bar(B_EMPTY)), "r"(zero) : "memory");
    }
  }
}

template <int MODE, uint32_t LO> __device__ __forceinline__ void advance(uint32_t& x, uint32_t inc) {
  constexpr uint32_t LEN = (MODE == 0 ? NU : 24) * 512;
  x += inc; if (x >= LO + LEN) x -= LEN;
}
__device__ __forceinline__ bool full_test(uint32_t i8) {
  uint32_t ok;
  asm volatile("{\n.reg .pred p;\nmbarrier.test_wait.parity.shared::cta.b64 p, [%1 + %3], %2;\nselp.u32 %0, 1, 0, p;\n}\n" : "=r"(ok) : "r"(i8 & 0x78), "r"(i8 >> 7), "n"(bar(B_FULL)) : "memory");
  return ok;
}
__device__ __forceinline__ void full_wait(uint32_t i8) { mbar_wait(bar(B_FULL) + (i8 & 0x78), i8 >> 7); }
__device__ __forceinline__ void release(uint32_t i8, uint32_t p) {
  asm volatile("{\n.reg .pred q;\nsetp.ne.u32 q, %1, 0;\n@q mbarrier.arrive.shared::cta.b64 _, [%0 + %2];\n}\n" ::"r"(i8 & 0x78), "r"(p), "n"(bar(B_EMPTY)) : "memory");
}
template <int MODE, int RELK, int FIRSTK, int N>
__device__ __forceinline__ bool kstep(float (&acc)[2][N], uint32_t hiA, uint32_t hiB, uint32_t& a, uint32_t& b, uint32_t inc, uint32_t& i8, uint32_t x) {
  constexpr uint32_t MI = MODE == 0 ? 64 : 512;
  wgmma_fence();
  if (FIRSTK == 2) { wgmma_z(acc[0], dsc(hiA, a), dsc(hiB, b)); wgmma_z(acc[1], dsc(hiA, a + MI), dsc(hiB, b)); }
  else { wgmma(acc[0], dsc(hiA, a), dsc(hiB, b)); wgmma(acc[1], dsc(hiA, a + MI), dsc(hiB, b)); }
  i8 += 8;
  const bool ok = full_test(i8);
#pragma unroll
  for (int k = 1; k < 4; k++) {
    wgmma(acc[0], dsc(hiA, a + 2 * k), dsc(hiB, b + 128 * k)); wgmma(acc[1], dsc(hiA, a + MI + 2 * k), dsc(hiB, b + 128 * k));
    if (k == RELK || k == 3) wgmma_commit();
    if (k == 3) { advance<MODE, LO_A>(a, inc); advance<MODE, LO_B>(b, inc); }
    if (!FIRSTK && k == RELK) {
      wgmma_wait<1>();
      release(i8, x);
    }
  }
  return ok;
}
template <int MODE, int N, class F, class G>
__device__ __forceinline__ void mainloop(float (&acc)[2][N], uint32_t sig, int t, int wg, uint32_t& sp, F&& prepare, G&& first_half) {
  const uint32_t turn = bar(B_TURN) + 8 * (wg ^ 1);
  constexpr uint32_t hiA = MODE == 0 ? 0x40000080u : 0x40000040u, hiB = 0x40000040u;
  constexpr Seg S0 = GEN.s.seg[0];
  uint32_t i8 = S0.i8 & 0xffff, nxt = S0.end8 & 0xffff, a = S0.a, b = S0.b, inc = S0.end8 >> 16;
  if (MODE != 0 || t != 0) {
    if (MODE == 2 || (MODE == 0 ? t != 12 : t != 4 && t != 15)) mbar_wait(bar(B_TURN) + 8 * wg, TURN_PH >> t);
    i8 = c_sched.seg[sp].i8 & 0xffff; nxt = c_sched.seg[sp].end8 & 0xffff; a = c_sched.seg[sp].a; b = c_sched.seg[sp].b; inc = c_sched.seg[sp].end8 >> 16;
  }
  uint32_t hiA_ = MODE == 1 && N == 64 ? hiA : hiA + (a >> 31);
  full_wait(i8);
  TL(t, 2);
  TS(i8, wg);
  bool ok = kstep<MODE, 3, MODE == 2 ? 1 : 2>(acc, hiA_, hiB, a, b, inc, i8, 0);
  if (MODE == 2 && (t == 2 || t == 13)) bar_sync(NB_OGO, 256);
#pragma unroll 1
  while (true) {
    uint32_t act;
    if (MODE == 1 && N == 64) hiA_ = hiA + (a >> 31);
    constexpr bool SINGLE = MODE == 1 && (GEN.single & (N == 64 ? 1 : 2));
    if (SINGLE && i8 == nxt) { sp++; nxt = c_sched.seg[sp].end8 & 0xffff; a = c_sched.seg[sp].a; b = c_sched.seg[sp].b; inc = c_sched.seg[sp].end8 >> 16; }
#pragma unroll 1
    while (true) {
      if (!ok) full_wait(i8);
      TS(i8, wg);
      ok = kstep<MODE, MODE == 1 ? 1 : 3, 0>(acc, hiA_, hiB, a, b, inc, i8, sig);
      if (__builtin_expect(i8 == nxt, 0)) {
        act = c_sched.seg[sp++].i8 >> 16;
        if (MODE == 1) mbar_arrive_if(turn, sig & (act >> 1));
        if (act & (MODE == 0 ? A_END | A_DRAIN | A_SYNC : MODE == 1 ? A_END | A_DRAIN : A_END)) break;
        nxt = c_sched.seg[sp].end8 & 0xffff; a = c_sched.seg[sp].a; b = c_sched.seg[sp].b;
        if (MODE == 1) inc = c_sched.seg[sp].end8 >> 16;
      }
    }
    if (MODE == 2 || (MODE == 1 && N == 64) || (act & A_END)) break;
    nxt = c_sched.seg[sp].end8 & 0xffff; a = c_sched.seg[sp].a; b = c_sched.seg[sp].b;
    if (MODE == 1) inc = c_sched.seg[sp].end8 >> 16;
    if (MODE == 0 && (act & A_SYNC)) bar_arrive(NB_PX, 256);
    wgmma_wait<0>();
    release(i8 + 8, sig);
    i8 = c_sched.seg[sp].i8 & 0xffff;
    if (MODE == 1 || (act & A_WAIT)) mbar_wait(bar(B_TURN) + 8 * wg, TURN_PH >> t);
    full_wait(i8);
    if (MODE == 0 && (act & A_SYNC)) bar_sync(NB_PY, 256);
    TS(i8, wg);
    ok = kstep<MODE, 3, 1>(acc, hiA_, hiB, a, b, inc, i8, 0);
  }
  if (MODE != 1) {
    constexpr int TL_ = MODE == 0 ? TAILQ : TAIL;
    uint32_t ta[TL_], tb[TL_];
#pragma unroll
    for (int x = 0; x < TL_; x++) {
      full_wait(i8 + 8 * x);
      TS(i8 + 8 * x, wg);
      ta[x] = a; tb[x] = b;
      advance<MODE, LO_A>(a, inc); advance<MODE, LO_B>(b, inc);
    }
#pragma unroll
    for (int h = 0; h < 2; h++) {
      const int mi = MODE == 0 ? 1 - h : h;
      wgmma_fence();
#pragma unroll
      for (int x = 0; x < TL_; x++)
#pragma unroll
        for (int k = 0; k < 4; k++) wgmma(acc[mi], dsc(hiA, ta[x] + mi * (MODE == 0 ? 64 : 512) + 2 * k), dsc(hiB, tb[x] + 128 * k));
      wgmma_commit();
      if (TL_ > 1 && h == 0) { wgmma_wait<1>(); release(i8 + 8, sig); prepare(); }
    }
    mbar_arrive_if(turn, sig);
    if (TL_ == 1) { wgmma_wait<2>(); release(i8 + 8, sig); prepare(); }
    wgmma_wait<1>();
    first_half();
    wgmma_wait<0>();
#pragma unroll
    for (int x = 0; x < TL_; x++) release(i8 + 16 + 8 * x, sig);
  } else {
    prepare();
    wgmma_wait<0>();
    release(i8 + 8, sig);
  }
}

template <int SWAP, int BY_SM>
__global__ void __launch_bounds__(384, 1) fused_kernel(Scratch* sc, const Ops* ops, const bf16* x0, bf16* out, const __grid_constant__ Params P) {
  extern __shared__ __align__(1024) uint8_t smem_raw[];
  const int tid = threadIdx.x;
  if (tid == 0) prefetch_tmap(&P.tm[M_X0]);
  if (tid == 128) prefetch_tmap(&P.tm[M_WQKV]);
  if (tid == 256) { mbar_init(bar(B_FULL), 2); fence_bar_init(); fence_proxy_async_smem(); }
  const int wg = __shfl_sync(0xffffffffu, tid >> 7, 0);
  const int w = __shfl_sync(0xffffffffu, (tid >> 5) & 3, 0);
  const int lane = tid & 31;
  const uint32_t t_entry = clock_now();
  int b = blockIdx.x;
  if (BY_SM) {
    uint32_t smid; asm volatile("mov.u32 %0, %%smid;" : "=r"(smid));
    const int tp = smid >> 1;
    const int q7 = (tp - 32) * 37 >> 8;
    const int v0 = (tp & 7) * 8 + (tp >> 3), v1 = tp * 8 - 244 - q7 * 55, v2 = tp < 62 ? tp + 4 : tp - 58;
    b = (tp < 32 ? v0 : tp < 60 ? v1 : v2) * 2 + (smid & 1);
  }
  const int mg = (b >> 5) & 3, m = mg * 4 + (b & 3);
  const int c = ((b >> 2) & 7) ^ (BY_SM ? 0 : (mg & 1) * 7);
  const int row0 = (m & 7) * 128, par = m >> 3;
  if (__builtin_expect(b >= NCTA, 0)) { helper_cta(P, sc, b - NCTA, wg, w); return; }
  if (wg == 2 && w == 0) {
    if (elect_one()) {
      tma4d(SB, &P.tm[M_X0], 0, row0, 0, par, bar(B_FULL));
      tma4d(SB + 16384, &P.tm[M_WQKV], c * 64, 0, 0, 0, bar(B_FULL));
      mbar_expect_tx(bar(B_FULL), 40960);
      mbar_arrive(bar(B_FULL));
    }
    __syncwarp();
    TLW(0, 1);
  } else {
    const int g = wg * 4 + w - (wg == 2);
    if (elect_one()) {
#pragma unroll
      for (int x = 1; x < 10; x++) mbar_init(bar(x) + g * 72, g < 4 ? 2 : g == 4 ? 4 : 1);
      fence_bar_init();
      fence_proxy_async_smem();
    }
    __syncwarp();
  }
  if (__builtin_expect(wg == 2, 0)) {
    reg_dealloc<40>();
    if (w < 2) {
      if (w == 0) producer<false>(P, ops->a, NOP0, lane, c, row0, par, t_entry);
      else producer<true>(P, ops->b, NOP1, lane, c, row0, par, t_entry);
    } else if (w == 2) {
      if (smem_u32(smem_raw) != SB) __trap();
      __syncthreads();
      const uint32_t tag = ld_epoch(sc->epoch + b);
      uint32_t* const flag = sc->flags[m * 8 + c];
      if (lane < 4) asm volatile("st.relaxed.gpu.global.v4.u32 [%0], {%1, %1, %1, %1};" ::"l"(flag + lane * 4), "r"(tag * 32 - 1) : "memory");
      __syncwarp();
      int ev = 0;
      uint32_t t_st = t_entry;
#pragma unroll 1
      for (int t = 0; t < 21; t++) {
        const int i = t >= 11 ? t - 11 : t;
        if (i == 8 || i == 9) continue;
        const bool od = i == 2 || i == 10, wide = i > 2 && i < 7;
        const uint32_t sig = c_sched.task[t].sig;
        const uint32_t pf = i == 0 ? 1 << M_OL | 1 << M_O | 1 << M_WO : i == 1 ? 1 << M_O24 | 1 << M_W13 | 1 << M_W1 | 1 << M_W3 | 1 << M_YL | 1 << M_Y : i == 3 ? 1 << M_HL :
                            i == 5 ? 1 << M_H | 1 << M_W2 : i == 10 ? 1 << M_WQKV | 1 << M_YL | 1 << M_Y : 0;
        if ((pf >> lane) & 1) prefetch_tmap(&P.tm[lane]);
        __syncwarp();
        if (od) {
          asm volatile("{\n.reg .pred pe, pw;\n.reg .u32 it;\nsetp.eq.u32 pe, %4, 1;\nmov.u32 it, 0;\n"
                       "WAIT_%=:\nmbarrier.try_wait.parity.shared::cta.b64 pw, [%0], %1;\n@pw bra.uni GO_%=;\n"
                       "add.u32 it, it, 1;\nsetp.lt.u32 pw, it, 0x10000;\n@pw bra.uni WAIT_%=;\ntrap;\n"
                       "GO_%=:\nfence.proxy.async.global;\nfence.acq_rel.gpu;\n"
                       "@pe red.relaxed.gpu.global.add.u32 [%2], %4;\n@pe mbarrier.arrive.shared::cta.b64 _, [%3];\n}\n"
                       ::"r"(bar(B_SIG + 1)), "r"(sig >> 1), "l"(&sc->cnt[mg][ev] + lane), "r"(bar(B_PUB) + 8 * ev), "r"(lane + 1) : "memory");
          ev++;
          TLW(t, 4);
        }
        if (i == 1) {
          mbar_wait(bar(B_SIG), sig);
          fence_proxy_async_smem();
#pragma unroll 1
          for (int r = 8; r < 128; r += 32) tma4d_store(&P.tm[M_O24], SM_STG + r * 128, row0 + r, 8 + c, par);
        } else {
          const CUtensorMap* mp = &P.tm[i == 0 ? M_OL : od ? M_YL : M_HL];
          const int nr = i && !od ? 64 : 128;
#pragma unroll 1
          for (int x = od ? 3 : i ? 0 : 1; x < (i == 0 || i == 7 ? 2 : 4); x += wide && (i & 1) ? 3 : 1) {
            const bool mine = wide && (x == 0 || x == 3);
            const int r0 = nr == 128 ? 0 : wide ? (x >> 1) * 64 : x * 64, gap = i == 0 ? GAP_O : od ? GAP_Y : i == 7 ? GAP_H6 : x == 0 ? GAP_H0 : GAP_H;
            const int blk = (od ? 1 : i == 0 ? 0 : i == 7 ? 6 : ((i - 3) >> 1) * 3 + (mine ? ((i - 3) & 1) * 2 : 1)) * 8 + c;
            const uint32_t src = od ? SB + ((c_sched.task[t].stg >> 8) & 31) * 8192 : mine ? SM_STG - 8192 : SM_STG + r0 * 128;
            mbar_wait(bar(B_SIG) + 8 * x, sig >> x);
            if (od) mbar_wait(bar(B_DEP - 1) + 8 * ev, 0);
            fence_proxy_async_smem();
            const uint32_t now = clock_now();
            if ((int)(now - t_st) > 0) t_st = now;
#pragma unroll 1
            for (int r = 0; r < nr; r += PROWS) {
              delay_until(t_st, 0);
              t_st += gap;
              tma4d_store(mp, src + r * 128, row0 + r0 + r, blk, par);
            }
            if (wide && x == 0) {
              if (elect_one()) { bulk_commit(); bulk_wait(); mbar_arrive(bar(B_FR0)); }
              __syncwarp();
            }
          }
        }
        if (elect_one()) { bulk_commit(); bulk_wait(); }
        __syncwarp();
        if (i == 1) mbar_wait(bar(B_SIG + 1), sig >> 1);
        if (elect_one()) {
          mbar_arrive(od ? bar(B_SF) : bar(B_FREE));
          if (i < 3 || i > 4) {
            asm volatile("fence.proxy.async.global;" ::: "memory");
            st_release(flag, tag * 32 + ev);
            mbar_arrive(bar(B_PUB) + 8 * ev);
          }
        }
        __syncwarp();
        if (i < 3 || i > 4) ev++;
        if (!od) TLW(t, 4);
      }
      if (lane == 0) sc->epoch[b] = tag;
    } else {
      __syncthreads();
      const uint32_t tag = ld_epoch(sc->epoch + b);
      delay_until(t_entry, WARM_T);
      asm volatile("st.shared.u32 [%0], %1;" ::"r"(SM_TAG + 4), "r"(reinterpret_cast<const uint32_t*>(&c_sched)[min(lane * 16, (int)sizeof(Sched) / 4 - 1)]) : "memory");
      int ncs = 0;
#pragma unroll 1
      for (int it = 0; it < 20; it++) {
        const int l = it >= 11, i = it - l * 11, e = i < 2 ? 0 : i - 2, ev = l * E_N + e;
#pragma unroll 1
        for (; ncs < (it < 2 ? it + 1 : it < 6 ? 2 : 9); ncs++) {
          uint4 v[2];
          ld_tag_wait<300>(v, &sc->cs[ncs][c][lane], tag);
          const uint32_t a = SM_CS + (ncs < 2 ? ncs * 768 : 512 + ncs * 512) + ((lane & 17) | (lane & 6) << 1 | (lane & 8) >> 2) * 4;
#pragma unroll
          for (int j = 0; j < 2; j++) {
            sts4f(a + j * 128, __uint_as_float(v[j].x)); sts4f(a + j * 128 + 256, __uint_as_float(v[j].y));
            if (ncs < 2) sts4f(a + j * 128 + 512, __uint_as_float(v[j].z));
          }
          mbar_arrive_warp(bar(B_CS) + 8 * ncs);
        }
        if (i == 0 || i == 2) {
          const int u = l * 2 + (i >> 1);
          uint4 v[6] = {};
          mbar_wait(bar(B_QT), u);
          if (m & 7) ld_tag_wait<0>(v, &sc->halo[u][m - 1][c][0][lane], tag);
          const uint32_t xa = xch(i, 0) + lane * 16;
          sts16(xa, v[0].x, v[0].y, v[0].z, v[1].x); sts16(xa + 512, v[1].y, v[1].z, v[2].x, v[2].y);
          sts16(xa + 1024, v[2].z, v[3].x, v[3].y, v[3].z); sts16(xa + 1536, v[4].x, v[4].y, v[4].z, v[5].x);
          if (lane < 4) sts16(stat(l * 2) - 64 + lane * 16, v[5].y, 0, v[5].z, 0);
          mbar_arrive_warp(bar(B_XCH));
          continue;
        }
        const bool all = e == E_YA || e == E_XA;
        const uint32_t* fp = all ? &sc->cnt[mg][ev] : sc->flags[m * 8 + (lane & 7)];
        uint32_t want = tag * 32 + (all ? 0 : ev);
        asm volatile("" : "+l"(fp), "+r"(want));
        mbar_wait(bar(B_PUB) + 8 * ev, 0);
        wait_flags(fp, want);
        mbar_arrive_warp(bar(B_DEP) + 8 * ev);
        if (e == E_YB || e == E_XB) {
          const int p = e == E_XB ? 1 : l * 2;
          if (elect_one()) {
            mbar_expect_tx(bar(B_SF + 1), 8192);
            asm volatile("cp.async.bulk.shared::cluster.global.mbarrier::complete_tx::bytes [%0], [%1], 8192, [%2];" ::"r"(SM_STG), "l"(&sc->stat[p][m][0][0]), "r"(bar(B_SF + 1)) : "memory");
          }
          __syncwarp();
          mbar_wait(bar(B_SF + 1), p);
#pragma unroll 1
          for (int h = 0; h < 2; h++) {
            float s0 = 0.f, q0 = 0.f, s1 = 0.f, q1 = 0.f;
#pragma unroll 4
            for (int j = 0; j < 8; j++) {
              float x0, x1, x2, x3;
              lds16f(SM_STG + j * 1024 + h * 512 + lane * 16, x0, x1, x2, x3);
              s0 += x0; q0 += x1; s1 += x2; q1 += x3;
            }
            const float2 r0 = ln_finish(s0, q0), r1 = ln_finish(s1, q1);
            sts16(stat(p + 1) + (h * 64 + lane * 2) * 8, __float_as_uint(r0.x), __float_as_uint(r0.y), __float_as_uint(r1.x), __float_as_uint(r1.y));
          }
          mbar_arrive_warp(bar(B_STAT) + 8 * (p + 1));
        }
      }
    }
  } else {
    const int tw = tid & 127;
    reg_alloc<232>();
    uint32_t sig;
    asm volatile("mov.u32 %0, %1;" : "=r"(sig) : "r"((uint32_t)(tw == 0)));
    __syncthreads();

    if (wg == 1) {
      const uint32_t tag = ld_epoch(sc->epoch + b);
      uint4* const mine = &sc->stat0[m][c * 16 + w * 4 + (lane >> 3)];
      if ((lane & 7) == 0) st_tag(mine, 0, 0, 0, 0);
      __syncwarp();
      delay_until(t_entry, ST_ROWS);
      const bf16* xr = x0 + (size_t)((row0 + c * 16 + w * 4 + (lane >> 3)) * 2 + par) * D_ + (lane & 7) * 8;
      float sum = 0.f, sq = 0.f;
#pragma unroll 1
      for (int j0 = 0; j0 < 16; j0 += 4) {
        uint4 xv[4];
#pragma unroll
        for (int j = 0; j < 4; j++) xv[j] = ldcg16(xr + (j0 + j) * 64);
#pragma unroll
        for (int j = 0; j < 4; j++) {
          const uint32_t x[4] = {xv[j].x, xv[j].y, xv[j].z, xv[j].w};
#pragma unroll
          for (int e = 0; e < 8; e++) { const float d = e & 1 ? bf_hi(x[e >> 1]) : bf_lo(x[e >> 1]); sum += d; sq = fmaf(d, d, sq); }
        }
      }
#pragma unroll
      for (int o = 4; o > 0; o >>= 1) { sum += __shfl_xor_sync(0xffffffffu, sum, o); sq += __shfl_xor_sync(0xffffffffu, sq, o); }
      const float2 fin = ln_finish(sum, sq);
      if ((lane & 7) == 0) st_tag(mine, __float_as_uint(fin.x), __float_as_uint(fin.y), 0, tag);
      __syncwarp();
      TL(22, 5);
      uint4 v[1];
      ld_tag_wait<200>(v, &sc->stat0[m][tw], tag);
      sts8f(stat(0) + tw * 8, __uint_as_float(v[0].x), __uint_as_float(v[0].y));
      if (tw == 0) { asm volatile("st.shared.u32 [%0], %1;" ::"r"(SM_TAG), "r"(tag) : "memory"); sts16(SM_ZERO, 0, 0, 0, 0); }
      mbar_arrive_warp(bar(B_STAT));
      TL(22, 6);
    }

    uint32_t sp = wg * NSEG;
#pragma unroll 1
    for (int t = wg; t < 22; t += 2) {
      const int l = t >= 11, i = t - l * 11;
      if (t == 0) TL(t, 0);
      if (i < 2) {
        float acc[2][96];
        if (w == 3 && (m & 7) < 7) {
#pragma unroll
          for (int j = 0; j < 6; j++) st_tag(&sc->halo[l * 2 + i][m][c][j][lane_now()], 0, 0, 0, 0);
        }
        uint32_t Q[4][8], K[4][8], V[4][8], sta, csa;
        float2 st[4];
        auto fix = [&](int g, int j, float2 cs) {
          const int mi = g & 1, half = g >> 1;
          return pack_bf16_v(fmaf(st[g].y, cs.x, acc[mi][j * 4 + half * 2]), fmaf(st[g].y, cs.y, acc[mi][j * 4 + half * 2 + 1]));
        };
        mainloop<0>(acc, sig, t, wg, sp, [&]() {
          const int lane = lane_now();
          mbar_wait(bar(B_FREE), FREE_PH >> t);
          mbar_wait(bar(B_STAT) + l * 16, 0);
          mbar_wait(bar(B_CS) + i * 8, 0);
          sta = stat(l * 2) + w * 256;
          csa = SM_CS + i * 768 + (lane & 3) * 16;
          st[1] = lds8f(sta + (8 + (lane >> 2)) * 8); st[3] = lds8f(sta + (24 + (lane >> 2)) * 8);
        }, [&]() {
          const int lane = lane_now();
          mbar_arrive_if(bar(B_QT), sig);
#pragma unroll
          for (int j = 0; j < 8; j += 2) {
            float2 c0, c1;
            lds16f(csa + (16 + j) * 32, c0.x, c0.y, c1.x, c1.y);
            V[3][j] = movmat(fix(3, 16 + j, c0)); V[3][j + 1] = movmat(fix(3, 17 + j, c1));
            lds16f(csa + (8 + j) * 32, c0.x, c0.y, c1.x, c1.y);
            K[3][j] = fix(3, 8 + j, c0); K[3][j + 1] = fix(3, 9 + j, c1);
          }
          if (w < 3) {
            const uint32_t xa = xch(i, w + 1) + lane * 16;
            sts16(xa, K[3][0], K[3][1], K[3][2], K[3][3]); sts16(xa + 512, K[3][4], K[3][5], K[3][6], K[3][7]);
            sts16(xa + 1024, V[3][0], V[3][1], V[3][2], V[3][3]); sts16(xa + 1536, V[3][4], V[3][5], V[3][6], V[3][7]);
            mbar_arrive_warp(bar(B_XCH));
          } else if ((m & 7) < 7) {
            const uint32_t tag = lds4(SM_TAG), r0 = lds4(sta + (24 + 2 * (lane & 3)) * 8), r1 = lds4(sta + (25 + 2 * (lane & 3)) * 8);
            uint4* const p = &sc->halo[l * 2 + i][m][c][0][lane];
            st_tag(p, K[3][0], K[3][1], K[3][2], tag); st_tag(p + 32, K[3][3], K[3][4], K[3][5], tag); st_tag(p + 64, K[3][6], K[3][7], V[3][0], tag);
            st_tag(p + 96, V[3][1], V[3][2], V[3][3], tag); st_tag(p + 128, V[3][4], V[3][5], V[3][6], tag); st_tag(p + 160, V[3][7], r0, r1, tag);
          }
        });
        TL(t, 3);
        const int lane = lane_now(), q = lane & 3, r8 = lane >> 2;
        st[0] = lds8f(sta + r8 * 8); st[2] = lds8f(sta + (16 + r8) * 8);
#pragma unroll
        for (int j0 = 22; j0 >= 0; j0 -= 2) {
          float2 cs[2];
          lds16f(csa + j0 * 32, cs[0].x, cs[0].y, cs[1].x, cs[1].y);
#pragma unroll
          for (int j = j0; j < j0 + 2; j++)
#pragma unroll
            for (int g = 0; g < (j < 8 ? 4 : 3); g++) {
              const uint32_t pk = fix(g, j, cs[j - j0]);
              if (j < 8) Q[g][j] = pk; else if (j < 16) K[g][j - 8] = pk; else V[g][j - 16] = movmat(pk);
            }
        }
        const bool up0 = (2 * q) > r8, up1 = (2 * q + 1) > r8;
        const uint32_t mskP = (up0 ? 0xffffu : 0u) | (up1 ? 0xffff0000u : 0u);
        uint32_t ka0 = sta + q * 16 - (up0 ? 64 : 0), ka1 = sta + q * 16 + (up1 ? -56 : 8);
        asm volatile("" : "+r"(ka0), "+r"(ka1));
        TL(t, 5);
        uint32_t Kp[8] = {}, Vp[8] = {}, PS[2][4] = {}, PP[2][4] = {};
        float sS[2][4][2], sP[2][4][2] = {}, O[2][4][4][2], z0, z1, z2, z3;
        auto receive = [&]() {
          const uint32_t xa = xch(i, w) + lane * 16;
          mbar_wait(bar(B_XCH), i);
          lds16(xa, Kp[0], Kp[1], Kp[2], Kp[3]); lds16(xa + 512, Kp[4], Kp[5], Kp[6], Kp[7]);
          lds16(xa + 1024, Vp[0], Vp[1], Vp[2], Vp[3]); lds16(xa + 1536, Vp[4], Vp[5], Vp[6], Vp[7]);
          TL(i == 0 ? 22 : 23, t < 11 ? 3 : 4);
        };
        auto score = [&](float& s0, float& s1, float& s2, float& s3, int g, const uint32_t (&k)[8], int j, bool first) {
          mma16816(s0, s1, s2, s3, Q[g][j], Q[g + 1][j], Q[g][j + 1], Q[g + 1][j + 1], k[j], k[j + 1], first ? z0 : s0, first ? z1 : s1, first ? z2 : s2, first ? z3 : s3);
        };
        auto score0 = [&]() {
          float d[2][2];
#pragma unroll
          for (int x = 0; x < 4; x++) score(sP[x & 1][0][0], sP[x & 1][0][1], d[x & 1][0], d[x & 1][1], 0, Kp, (x & 1) * 4 + (x & 2), x < 2);
        };
        auto softmax = [&](int g) {
          const float rk0 = lds4f(ka0 + g * 64), rk1 = lds4f(ka1 + g * 64);
          const float f = st[g].x * (0.17677669529663687f * LOG2E), f0 = f * rk0, f1 = f * rk1;
          const bool noprev = g == 0 && (m & 7) == 0 && w == 0;
#pragma unroll
          for (int h = 0; h < 2; h++) {
            float v0 = (up0 ? sP[h][g][0] : sS[h][g][0]) * f0, v1 = (up1 ? sP[h][g][1] : sS[h][g][1]) * f1;
            if (noprev && up0) v0 = -1e9f * LOG2E;
            if (noprev && up1) v1 = -1e9f * LOG2E;
            float mx = fmaxf(v0, v1);
            mx = fmaxf(mx, __shfl_xor_sync(0xffffffffu, mx, 1)); mx = fmaxf(mx, __shfl_xor_sync(0xffffffffu, mx, 2));
            const float e0 = ex2f(v0 - mx), e1 = ex2f(v1 - mx);
            float sum = e0 + e1;
            sum += __shfl_xor_sync(0xffffffffu, sum, 1); sum += __shfl_xor_sync(0xffffffffu, sum, 2);
            const float inv = rcpf(sum);
            const uint32_t pk = pack_bf16_v(e0 * rk0 * inv, e1 * rk1 * inv);
            PS[h][g] = pk & ~mskP; PP[h][g] = pk & mskP;
          }
        };
        const uint32_t sa = SM_STG + (w * 32 + (lane & 7)) * 128 + (((lane >> 3) ^ (lane & 7)) << 4);
        auto stage = [&](int g) {
#pragma unroll
          for (int h = 0; h < 2; h++)
            stsm4t((sa ^ (h * 64)) + g * 1024, pack_bf16_v(O[h][g][0][0], O[h][g][0][1]), pack_bf16_v(O[h][g][1][0], O[h][g][1][1]),
                  pack_bf16_v(O[h][g][2][0], O[h][g][2][1]), pack_bf16_v(O[h][g][3][0], O[h][g][3][1]));
        };
        if (i == 0) { receive(); bar_sync(NB_PX, 256); }
        lds16f(SM_ZERO, z0, z1, z2, z3);
        if (i == 0) score0();
        {
          float d[2][2];
#pragma unroll
          for (int x = 0; x < 4; x++) {
            const int h = x & 1, j = h * 4 + (x & 2);
#pragma unroll
            for (int g = 0; g < 3; g++) score(sS[h][g][0], sS[h][g][1], sP[h][g + 1][0], sP[h][g + 1][1], g, K[g], j, x < 2);
            score(d[h][0], d[h][1], sS[h][3][0], sS[h][3][1], 2, K[3], j, x < 2);
          }
        }
        if (i == 0) { bar_arrive(NB_PY, 256); softmax(0); }
#pragma unroll
        for (int g = 1; g < 4; g++) softmax(g);
        TL(23, i == 0 ? (t < 11 ? 5 : 6) : 7);
        if (i == 0) bar_sync(NB_PX + ((PS[0][1] | PS[0][2] | PS[0][3] | PS[1][1] | PS[1][2] | PS[1][3]) & __float_as_uint(z0)), 256);
        lds16f(SM_ZERO, z0, z1, z2, z3);
        auto pv = [&](int g, const uint32_t (&vp)[8]) {
#pragma unroll
          for (int x = 0; x < 8; x += 2) {
            const int h = x >> 2, j = x & 3;
            mma16816(O[h][g][j][0], O[h][g][j][1], O[h][g][j + 1][0], O[h][g][j + 1][1], vp[x], vp[x + 1], V[g][x], V[g][x + 1], PP[h][g], PS[h][g], z0, z1, z2, z3);
          }
        };
        pv(1, V[0]); pv(3, V[2]); pv(2, V[1]);
        if (i) {
          stage(1); stage(2); stage(3);
          mbar_arrive_warp(bar(B_SIG));
          receive(); score0(); softmax(0);
        }
        pv(0, Vp);
        if (i == 0) { bar_arrive(NB_PY, 256); stage(1); stage(2); stage(3); stage(0); }
        else { stage(0); copy_out<2>(SM_STG + w * 4096, sc->o, par * (S_ * D_) + (row0 + w * 32) * 128 + (8 + c) * PANEL, 128, lane); }
        mbar_arrive_warp(bar(B_SIG + 1));
        if (i) bar_arrive(NB_OGO, 256);
        TL(t, 6);
      } else if (i > 2 && i < 7) {
        float acc[2][96], hr[4], mn[16];
        float2 cs[24];
        uint32_t so, sta, csa, sv[8][4];
        const int odd = (i - 3) & 1, blk = ((i - 3) >> 1) * 3;
        auto own_sums = [&](int g) {
#pragma unroll
          for (int x = 0; x < 4; x++) { const int j = (x >> 1) * 8 + g * 4 + (x & 1) * 2; lds16f(csa + odd * 1024 + j * 32, cs[j].x, cs[j].y, cs[j + 1].x, cs[j + 1].y); }
        };
        mainloop<1>(acc, sig, t, wg, sp, [&]() {
          const int lane = lane_now();
          so = SM_STG - 8192 + (w * 16 + (lane & 7)) * 128 + (((lane >> 3) ^ (lane & 7)) << 4);
          sta = stat(l * 2 + 1) + (w * 16 + (lane >> 2)) * 8;
          csa = SM_CS + 1536 + blk * 512 + (lane & 3) * 16;
          mbar_wait(bar(B_STAT + 1) + l * 16, 0);
          mbar_wait(bar(B_CS + 3) + 8 * (blk + odd), 0);
#pragma unroll
          for (int j = 0; j < 4; j++) hr[j] = 0.5f * lds4f(sta + (j >> 1) * 512 + (j & 1) * 64);
          own_sums(0);
          mbar_wait(bar(B_FREE), FREE_PH >> t);
        }, []() {});
        TL(t, 3);
        auto fetch = [&](int x, bool up) {
          const int r = x < 4 ? x & 1 : x < 12 ? (x - 4) >> 1 : 2 + (x & 1);
          if (x < 16) mn[x] = __uint_as_float(lds4(sta + 4 + (r >> 1) * 512 + (r & 1) * 64));
          if (up && x >= 4 && x < 12) ldsm4((so ^ ((x & 1) * 64)) + 8192 + ((r >> 1) * 64 + (r & 1) * 8) * 128, sv[x - 4][0], sv[x - 4][1], sv[x - 4][2], sv[x - 4][3]);
          if (x == 2) own_sums(1);
          if (x == 3) {
#pragma unroll
            for (int j = 16; j < 24; j += 2) lds16f(csa + (SWAP ^ odd) * 256 + j * 32, cs[j].x, cs[j].y, cs[j + 1].x, cs[j + 1].y);
          }
        };
        auto silu = [&](float g, float h) { const float a = g * h; return fmaf(a, tanhf_(a), a); };
        auto own = [&](int mi) {
#pragma unroll
          for (int x = mi * 12; x < mi * 12 + 4; x++) {
            const int g = (x >> 1) & 1, half = x & 1;
            uint32_t v[4];
#pragma unroll
            for (int j = 0; j < 4; j++) {
              const int jg = g * 4 + j + SWAP * 8, ju = jg ^ 8;
              v[j] = pack_bf16(silu(fmaf(mn[x], cs[jg].x, acc[mi][jg * 4 + half * 2]), hr[mi * 2 + half]) * fmaf(mn[x], cs[ju].x, acc[mi][ju * 4 + half * 2]),
                               silu(fmaf(mn[x], cs[jg].y, acc[mi][jg * 4 + half * 2 + 1]), hr[mi * 2 + half]) * fmaf(mn[x], cs[ju].y, acc[mi][ju * 4 + half * 2 + 1]));
            }
            stsm4((so ^ (g * 64)) + half * 1024, v[0], v[1], v[2], v[3]);
            if ((x & 3) == 3) mbar_arrive_warp(bar(B_SIG + mi * 3));
            fetch(x + 2, true);
          }
        };
        auto shared = [&](bool up) {
#pragma unroll
          for (int x = 0; x < 8; x++) {
            const int mi = x >> 2, half = (x >> 1) & 1, g = x & 1;
            uint32_t v[4];
#pragma unroll
            for (int j = 0; j < 4; j++) {
              const int jx = 16 + g * 4 + j;
              const float x0 = fmaf(mn[x + 4], cs[jx].x, acc[mi][jx * 4 + half * 2]), x1 = fmaf(mn[x + 4], cs[jx].y, acc[mi][jx * 4 + half * 2 + 1]);
              v[j] = up ? pack_bf16(bf_lo(sv[x][j]) * x0, bf_hi(sv[x][j]) * x1) : pack_bf16(silu(x0, hr[x >> 1]), silu(x1, hr[x >> 1]));
            }
            stsm4((so ^ (g * 64)) + 8192 + (mi * 64 + half * 8) * 128, v[0], v[1], v[2], v[3]);
            if (up && (x & 3) == 3) mbar_arrive_warp(bar(B_SIG + 1 + mi));
            fetch(x + 6, up);
          }
        };
        fetch(0, false); fetch(1, false);
        own(0);
        if (odd) shared(true); else shared(false);
        TL(t, 5);
        mbar_wait(bar(B_FR0), odd);
        own(1);
        TL(t, 6);
      } else if (i == 7) {
        float acc[2][64];
        float2 cs[16];
        float hr[4];
        uint32_t so, sta;
        mainloop<1>(acc, sig, t, wg, sp, [&]() {
          const int lane = lane_now();
          so = SM_STG + (w * 16 + (lane & 7)) * 128 + (((lane >> 3) ^ (lane & 7)) << 4);
          sta = stat(l * 2 + 1) + (w * 16 + (lane >> 2)) * 8;
          mbar_wait(bar(B_STAT + 1) + l * 16, 0);
          mbar_wait(bar(B_CS + 8), 0);
#pragma unroll
          for (int j = 0; j < 16; j += 2) lds16f(SM_CS + 9 * 512 + (lane & 3) * 16 + j * 32, cs[j].x, cs[j].y, cs[j + 1].x, cs[j + 1].y);
#pragma unroll
          for (int j = 0; j < 4; j++) hr[j] = 0.5f * lds4f(sta + (j >> 1) * 512 + (j & 1) * 64);
        }, []() {});
        mbar_wait(bar(B_FREE), FREE_PH >> t);
        TL(t, 3);
        float mn[8];
#pragma unroll
        for (int x = 0; x < 2; x++) mn[x] = __uint_as_float(lds4(sta + 4 + (x >> 2) * 512 + ((x >> 1) & 1) * 64));
#pragma unroll
        for (int x = 0; x < 8; x++) {
          const int mi = x >> 2, half = (x >> 1) & 1, g = x & 1;
          uint32_t v[4];
#pragma unroll
          for (int j = 0; j < 4; j++) {
            const int jg = g * 4 + j + SWAP * 8, ju = jg ^ 8;
            const float2 cg = cs[jg], cu = cs[ju];
            const float g0 = fmaf(mn[x], cg.x, acc[mi][jg * 4 + half * 2]), g1 = fmaf(mn[x], cg.y, acc[mi][jg * 4 + half * 2 + 1]);
            const float u0 = fmaf(mn[x], cu.x, acc[mi][ju * 4 + half * 2]), u1 = fmaf(mn[x], cu.y, acc[mi][ju * 4 + half * 2 + 1]);
            const float a0 = g0 * hr[x >> 1], a1 = g1 * hr[x >> 1];
            v[j] = pack_bf16(fmaf(a0, tanhf_(a0), a0) * u0, fmaf(a1, tanhf_(a1), a1) * u1);
          }
          stsm4((so ^ (g * 64)) + (mi * 64 + half * 8) * 128, v[0], v[1], v[2], v[3]);
          if ((x & 3) == 3) mbar_arrive_warp(bar(B_SIG + mi));
          if (x + 2 < 8) mn[x + 2] = __uint_as_float(lds4(sta + 4 + ((x + 2) >> 2) * 512 + (((x + 2) >> 1) & 1) * 64));
        }
        TL(t, 6);
      } else if (i == 2 || i == 10) {
        float acc[2][64], rsc[4];
        {
          const int lane = lane_now();
          const uint32_t e = c_sched.task[t].res;
          const uint32_t ra = SB + (w * 16 + (lane & 7)) * 128 + (((lane >> 3) ^ (lane & 7)) << 4);
          float sd[4];
#pragma unroll
          for (int j = 0; j < 4; j++) {
            rsc[j] = i == 10 ? lds4f(stat(l * 2 + 1) + ((j >> 1) * 64 + w * 16 + (j & 1) * 8 + (lane >> 2)) * 8) : 1.f;
            sd[j] = rcpf(rsc[j]);
          }
          const uint32_t zero = lds4(SM_ZERO);
          mbar_wait(bar(B_RES), i == 10);
          uint32_t dep[16];
#pragma unroll
          for (int x = 0; x < 16; x++) {
            const int mi = x >> 3, half = (x >> 2) & 1, g = x & 3;
            uint32_t v[4];
            ldsm4(((e >> ((g >> 1) * 8)) & 31) * 8192 + ((ra ^ ((g & 1) * 64)) | (x >= RLA ? dep[x - RLA] : 0)) + (mi * 64 + half * 8) * 128, v[0], v[1], v[2], v[3]);
#pragma unroll
            for (int j = 0; j < 4; j++) {
              asm volatile("shl.b32 %0, %1, 16;" : "=f"(acc[mi][(g * 4 + j) * 4 + half * 2]) : "r"(v[j]));
              asm volatile("and.b32 %0, %1, 0xffff0000;" : "=f"(acc[mi][(g * 4 + j) * 4 + half * 2 + 1]) : "r"(v[j]));
              acc[mi][(g * 4 + j) * 4 + half * 2] *= sd[mi * 2 + half]; acc[mi][(g * 4 + j) * 4 + half * 2 + 1] *= sd[mi * 2 + half];
            }
            asm("and.b32 %0, %1, %2;" : "=r"(dep[x]) : "f"(acc[mi][(g * 4 + 3) * 4 + half * 2 + 1]), "r"(zero));
          }
          mbar_arrive_warp(bar(B_RF));
        }
        auto stage = [&](int mi, int hi) {
          const int lane = lane_now();
          const uint32_t sw = SB + ((c_sched.task[t].stg >> (8 * hi)) & 31) * 8192 + (mi * 64 + w * 16) * 128, so = sw + (lane & 7) * 128 + (((lane >> 3) ^ (lane & 7)) << 4);
#pragma unroll
          for (int half = 0; half < 2; half++)
#pragma unroll
            for (int g = 0; g < 2; g++) {
              uint32_t v[4];
#pragma unroll
              for (int j = 0; j < 4; j++) {
                acc[mi][(hi * 8 + g * 4 + j) * 4 + half * 2] *= rsc[mi * 2 + half]; acc[mi][(hi * 8 + g * 4 + j) * 4 + half * 2 + 1] *= rsc[mi * 2 + half];
                v[j] = pack_bf16(acc[mi][(hi * 8 + g * 4 + j) * 4 + half * 2], acc[mi][(hi * 8 + g * 4 + j) * 4 + half * 2 + 1]);
              }
              stsm4((so ^ (g * 64)) + half * 1024, v[0], v[1], v[2], v[3]);
            }
          if (mi && !hi) mbar_arrive_warp(bar(B_SIG));
          if (hi == 0 || t == 21) {
            const int pitch = t == 21 ? D_ * 4 : 128;
            copy_out<4>(sw, t == 21 ? out : sc->y, (row0 + mi * 64 + w * 16) * pitch + (t == 21 ? par * (D_ * 2) + (hi * 8 + c) * 128 : par * (S_ * D_) + c * PANEL), pitch, lane);
          }
        };
        mainloop<2>(acc, sig, t, wg, sp, []() {}, [&]() { stage(0, 0); stage(0, 1); });
        TL(t, 3);
        stage(1, 0); mbar_arrive_warp(bar(B_SIG + 1));
        TL(t, 6);
        stage(1, 1); mbar_arrive_warp(bar(B_SIG + 2));
        if (t < 21) {
          const int lane = lane_now(), q = lane & 3;
          const uint32_t zero = lds4(SM_ZERO);
          float s[4], s2[4];
#pragma unroll
          for (int x = 0; x < 4; x++) {
            float a0 = x ? __uint_as_float(__float_as_uint(s[x - 1]) & zero) : 0.f, b0 = x ? __uint_as_float(__float_as_uint(s2[x - 1]) & zero) : 0.f;
#pragma unroll
            for (int j = 0; j < 32; j++) { const float d = acc[x >> 1][(j >> 1) * 4 + (x & 1) * 2 + (j & 1)]; a0 += d; b0 = fmaf(d, d, b0); }
            s[x] = a0; s2[x] = b0;
          }
#pragma unroll
          for (int x = 0; x < 2; x++) {
            s[x] = (q & 2 ? s[x + 2] : s[x]) + __shfl_xor_sync(0xffffffffu, q & 2 ? s[x] : s[x + 2], 2);
            s2[x] = (q & 2 ? s2[x + 2] : s2[x]) + __shfl_xor_sync(0xffffffffu, q & 2 ? s2[x] : s2[x + 2], 2);
          }
          const float r = (q & 1 ? s[1] : s[0]) + __shfl_xor_sync(0xffffffffu, q & 1 ? s[0] : s[1], 1);
          const float r2 = (q & 1 ? s2[1] : s2[0]) + __shfl_xor_sync(0xffffffffu, q & 1 ? s2[0] : s2[1], 1);
          asm volatile("st.global.v2.f32 [%0], {%1, %2};" ::"l"(&sc->stat[i == 10 ? 1 : l * 2][m][c][(q >> 1) * 64 + w * 16 + (q & 1) * 8 + (lane >> 2)]), "f"(r), "f"(r2) : "memory");
          mbar_arrive_warp(bar(B_SIG + 3));
        }
      }
    }
  }
}

typedef CUresult (*PFN_encodeTiled)(CUtensorMap*, CUtensorMapDataType, cuuint32_t, void*, const cuuint64_t*, const cuuint64_t*, const cuuint32_t*,
                                    const cuuint32_t*, CUtensorMapInterleave, CUtensorMapSwizzle, CUtensorMapL2promotion, CUtensorMapFloatOOBfill);

void make_map(PFN_encodeTiled enc, CUtensorMap* mp, const void* ptr, int rank, const cuuint64_t* gd, const cuuint64_t* gs, const cuuint32_t* bd) {
  const cuuint32_t es[4] = {1, 1, 1, 1};
  enc(mp, CU_TENSOR_MAP_DATA_TYPE_BFLOAT16, rank, const_cast<void*>(ptr), gd, gs, bd, es, CU_TENSOR_MAP_INTERLEAVE_NONE, CU_TENSOR_MAP_SWIZZLE_128B,
      CU_TENSOR_MAP_L2_PROMOTION_L2_128B, CU_TENSOR_MAP_FLOAT_OOB_FILL_NONE);
}
void make_map_act(PFN_encodeTiled enc, CUtensorMap* mp, const void* ptr, uint64_t cols, uint64_t s1, uint64_t s2, uint64_t s3, uint32_t rows) {
  const cuuint64_t gd[4] = {64, S_ / 2, cols / 64, 2}, gs[3] = {s1, s2, s3};
  const cuuint32_t bd[4] = {64, rows, 1, 1};
  make_map(enc, mp, ptr, 4, gd, gs, bd);
}
void make_map_w(PFN_encodeTiled enc, CUtensorMap* mp, const void* ptr, uint64_t rows, uint64_t cols, uint32_t np, uint64_t sp, uint64_t tiles, uint32_t nt) {
  const cuuint64_t gd[4] = {512, rows, np, tiles}, gs[3] = {cols * 2, sp, 1024};
  const cuuint32_t bd[4] = {64, 64, np, nt};
  make_map(enc, mp, ptr, 4, gd, gs, bd);
}

}

extern "C" void kernel_launch(void* const* d_in, const int* in_sizes, int n_in, void* d_out, int out_size) {
  (void)in_sizes; (void)n_in; (void)out_size;
  static PFN_encodeTiled enc = nullptr;
  static void *p_sc, *p_ops, *p_w;
  static int by_sm = 0;
  void (*const kernels[4])(Scratch*, const Ops*, const bf16*, bf16*, Params) = {fused_kernel<0, 0>, fused_kernel<1, 0>, fused_kernel<0, 1>, fused_kernel<1, 1>};
  if (!enc) {
    void* fn = nullptr; cudaDriverEntryPointQueryResult qr;
    cudaGetDriverEntryPoint("cuTensorMapEncodeTiled", &fn, cudaEnableDefault, &qr);
    enc = (PFN_encodeTiled)fn;
    cudaGetSymbolAddress(&p_sc, g_sc); cudaGetSymbolAddress(&p_ops, g_ops); cudaGetSymbolAddress(&p_w, g_w13);
    for (int i = 0; i < 4; i++) cudaFuncSetAttribute(kernels[i], cudaFuncAttributeMaxDynamicSharedMemorySize, SM_TOTAL);
    int dev = 0, sms = 0;
    cudaGetDevice(&dev);
    cudaDeviceGetAttribute(&sms, cudaDevAttrMultiProcessorCount, dev);
    by_sm = sms == NCTA + NHELP;
    for (int i = 1; i < 4 && by_sm; i++) {
      cudaLaunchConfig_t cfg = {};
      cudaLaunchAttribute at;
      at.id = cudaLaunchAttributeClusterDimension; at.val.clusterDim.x = 1 << i; at.val.clusterDim.y = at.val.clusterDim.z = 1;
      cfg.gridDim = dim3(NCTA); cfg.blockDim = dim3(384); cfg.dynamicSmemBytes = SM_TOTAL; cfg.attrs = &at; cfg.numAttrs = 1;
      int n = 0;
      if (cudaOccupancyMaxActiveClusters(&n, kernels[0], &cfg) != cudaSuccess) { (void)cudaGetLastError(); n = 0; }
      by_sm = n == (i == 1 ? 66 : i == 2 ? 30 : 15);
    }
  }
  Params P;
  Scratch* const sc = (Scratch*)p_sc;
  make_map_act(enc, &P.tm[M_X0], d_in[0], D_, D_ * 4, 128, D_ * 2, 128);
  make_map_act(enc, &P.tm[M_O], sc->o, D_, 128, PANEL, S_ * D_, 128);
  make_map_act(enc, &P.tm[M_Y], sc->y, D_, 128, PANEL, S_ * D_, 128);
  make_map_act(enc, &P.tm[M_H], sc->h, F_, 128, PANEL, S_ * F_, 128);
  make_map_act(enc, &P.tm[M_OL], sc->o, D_, 128, PANEL, S_ * D_, PROWS);
  make_map_act(enc, &P.tm[M_YL], sc->y, D_, 128, PANEL, S_ * D_, PROWS);
  make_map_act(enc, &P.tm[M_HL], sc->h, F_, 128, PANEL, S_ * F_, PROWS);
  make_map_act(enc, &P.tm[M_O24], sc->o, D_, 128, PANEL, S_ * D_, 24);
  make_map_w(enc, &P.tm[M_WQKV], d_in[1], D_, 3 * D_, 3, D_ * 2, 2, 1);
  make_map_w(enc, &P.tm[M_WO], d_in[2], D_, D_, 2, 1024, 1, 1);
  make_map_w(enc, &P.tm[M_W2], d_in[6], F_, D_, 2, 1024, 1, 1);
  const char *w1 = (const char*)d_in[4], *w3 = (const char*)d_in[5];
  if (w1 == w3 || (uint64_t)(w1 < w3 ? w3 - w1 : w1 - w3) >> 39) {
    cudaMemcpyAsync(p_w, w1, (size_t)D_ * F_ * 2, cudaMemcpyDeviceToDevice);
    cudaMemcpyAsync((bf16*)p_w + D_ * F_, w3, (size_t)D_ * F_ * 2, cudaMemcpyDeviceToDevice);
    w1 = (const char*)p_w; w3 = w1 + (size_t)D_ * F_ * 2;
  }
  const bool swap = w3 < w1;
  make_map_w(enc, &P.tm[M_W13], swap ? w3 : w1, D_, F_, 2, swap ? w1 - w3 : w3 - w1, 7, 1);
  make_map_w(enc, &P.tm[M_W1], w1 + 1024, D_, F_, 1, 1024, 6, 1);
  make_map_w(enc, &P.tm[M_W3], w3 - 1024, D_, F_, 1, 1024, 7, 1);
  kernels[by_sm * 2 + swap]<<<NCTA + NHELP, 384, SM_TOTAL>>>(sc, (const Ops*)p_ops, (const bf16*)d_in[0], (bf16*)d_out, P);
}
```

```cpp
#include <cuda_runtime.h>
#include <cuda_bf16.h>
#include <cuda.h>
#include <stdint.h>
#include <stddef.h>

typedef __nv_bfloat16 bf16;
#define GU_E 4
#define G_N1 8
#define Q_P1 4
#define Q_P2 6
#define Q_P0 1
#define RES_O 3
#define RES_D 2
#define HOLD_O 6
#define PROWS 16
#define GAP_O 150
#define GAP_Y 100
#define GAP_H 350
#define GAP_H6 1000
#define ST_T1 600
#define ST_D1 700
#define ST_ROWS 3500
#define WARM_T 4000
#define G_HOLD 2
#define D_PAD 0
#define GAP_H0 150
#define RLA 3
#define PADS 0x10000000
constexpr int TAILQ = 1, TAIL = 2;

namespace {

constexpr int S_ = 2048, D_ = 1024, F_ = 3584;
constexpr int PANEL = S_ / 2 * 128;
constexpr int NCTA = 128;
constexpr int NHELP = 4;

constexpr uint32_t SB = 1024;
constexpr int NU = 25;
constexpr uint32_t SM_STG  = SB + NU * 8192;
__host__ __device__ constexpr uint32_t xch(int i, int w) { return i ? SM_STG - 8192 + w * 2048 : SM_STG + w * 4096; }
constexpr uint32_t BARS    = SM_STG + 16384;
constexpr uint32_t SM_STAT = BARS + 896;
__host__ __device__ constexpr uint32_t stat(int set) { return SM_STAT + set * 1088 + 64; }
constexpr uint32_t SM_CS   = SM_STAT + 4352;
constexpr uint32_t SM_END  = SM_CS + 5120;
constexpr int SM_TOTAL = SM_END - SB;
static_assert(BARS % 1024 == 0 && SM_TOTAL <= 232448, "smem");
constexpr int B_FULL = 0, B_EMPTY = 16, B_SIG = 37, B_XCH = 41, B_RF = 42, B_STAT = 45, B_TURN = 49, B_RES = 51, B_FREE = 52, B_SF = 53, B_QT = 55, B_PASS = 56,
              B_CS = 57, B_DEP = 66, B_PUB = 82, B_FR0 = 98, B_N = 100;
__host__ __device__ constexpr uint32_t bar(int i) { return BARS + 8 * i; }
constexpr uint32_t SM_TAG = BARS + 8 * B_N, SM_ZERO = SM_TAG + 16;
constexpr int NB_PX = 1, NB_PY = 2, NB_OGO = 3, NB_END = 4;

constexpr int E_O0 = 0, E_O1 = 1, E_YA = 2, E_YB = 3, E_H4 = 4, E_XA = 7, E_XB = 8, E_N = 9;

constexpr int M_X0 = 0, M_O = 1, M_Y = 2, M_H = 3;
constexpr int M_WQKV = 4, M_WO = 5, M_W13 = 6, M_W1 = 7, M_W3 = 8, M_W2 = 9;
constexpr int M_OL = 10, M_YL = 11, M_HL = 12, M_O24 = 13, M_N = 14;

constexpr int FIRST = 5;
constexpr int NBAT = 12, NSEG = 48;
constexpr uint32_t A_END = 1, A_TURN = 2, A_DRAIN = 4, A_WAIT = 8, A_SYNC = 16;
constexpr uint32_t A_MARK = 0;
constexpr uint32_t phases(bool turn) {
  uint32_t r = 0, n[2] = {turn ? 0u : 1u, 0};
  for (int t = turn; t < 22; t++) if (turn ? t % 11 < 8 || t % 11 == 10 : t % 11 < 8 && t % 11 != 2) r |= (n[turn ? t & 1 : 0]++ & 1) << t;
  return r;
}
constexpr uint32_t TURN_PH = phases(true), FREE_PH = phases(false);
struct Task { uint32_t stg, res, sig; };
struct Seg { uint32_t i8, end8, a, b; };
constexpr uint32_t LO_A = 0x10000 + SB / 16, LO_B = 0x2000000 + SB / 16;
struct Sched { Seg seg[2 * NSEG]; Task task[22]; };
struct Ops { uint32_t x[2][8][NBAT * 32]; uint64_t y[2][32]; };
struct Gen {
  Sched s{}; Ops o{};
  int n[2] = {0, 0}, nseg[2] = {0, NSEG}, cur = -1, pos = 0, err = 0, res = 0, nres = 0;
  int mask[400] = {}, sa[400] = {}, sb[400][2] = {}, own[NU][2] = {}, tok[NU] = {}, known[2][2] = {{-1, -1}, {-1, -1}};
  constexpr void emit(int p, int wait, int par, int dst, int map, int kb8, int arr, int load, int y) {
    if (cur < FIRST) return;
    const int j = n[p]++;
    if (j >= NBAT * 32) return;
    for (int c = 0; c < 8; c++) {
      const int k = (y & 63) + (((y >> 6) & 7) > c) + (y & (1 << 9) ? c : 0);
      o.x[p][c][j] = (uint32_t)((p ? ((y >> 10) & 7) | (y >> 13) << 22 | (load ? map - M_WQKV : 0) << 3 | k << 6 : k | (y >> 10) << 6 | map << 7) | load << 12 | dst << 13 |
                                (res ? B_RES : B_FULL + (cur & 15)) << 18 | wait << 24) | (uint32_t)(par & 1) << 31;
    }
    o.y[p][j & 31] |= (uint64_t)(kb8 | arr << 3 | (!p && arr && mask[cur] != 3 && !res) << 4) << (j >> 5) * 5;
  }
  constexpr bool done(int p, int x) const { return x < 0 || ((!(mask[x] & 1) || known[p][0] >= x) && (!(mask[x] & 2) || known[p][1] >= x)); }
  constexpr void op(int p, int dst, int nu, int map, int kb8, int arr, int y, int xw = -1, int xp = 0) {
    int w[8] = {}, wp[8] = {}, nw = 0;
    if (xw >= 0) { w[nw] = xw; wp[nw++] = xp; }
    for (int u = dst; u < dst + nu; u++) if (tok[u] && (u == dst || tok[u] != tok[u - 1])) { w[nw] = (tok[u] - 1) >> 1; wp[nw++] = tok[u] - 1; }
    for (int x = cur - 1; x >= 0; x--) {
      bool need = x <= cur - 12;
      for (int u = dst; u < dst + nu; u++) need = need || own[u][0] == x + 1 || own[u][1] == x + 1;
      if (!need || done(p, x)) continue;
      if (cur - x >= 16 || !done(p, x - 16)) err |= 1;
      w[nw] = B_EMPTY + ((x + 2) & 15); wp[nw++] = x >> 4;
      for (int g = 0; g < 2; g++) if (((mask[x] >> g) & 1) && known[p][g] < x) known[p][g] = x;
    }
    for (; nw > 1; nw--) emit(p, w[nw - 1], wp[nw - 1], 0, 0, 0, 0, 0, 0);
    emit(p, nw ? w[0] : B_PASS, nw ? wp[0] : 1, dst, map, kb8, arr, nu > 0, y);
    for (int u = dst; u < dst + nu; u++) { own[u][0] = cur + 1; own[u][1] = 0; tok[u] = 0; }
  }
  constexpr int step(int m) { mask[++cur] = m; return cur; }
  constexpr int slot() { int u = (pos + 1) & ~1; if (u >= 24) u = 0; pos = u + 2; return u; }
  constexpr int alloc(int nu) { if (pos + nu > 24) pos = 0; pos += nu; return pos - nu; }
  constexpr int qslot() { int u = (pos + 4) / 5 * 5; if (u >= NU) u = 0; pos = u + 5; return u; }
  constexpr void stage(int u, int first, int t) {
    first -= TAIL;
    for (int x = u; x < u + 2; x++) { if (own[x][0] > first || own[x][1] > first || tok[x]) err |= 2; own[x][0] = cur + 1; own[x][1] = 0; tok[x] = t; }
  }
  static constexpr int kown(int hi) { return hi * 8 | 1 << 9; }
  static constexpr int kskip(int hi, int j) { return (hi * 8 + j) | (j + 1) << 6; }
  static constexpr int kpos(int p) { return p < 2 ? kown(p) : p < 9 ? kskip(0, p - 2) : kskip(1, p - 9); }
  constexpr void segs(int t, const int* st, const uint32_t* act, int cnt, int tail, int inc0) {
    const int g = t & 1, wrap = inc0 == 5 ? NU : 24;
    int j0 = 0;
    for (int j = 0; j < cnt; j++) {
      const int x = st[j], inc = inc0 ? inc0 : j0 + 1 < cnt ? (sa[st[j0 + 1]] - sa[st[j0]] + wrap) % wrap : 0;
      const bool next = j + 1 < cnt && st[j + 1] == x + 1 && sa[x + 1] == (sa[x] + inc) % wrap && sb[x + 1][g] == (sb[x][g] + inc) % wrap;
      if (j >= cnt - tail - 1 && j + 1 < cnt && !next) err |= 4;
      if (j + 1 < cnt && st[j + 1] != x + 1 && !(act[j] & A_DRAIN)) err |= 8;
      if (j >= cnt - tail || (next && !act[j] && j != cnt - tail - 1)) continue;
      if (j == j0 && (j == 0 || (inc0 != 4 && (act[j - 1] & (A_DRAIN | A_SYNC))))) err |= act[j] ? 16 : 0;
      const int y = st[j0];
      s.seg[nseg[g]++] = Seg{(uint32_t)y * 8 | (act[j] | (j == cnt - tail - 1 ? A_END : 0)) << 16, (uint32_t)(x + 1) * 8 | inc * 512 << 16, LO_A + sa[y] * 512, LO_B + sb[y][g] * 512};
      j0 = j + 1;
    }
  }
  constexpr void residual(int t, int map, bool q) {
    const int u0 = q ? qslot() : slot(), u1 = q ? u0 + 2 : slot();
    res = 1;
    op(0, u0, 2, map, 4, 1, kown(0)); op(0, u1, 2, map, 0, 0, kown(1));
    res = 0;
    for (int x = 0; x < 4; x++) { const int u = (x < 2 ? u0 : u1) + (x & 1); own[u][0] = 0; tok[u] = 1 + B_RF * 2 + (nres & 1); }
    nres++;
    s.task[t].res = u0 | u1 << 8;
  }
  constexpr Gen() {
    int cs[4] = {};
    for (int t = 0; t < 22; t++) {
      const int i = t % 11, use = i == 0 ? 2 : i == 1 || i == 7 ? 3 : i == 3 || i == 5 ? 9 : i == 8 || i == 9 ? 0 : 15;
      for (int x = 0; x < 4; x++) if ((use >> x) & 1) s.task[t].sig |= (cs[x]++ & 1) << x;
    }
    for (int l = 0; l < 2; l++) {
      const int T = l * 11, dep = B_DEP + l * E_N;
      int st[7][56] = {};
      uint32_t act[7][56] = {};
      if (l == 1) {
        const int first = cur + 1;
        for (int j = 0; j < 4; j++) {
          const int x = st[j >> 1][j & 1] = step(1 << ((T + (j >> 1)) & 1)), u = qslot();
          sb[x][0] = sb[x][1] = u + 2;
          if (j < 2) {
            sa[x] = (u + 5) % NU; stage(sa[x], first, j ? 1 + B_SF * 2 + 1 : 0); s.task[10].stg |= sa[x] << (8 * j);
            op(0, 0, 0, 0, 0, 1, 1 << 10, B_SIG + 2 * j, s.task[10].sig >> (2 * j));
          }
          else { sa[x] = sa[x - 2]; own[sa[x]][1] = own[sa[x] + 1][1] = x + 1; op(0, 0, 0, 0, 0, 1, 0); }
          op(1, u + 2, 3, M_WQKV, 3, 1, kown(j & 1) | (j >> 1) << 10);
        }
        act[0][1] = A_DRAIN; act[1][1] = A_DRAIN | A_WAIT;
      }
      for (int i = 0; i < 2; i++) {
        for (int j = 2 * l; j < 16; j++) {
          if (i && j == 16 - RES_O) residual(T + 2, l ? M_Y : M_X0, true);
          const int x = st[i][j] = step(1 << ((T + i) & 1)), u = qslot(), k = l ? kpos(j) : j;
          sa[x] = u; sb[x][0] = sb[x][1] = u + 2;
          op(0, u, 2, l ? M_Y : M_X0, 2, 1, k, l && i == 0 && (j == 2 || j == 9) ? B_DEP + (j == 2 ? E_XA : E_XB) : -1);
          op(1, u + 2, 3, M_WQKV, 3, 1, k | i << 10);
        }
        if (i) act[1][Q_P1 - 1 + (l ? 2 : Q_P0)] = act[1][Q_P2 - 1 + (l ? 2 : Q_P0)] = A_SYNC;
        if (i && own[NU - 1][0] > cur - TAILQ) err |= 256;
        segs(T + i, st[i], act[i], 16, TAILQ, 5);
      }
      for (int j = 0; j < 16; j++) {
        const int x = st[0][j] = step(1 << (T & 1)), k = j < 8 ? j : j == 8 ? kown(1) : kskip(1, j - 9), hold = j == HOLD_O ? B_PUB + l * E_N + E_O1 : -1;
        act[0][j] = j == 8 ? A_MARK : 0;
        if (j != 8) { sa[x] = slot(); op(0, sa[x], 2, M_O, 2, 1, k, j == 0 ? dep + E_O0 : j == 9 ? dep + E_O1 : hold); }
        else { sa[x] = NU; op(0, 0, 0, 0, 0, 1, 1 << 10, B_SIG + 1, s.task[T + 1].sig >> 1); }
        sb[x][0] = sb[x][1] = slot();
        op(1, sb[x][0], 2, M_WO, 2, 1, k, hold);
      }
      segs(T + 2, st[0], act[0], 16, TAIL, 4);
      int beg[6] = {0, 16}, end[5] = {16, 32 - G_N1}, cnt[5] = {}, ord = 0, pm = 0, nrun = 0;
      for (int j = 2; j < 5; j++) { beg[j] = end[j - 2] + GU_E; end[j] = beg[j] + 16; }
      beg[5] = end[4];
      const int first = cur + 1;
      for (int j = 0; j < end[4]; j++) {
        int tl[2] = {-1, -1}, m = 0;
        for (int v = 0; v < 5; v++) if ((j >= beg[v] && j < end[v]) || (v == 1 && j < G_N1)) { const int g = (T + 3 + v) & 1; if (tl[g] >= 0) err |= 32; tl[g] = v; m |= 1 << g; }
        if (!m) err |= 32;
        if (j == end[4] - RES_D) residual(T + 10, M_Y, false);
        const int x = step(m), k = kpos(j < 16 ? j : (j + G_N1) & 15), v0 = m == 3 ? (tl[0] < tl[1] ? tl[0] : tl[1]) : tl[m >> 1];
        if (m != pm) {
          ord = 0;
          pos += ((uint64_t)PADS >> (4 * nrun++)) & 15;
          if (m == 3 && v0 < 3) { if ((0x92 >> (pos & 7)) & 1) pos++; ord = (pos & 7) == 5 ? 1 : (pos & 7) == 2 ? 2 : 0; }
          if (v0 == 4) { pos = (pos + 1) & ~1; for (int y = 0; y < (l ? 0 : D_PAD); y++) slot(); }
          pm = m;
        }
        if (m != 3 && v0 < 4) ord = pos == 20 || pos == 21 ? 1 : pos == 22 ? 0 : ord;
        int ub[2] = {}, n8 = 0;
        for (int y = 0, q = 0; y < (m == 3 ? 3 : 2); y++) {
          if (y == ord) sa[x] = alloc(2);
          else { const int nu = v0 + q < 4 ? 3 : 2; ub[q++] = alloc(nu); n8 += nu; }
        }
        if (j < 2) { stage(sa[x], first, j ? 1 + B_SF * 2 : 0); s.task[T + 2].stg |= sa[x] << (8 * j); op(0, 0, 0, 0, 0, 1, 1 << 10, B_SIG + 2 * j, s.task[T + 2].sig >> (2 * j)); }
        else op(0, sa[x], 2, M_Y, 2, 1, k, j == 2 ? dep + E_YA : j == 9 ? dep + E_YB : -1);
        for (int q = 0; q < (m == 3 ? 2 : 1); q++) {
          const int v = v0 + q, blk = (v >> 1) * 3 + (v & 1) * 2;
          op(1, ub[q], v < 4 ? 3 : 2, M_W13, q ? 0 : n8, !q, k | blk << 10 | (v < 4 ? 1 + (v & 1) : 0) << 13, j == G_HOLD && !q ? B_PUB + l * E_N + E_YA : -1);
          sb[x][(T + 3 + v) & 1] = ub[q];
          act[v][cnt[v]] = j == beg[v + 1] - 1 ? A_TURN : v == 1 && j == G_N1 - 1 ? A_DRAIN | A_WAIT : v == 0 && j == 1 ? A_MARK : 0;
          st[v][cnt[v]++] = x;
        }
      }
      for (int v = 0; v < 5; v++) { if (cnt[v] != 16) err |= 64; segs(T + 3 + v, st[v], act[v], 16, 0, 0); }
      for (int j = 0; j < 56; j++) {
        const int x = st[0][j] = step(1 << (T & 1));
        act[0][j] = 0;
        sa[x] = slot(); op(0, sa[x], 2, M_H, 2, 1, j, j == 0 ? dep + E_H4 : j == 32 ? dep + E_H4 + 1 : j == 48 ? dep + E_H4 + 2 : -1);
        sb[x][0] = sb[x][1] = slot(); op(1, sb[x][0], 2, M_W2, 2, 1, j);
      }
      segs(T + 10, st[0], act[0], 56, TAIL, 4);
    }
    { const int u0 = slot(), u1 = slot(); stage(u0, cur + 1, 0); stage(u1, cur + 1, 0); s.task[21].stg = u0 | u1 << 8; }
    if (n[0] > NBAT * 32 || n[1] > NBAT * 32 || nseg[0] >= NSEG || nseg[1] >= 2 * NSEG) err |= 128;
    for (int p = 0; p < 2; p++) for (int c = 0; c < 8; c++) for (int x = n[p]; x < NBAT * 32; x++) o.x[p][c][x] = B_PASS << 24 | 1u << 31;
  }
};
constexpr Gen GEN{};
static_assert(GEN.err == 0, "schedule");

struct __align__(64) Params {
  CUtensorMap tm[M_N];
};

}

__constant__ Sched c_sched = GEN.s;
__device__ const Ops g_ops = GEN.o;
struct __align__(1024) Scratch {
  float2 stat[3][16][8][128];
  uint4 stat0[16][128];
  uint4 halo[4][16][8][6][32];
  uint4 cs[9][8][64];
  uint32_t flags[NCTA][32];
  uint32_t cnt[4][32];
  uint32_t epoch[NCTA + NHELP];
  __align__(1024) bf16 o[S_ * D_];
  bf16 y[S_ * D_], h[S_ * F_];
};
__device__ Scratch g_sc;
__device__ __align__(1024) bf16 g_w13[2 * D_ * F_];

#define TL(t, i) do {} while (0)
#define TS(i8, wg) do {} while (0)
#define TLW(t, i) do {} while (0)
#define MB_LIMIT (1 << 16)
#define FL_LIMIT (1 << 21)

namespace {

__device__ __forceinline__ uint32_t smem_u32(const void* p) { return (uint32_t)__cvta_generic_to_shared(p); }
__device__ __forceinline__ void mbar_init(uint32_t br, uint32_t cnt) { asm volatile("mbarrier.init.shared::cta.b64 [%0], %1;" ::"r"(br), "r"(cnt)); }
__device__ __forceinline__ void mbar_expect_tx(uint32_t br, uint32_t bytes) { asm volatile("mbarrier.arrive.expect_tx.shared::cta.b64 _, [%0], %1;" ::"r"(br), "r"(bytes) : "memory"); }
__device__ __forceinline__ void mbar_arrive(uint32_t br) { asm volatile("mbarrier.arrive.shared::cta.b64 _, [%0];" ::"r"(br) : "memory"); }
__device__ __forceinline__ void mbar_arrive_if(uint32_t br, uint32_t p) {
  asm volatile("{\n.reg .pred q;\nsetp.ne.u32 q, %1, 0;\n@q mbarrier.arrive.shared::cta.b64 _, [%0];\n}\n" ::"r"(br), "r"(p) : "memory");
}
__device__ __forceinline__ void mbar_arrive_warp(uint32_t br) {
  asm volatile("{\n.reg .pred q;\nbar.warp.sync 0xffffffff;\nelect.sync _|q, 0xffffffff;\n@q mbarrier.arrive.shared::cta.b64 _, [%0];\n}\n" ::"r"(br) : "memory");
}
__device__ __forceinline__ bool mbar_try_wait(uint32_t br, uint32_t parity) {
  uint32_t ok;
  asm volatile("{\n.reg .pred p;\nmbarrier.try_wait.parity.shared::cta.b64 p, [%1], %2;\nselp.u32 %0, 1, 0, p;\n}\n" : "=r"(ok) : "r"(br), "r"(parity) : "memory");
  return ok;
}
__device__ __forceinline__ void mbar_wait(uint32_t br, uint32_t parity) {
#pragma unroll 1
  for (int it = 0; it < MB_LIMIT; ++it) { if (mbar_try_wait(br, parity)) return; }
  __trap();
}
__device__ __forceinline__ bool elect_one() { uint32_t p; asm volatile("{\n.reg .pred P;\nelect.sync _|P, 0xffffffff;\nselp.u32 %0, 1, 0, P;\n}\n" : "=r"(p)); return p; }
__device__ __forceinline__ void fence_proxy_async_smem() { asm volatile("fence.proxy.async.shared::cta;" ::: "memory"); }
__device__ __forceinline__ void tma4d(uint32_t dst, const CUtensorMap* m, int c0, int c1, int c2, int c3, uint32_t br) {
  asm volatile("cp.async.bulk.tensor.4d.shared::cluster.global.mbarrier::complete_tx::bytes [%0], [%1, {%3, %4, %5, %6}], [%2];" ::"r"(dst), "l"(m), "r"(br), "r"(c0), "r"(c1), "r"(c2), "r"(c3) : "memory");
}
__device__ __forceinline__ void tma4d_store(const CUtensorMap* m, uint32_t src, int c1, int c2, int c3) {
  asm volatile("{\n.reg .pred p;\nelect.sync _|p, 0xffffffff;\n@p cp.async.bulk.tensor.4d.global.shared::cta.bulk_group [%0, {%5, %2, %3, %4}], [%1];\n}\n" ::"l"(m), "r"(src), "r"(c1), "r"(c2), "r"(c3), "r"(0) : "memory");
}
__device__ __forceinline__ void stsm4(uint32_t a, uint32_t x, uint32_t y, uint32_t z, uint32_t w) {
  asm volatile("stmatrix.sync.aligned.m8n8.x4.shared.b16 [%0], {%1,%2,%3,%4};" ::"r"(a), "r"(x), "r"(y), "r"(z), "r"(w) : "memory");
}
__device__ __forceinline__ void stsm4t(uint32_t a, uint32_t x, uint32_t y, uint32_t z, uint32_t w) {
  asm volatile("stmatrix.sync.aligned.m8n8.x4.trans.shared.b16 [%0], {%1,%2,%3,%4};" ::"r"(a), "r"(x), "r"(y), "r"(z), "r"(w) : "memory");
}
__device__ __forceinline__ void ldsm4(uint32_t a, uint32_t& x, uint32_t& y, uint32_t& z, uint32_t& w) {
  asm volatile("ldmatrix.sync.aligned.m8n8.x4.shared.b16 {%0,%1,%2,%3}, [%4];" : "=r"(x), "=r"(y), "=r"(z), "=r"(w) : "r"(a) : "memory");
}
__device__ __forceinline__ void st_tag(uint4* p, uint32_t a, uint32_t b, uint32_t c, uint32_t tag) {
  asm volatile("{\n.reg .b64 x, y;\n.reg .b128 z;\nmov.b64 x, {%1, %2};\nmov.b64 y, {%3, %4};\nmov.b128 z, {x, y};\nst.relaxed.gpu.global.b128 [%0], z;\n}\n" ::"l"(p), "r"(a), "r"(b), "r"(c), "r"(tag) : "memory");
}
__device__ __forceinline__ uint4 ld_tag(const uint4* p) {
  uint4 v;
  asm volatile("{\n.reg .b64 x, y;\n.reg .b128 z;\nld.relaxed.gpu.global.b128 z, [%4];\nmov.b128 {x, y}, z;\nmov.b64 {%0, %1}, x;\nmov.b64 {%2, %3}, y;\n}\n" : "=r"(v.x), "=r"(v.y), "=r"(v.z), "=r"(v.w) : "l"(p) : "memory");
  return v;
}
template <int NAP, int N> __device__ __forceinline__ void ld_tag_wait(uint4 (&v)[N], const uint4* p, uint32_t tag) {
#pragma unroll 1
  for (int it = 0; it < FL_LIMIT; ++it) {
    uint32_t bad = 0;
#pragma unroll
    for (int j = 0; j < N; j++) v[j] = ld_tag(p + j * 32);
#pragma unroll
    for (int j = 0; j < N; j++) bad |= v[j].w ^ tag;
    if (__all_sync(0xffffffffu, bad == 0)) return;
    if (NAP) __nanosleep(NAP);
  }
  __trap();
}
__device__ __forceinline__ void prefetch_tmap(const CUtensorMap* m) { asm volatile("prefetch.tensormap [%0];" ::"l"(m) : "memory"); }
__device__ __forceinline__ void wgmma_fence() { asm volatile("wgmma.fence.sync.aligned;" ::: "memory"); }
__device__ __forceinline__ void wgmma_commit() { asm volatile("wgmma.commit_group.sync.aligned;" ::: "memory"); }
template <int N> __device__ __forceinline__ void wgmma_wait() { asm volatile("wgmma.wait_group.sync.aligned %0;" ::"n"(N) : "memory"); }
template <int R> __device__ __forceinline__ void reg_alloc() { asm volatile("setmaxnreg.inc.sync.aligned.u32 %0;" ::"n"(R)); }
template <int R> __device__ __forceinline__ void reg_dealloc() { asm volatile("setmaxnreg.dec.sync.aligned.u32 %0;" ::"n"(R)); }
__device__ __forceinline__ void bar_sync(int id, int n) { asm volatile("bar.sync %0, %1;" ::"r"(id), "r"(n) : "memory"); }
__device__ __forceinline__ void bar_arrive(int id, int n) { asm volatile("bar.arrive %0, %1;" ::"r"(id), "r"(n) : "memory"); }
__device__ __forceinline__ uint32_t ld_acquire(const uint32_t* p) { uint32_t v; asm volatile("ld.acquire.gpu.global.u32 %0, [%1];" : "=r"(v) : "l"(p) : "memory"); return v; }
__device__ __forceinline__ void st_release(uint32_t* p, uint32_t v) { asm volatile("st.release.gpu.global.u32 [%0], %1;" ::"l"(p), "r"(v) : "memory"); }
__device__ __forceinline__ uint4 ldcg16(const void* p) { uint4 v; asm volatile("ld.global.cg.v4.u32 {%0,%1,%2,%3}, [%4];" : "=r"(v.x), "=r"(v.y), "=r"(v.z), "=r"(v.w) : "l"(p) : "memory"); return v; }
__device__ __forceinline__ float2 lds8f(uint32_t a) { float2 v; asm volatile("ld.shared.v2.f32 {%0,%1}, [%2];" : "=f"(v.x), "=f"(v.y) : "r"(a)); return v; }
__device__ __forceinline__ float lds4f(uint32_t a) { float v; asm volatile("ld.shared.f32 %0, [%1];" : "=f"(v) : "r"(a)); return v; }
__device__ __forceinline__ uint32_t lds4(uint32_t a) { uint32_t v; asm volatile("ld.shared.u32 %0, [%1];" : "=r"(v) : "r"(a) : "memory"); return v; }
__device__ __forceinline__ void lds16f(uint32_t a, float& x, float& y, float& z, float& w) { asm volatile("ld.shared.v4.f32 {%0,%1,%2,%3}, [%4];" : "=f"(x), "=f"(y), "=f"(z), "=f"(w) : "r"(a) : "memory"); }
__device__ __forceinline__ void sts8f(uint32_t a, float x, float y) { asm volatile("st.shared.v2.f32 [%0], {%1,%2};" ::"r"(a), "f"(x), "f"(y) : "memory"); }
__device__ __forceinline__ void sts4f(uint32_t a, float x) { asm volatile("st.shared.f32 [%0], %1;" ::"r"(a), "f"(x) : "memory"); }
__device__ __forceinline__ void sts16(uint32_t a, uint32_t x, uint32_t y, uint32_t z, uint32_t w) { asm volatile("st.shared.v4.u32 [%0], {%1,%2,%3,%4};" ::"r"(a), "r"(x), "r"(y), "r"(z), "r"(w) : "memory"); }
__device__ __forceinline__ void lds16(uint32_t a, uint32_t& x, uint32_t& y, uint32_t& z, uint32_t& w) { asm volatile("ld.shared.v4.u32 {%0,%1,%2,%3}, [%4];" : "=r"(x), "=r"(y), "=r"(z), "=r"(w) : "r"(a) : "memory"); }
__device__ __forceinline__ uint32_t pack_bf16(float a, float b) { uint32_t r; asm("cvt.rn.bf16x2.f32 %0, %1, %2;" : "=r"(r) : "f"(b), "f"(a)); return r; }
__device__ __forceinline__ uint32_t pack_bf16_v(float a, float b) { uint32_t r; asm volatile("cvt.rn.bf16x2.f32 %0, %1, %2;" : "=r"(r) : "f"(b), "f"(a)); return r; }
__device__ __forceinline__ float bf_lo(uint32_t v) { return __uint_as_float(v << 16); }
__device__ __forceinline__ float bf_hi(uint32_t v) { return __uint_as_float(v & 0xffff0000u); }
constexpr float LOG2E = 1.4426950408889634f;
__device__ __forceinline__ float ex2f(float x) { float y; asm("ex2.approx.ftz.f32 %0, %1;" : "=f"(y) : "f"(x)); return y; }
__device__ __forceinline__ float tanhf_(float x) { float y; asm("tanh.approx.f32 %0, %1;" : "=f"(y) : "f"(x)); return y; }
__device__ __forceinline__ float rcpf(float x) { float y; asm("rcp.approx.ftz.f32 %0, %1;" : "=f"(y) : "f"(x)); return y; }
__device__ __forceinline__ float bf_round(float a) { return bf_lo(pack_bf16(a, 0.f)); }
__device__ __forceinline__ uint32_t movmat(uint32_t a) { uint32_t d; asm volatile("movmatrix.sync.aligned.m8n8.trans.b16 %0, %1;" : "=r"(d) : "r"(a)); return d; }
__device__ __forceinline__ void mma16816(float& d0, float& d1, float& d2, float& d3, uint32_t a0, uint32_t a1, uint32_t a2, uint32_t a3, uint32_t b0, uint32_t b1,
                                         float c0, float c1, float c2, float c3) {
  asm volatile("mma.sync.aligned.m16n8k16.row.col.f32.bf16.bf16.f32 {%0,%1,%2,%3}, {%4,%5,%6,%7}, {%8,%9}, {%10,%11,%12,%13};"
               : "=f"(d0), "=f"(d1), "=f"(d2), "=f"(d3) : "r"(a0), "r"(a1), "r"(a2), "r"(a3), "r"(b0), "r"(b1), "f"(c0), "f"(c1), "f"(c2), "f"(c3));
}
template <int N> __device__ __forceinline__ void copy_out(uint32_t a, void* base, uint32_t ofs, int pitch, int lane) {
  a += (lane >> 3) * 128 + (((lane ^ (lane >> 3)) & 7) << 4);
  char* const g = static_cast<char*>(base) + (ofs + (lane >> 3) * pitch + (lane & 7) * 16);
  uint32_t v[N][4];
  __syncwarp();
#pragma unroll
  for (int j = 0; j < N; j++) lds16((a ^ ((j & 1) * 64)) + j * 512, v[j][0], v[j][1], v[j][2], v[j][3]);
#pragma unroll
  for (int j = 0; j < N; j++) asm volatile("st.global.v4.u32 [%0], {%1, %2, %3, %4};" ::"l"(g + j * 4 * pitch), "r"(v[j][0]), "r"(v[j][1]), "r"(v[j][2]), "r"(v[j][3]) : "memory");
}
__device__ __forceinline__ int lane_now() { int v; asm volatile("mov.u32 %0, %%laneid;" : "=r"(v)); return v; }
__device__ __forceinline__ uint32_t uni(uint32_t x, int lane) { return __shfl_sync(0xffffffffu, x + lane, 0); }
__device__ __forceinline__ uint64_t dsc(uint32_t hi, uint32_t lo) { return ((uint64_t)hi << 32) | lo; }

#define R8(a, o) "+f"(a[o]), "+f"(a[o + 1]), "+f"(a[o + 2]), "+f"(a[o + 3]), "+f"(a[o + 4]), "+f"(a[o + 5]), "+f"(a[o + 6]), "+f"(a[o + 7])
#define R32(a, o) R8(a, o), R8(a, o + 8), R8(a, o + 16), R8(a, o + 24)
#define REG64 "%0, %1, %2, %3, %4, %5, %6, %7, %8, %9, %10, %11, %12, %13, %14, %15, %16, %17, %18, %19, %20, %21, %22, %23, %24, %25, %26, %27, %28, %29, %30, %31, " \
              "%32, %33, %34, %35, %36, %37, %38, %39, %40, %41, %42, %43, %44, %45, %46, %47, %48, %49, %50, %51, %52, %53, %54, %55, %56, %57, %58, %59, %60, %61, %62, %63"
#define REG96 REG64 ", %64, %65, %66, %67, %68, %69, %70, %71, %72, %73, %74, %75, %76, %77, %78, %79, %80, %81, %82, %83, %84, %85, %86, %87, %88, %89, %90, %91, %92, %93, %94, %95"
__device__ __forceinline__ void wgmma(float (&d)[64], uint64_t da, uint64_t db) {
  asm volatile("wgmma.mma_async.sync.aligned.m64n128k16.f32.bf16.bf16 {" REG64 "}, %64, %65, 1, 1, 1, 0, 1;\n"
               : R32(d, 0), R32(d, 32) : "l"(da), "l"(db));
}
__device__ __forceinline__ void wgmma(float (&d)[96], uint64_t da, uint64_t db) {
  asm volatile("wgmma.mma_async.sync.aligned.m64n192k16.f32.bf16.bf16 {" REG96 "}, %96, %97, 1, 1, 1, 0, 1;\n"
               : R32(d, 0), R32(d, 32), R32(d, 64) : "l"(da), "l"(db));
}
#define W8(a, o) "=f"(a[o]), "=f"(a[o + 1]), "=f"(a[o + 2]), "=f"(a[o + 3]), "=f"(a[o + 4]), "=f"(a[o + 5]), "=f"(a[o + 6]), "=f"(a[o + 7])
#define W32(a, o) W8(a, o), W8(a, o + 8), W8(a, o + 16), W8(a, o + 24)
__device__ __forceinline__ void wgmma_z(float (&d)[64], uint64_t da, uint64_t db) {
  asm volatile("wgmma.mma_async.sync.aligned.m64n128k16.f32.bf16.bf16 {" REG64 "}, %64, %65, 0, 1, 1, 0, 1;\n"
               : W32(d, 0), W32(d, 32) : "l"(da), "l"(db));
}
__device__ __forceinline__ void wgmma_z(float (&d)[96], uint64_t da, uint64_t db) {
  asm volatile("wgmma.mma_async.sync.aligned.m64n192k16.f32.bf16.bf16 {" REG96 "}, %96, %97, 0, 1, 1, 0, 1;\n"
               : W32(d, 0), W32(d, 32), W32(d, 64) : "l"(da), "l"(db));
}

__device__ __forceinline__ void wgmma_cs(float (&d)[4], uint64_t da, uint64_t db) {
  asm volatile("wgmma.mma_async.sync.aligned.m64n8k16.f32.bf16.bf16 {%0, %1, %2, %3}, %4, %5, 1, 1, 1, 1, 0;\n" : "+f"(d[0]), "+f"(d[1]), "+f"(d[2]), "+f"(d[3]) : "l"(da), "l"(db));
}
__device__ __forceinline__ void bulk_commit() { asm volatile("cp.async.bulk.commit_group;" ::: "memory"); }
__device__ __forceinline__ void bulk_wait() { asm volatile("cp.async.bulk.wait_group 0;" ::: "memory"); }
__device__ __forceinline__ void fence_bar_init() { asm volatile("fence.mbarrier_init.release.cluster;" ::: "memory"); }

__device__ __forceinline__ uint32_t clock_now() { uint32_t v; asm volatile("mov.u32 %0, %%clock;" : "=r"(v)); return v; }
__device__ __forceinline__ void delay_until(uint32_t t0, int cycles) {
#pragma unroll 1
  for (int it = 0; it < 1000 && (int)(clock_now() - t0) < cycles; it++) __nanosleep(40);
}
__device__ __forceinline__ uint32_t ld_epoch(const uint32_t* p) { uint32_t v; asm volatile("ld.global.u32 %0, [%1];" : "=r"(v) : "l"(p) : "memory"); return v + 1; }
__device__ __forceinline__ void wait_flags(const uint32_t* f, uint32_t tag) {
#pragma unroll 1
  for (int it = 0; it < FL_LIMIT; ++it) if (__all_sync(0xffffffffu, (int)(ld_acquire(f) - tag) >= 0)) return;
  __trap();
}

__device__ __forceinline__ float2 ln_finish(float sum, float sq) {
  const float mean = sum * (1.f / D_), var = fmaxf(fmaf(-mean, mean, sq * (1.f / D_)), 0.f);
  const float mb = bf_round(mean);
  const float vb = bf_round(var);
  const float sd = bf_round(sqrtf(bf_round(vb + 1e-5f)));
  return make_float2(1.0f / sd, -mb);
}

__device__ __forceinline__ void helper_cta(const Params& P, Scratch* sc, int e, int wg, int w) {
  const int tid = threadIdx.x;
  if (tid == 256) {
#pragma unroll
    for (int i = 0; i < 16; i++) mbar_init(bar(i), 1);
    fence_bar_init();
  }
  if (tid < 64) sts16(SM_STG + tid * 16, 0x3f803f80u, 0x3f803f80u, 0x3f803f80u, 0x3f803f80u);
  fence_proxy_async_smem();
  __syncthreads();
  if (wg == 2) {
    if (w == 0) {
#pragma unroll 1
      for (int n = 0; n < 9 * 32; n++) {
        const int job = n >> 5;
        const uint32_t fb = bar(n & 7), dst = SB + (n & 7) * 24576;
        mbar_wait(bar(8 + (n & 7)), (n >> 3) + 1);
        if (elect_one()) {
          mbar_expect_tx(fb, job < 2 ? 24576 : 16384);
          tma4d(dst, &P.tm[job < 2 ? M_WQKV : M_W13], (e * 2 + (n & 1)) * 64, (n & 30) * 32, 0, job < 2 ? job : job - 2, fb);
        }
        __syncwarp();
      }
    }
  } else {
    const uint32_t tag = ld_epoch(sc->epoch + NCTA + e);
    const int lane = tid & 31;
#pragma unroll 1
    for (int job = 0; job < 9; job++) {
      float s[3][4] = {};
#pragma unroll 1
      for (int n = job * 32 + wg; n < job * 32 + 32; n += 2) {
        mbar_wait(bar(n & 7), n >> 3);
        wgmma_fence();
        const uint32_t a = ((SB + (n & 7) * 24576) >> 4) + 0x2000000;
#pragma unroll
        for (int k = 0; k < 8; k++) wgmma_cs(s[k & 1], dsc(0x40000040u, a + (k & 1) * 512 + (k >> 1) * 128), dsc(0x40000040u, (SM_STG >> 4) + 0x10000));
        if (job < 2) {
          wgmma_fence();
#pragma unroll
          for (int k = 0; k < 4; k++) wgmma_cs(s[2], dsc(0x40000040u, a + 1024 + k * 128), dsc(0x40000040u, (SM_STG >> 4) + 0x10000));
        }
        wgmma_commit();
        wgmma_wait<0>();
        mbar_arrive_if(bar(8 + (n & 7)), (tid & 127) == 0);
      }
      if (!(lane & 2))
        st_tag(&sc->cs[job][e * 2 + wg][w * 16 + (lane & 1) * 8 + (lane >> 2)], __float_as_uint(lane & 1 ? s[0][2] : s[0][0]), __float_as_uint(lane & 1 ? s[1][2] : s[1][0]),
               __float_as_uint(lane & 1 ? s[2][2] : s[2][0]), tag);
      __syncwarp();
    }
    bar_sync(NB_END, 256);
    if (tid == 0) sc->epoch[NCTA + e] = tag;
  }
}

template <bool WEIGHTS>
__device__ __forceinline__ void producer(const Params& P, const Ops* ops, int lane, int c, int row, int par, uint32_t t_entry) {
  uint64_t pol;
  asm volatile("createpolicy.fractional.L2::evict_first.b64 %0, 1.0;" : "=l"(pol));
  __syncthreads();
  constexpr int NB = (GEN.n[WEIGHTS] + 31) / 32;
  uint32_t xs[NB + 1];
#pragma unroll
  for (int j = 0; j < NB; j++) xs[j] = __ldg(&ops->x[WEIGHTS][c][j * 32 + lane]);
  xs[NB] = 0;
  uint64_t ys = __ldg(&ops->y[WEIGHTS][lane]);
#pragma unroll 1
  for (int j = 1; j < FIRST; j++) {
    delay_until(t_entry, ST_T1 + (j - 1) * ST_D1);
    if (elect_one()) {
      mbar_expect_tx(bar(B_FULL) + 8 * j, WEIGHTS ? 24576 : 16384);
      if (WEIGHTS) tma4d(SB + j * 40960 + 16384, &P.tm[M_WQKV], c * 64, j * 64, 0, 0, bar(B_FULL) + 8 * j);
      else tma4d(SB + j * 40960, &P.tm[M_X0], 0, row, j, par, bar(B_FULL) + 8 * j);
    }
    __syncwarp();
  }
  if (!WEIGHTS && lane == 0) {
#pragma unroll
    for (int j = 0; j < FIRST; j++) mbar_arrive(bar(B_EMPTY + 2 + j));
  }
  __syncwarp();
  uint32_t xn = __shfl_sync(0xffffffffu, xs[0], 0);
  const uint64_t maps = reinterpret_cast<uint64_t>(&P.tm[WEIGHTS ? M_WQKV : 0]);
  if ((uint32_t)maps > 0xfffffcffu) __trap();
  const uint32_t sb = uni(SB, lane), bars = uni(BARS, lane), zero = uni(0, lane), mlo = uni((uint32_t)maps, lane), mhi = uni(maps >> 32, lane);
#pragma unroll 1
  for (int bt = 0; bt < NB; bt++) {
    const uint32_t xw = lane ? xs[0] : xs[1], y = (uint32_t)ys, bytes = (y & 7) << 13, eb = ((xs[0] >> 15) + 16) & 0x78;
    const int arr = y & 8 ? lane + 1 : 0, solo = y & 16 ? lane + 1 : 0;
    ys >>= 5;
#pragma unroll
    for (int j = 0; j < NB; j++) xs[j] = xs[j + 1];
#pragma unroll 1
    for (int j = 1; j <= 32; j++) {
      const uint32_t x = xn;
      xn = __shfl_sync(0xffffffffu, xw, j);
#define OP_WAIT(X) "{\n.reg .pred pe, pa, pn, ps, pw;\n.reg .u32 it;\n" \
                "elect.sync _|pe, 0xffffffff;\nsetp.eq.u32 pa, %0, %1;\nsetp.ne.and.u32 pn, %2, 0, pe;\n" X \
                "mov.u32 it, 0;\n" \
                "WAIT_%=:\n" \
                "mbarrier.try_wait.parity.shared::cta.b64 pw, [%3 + %9], %4;\n" \
                "@pw bra.uni GO_%=;\n" \
                "add.u32 it, it, 1;\nsetp.lt.u32 pw, it, 0x10000;\n" \
                "@pw bra.uni WAIT_%=;\n" \
                "trap;\n" \
                "GO_%=:\n"
#define OP_ARGS "r"(arr), "r"(j), "r"(x & (1 << 12)), "r"((x >> 21) & 0x3f8), "r"(x >> 31), "r"(((x >> 15) & (WEIGHTS ? 0x78 : 0x1f8)) | bars), "r"(bytes), "r"((x & 0x3e000) | sb), \
                "l"(dsc(mhi, mlo + (WEIGHTS ? (x & 0x38) * 16 : x & 0x180))), "n"(BARS), "r"(x & (WEIGHTS ? 0xfc0 : 63)), "r"(x & (WEIGHTS ? 7 : 64))
      if (WEIGHTS)
        asm volatile(OP_WAIT("setp.ne.and.u32 ps, %17, 0, pe;\n")
                     "@pn cp.async.bulk.tensor.4d.shared::cluster.global.mbarrier::complete_tx::bytes.L2::cache_hint [%7], [%8, {%12, %10, %13, %11}], [%5], %14;\n"
                     "@ps cp.async.bulk.tensor.4d.shared::cluster.global.mbarrier::complete_tx::bytes.L2::cache_hint [%15], [%16, {%12, %10, %13, %11}], [%5], %14;\n"
                     "@pa mbarrier.arrive.expect_tx.shared::cta.b64 _, [%5], %6;\n"
                     "}\n" ::OP_ARGS, "r"(c * 64), "r"(zero), "l"(pol), "r"(((x & 0x3e000) | sb) + 16384),
                     "l"(dsc(mhi, mlo + (M_W13 - M_WQKV) * 128 + ((x >> 15) & 0x180))), "r"((x >> 15) & 0x180) : "memory");
      else
        asm volatile(OP_WAIT(".reg .pred pf;\nsetp.ne.u32 pf, %11, 0;\nsetp.eq.u32 ps, %14, %1;\n")
                     "@pn cp.async.bulk.tensor.4d.shared::cluster.global.mbarrier::complete_tx::bytes [%7], [%8, {%17, %12, %10, %13}], [%5];\n"
                     "@pf fence.proxy.async.shared::cta;\n"
                     "@pa mbarrier.arrive.expect_tx.shared::cta.b64 _, [%5], %6;\n"
                     "@ps mbarrier.arrive.shared::cta.b64 _, [%15 + %16];\n"
                     "}\n" ::OP_ARGS, "r"(row), "r"(par), "r"(solo), "r"(eb), "n"(bar(B_EMPTY)), "r"(zero) : "memory");
    }
  }
}

template <int MODE, uint32_t LO> __device__ __forceinline__ void advance(uint32_t& x, uint32_t inc) {
  constexpr uint32_t LEN = (MODE == 0 ? NU : 24) * 512;
  x += inc; if (x >= LO + LEN) x -= LEN;
}
__device__ __forceinline__ bool full_test(uint32_t i8) {
  uint32_t ok;
  asm volatile("{\n.reg .pred p;\nmbarrier.test_wait.parity.shared::cta.b64 p, [%1 + %3], %2;\nselp.u32 %0, 1, 0, p;\n}\n" : "=r"(ok) : "r"(i8 & 0x78), "r"(i8 >> 7), "n"(bar(B_FULL)) : "memory");
  return ok;
}
__device__ __forceinline__ void full_wait(uint32_t i8) { mbar_wait(bar(B_FULL) + (i8 & 0x78), i8 >> 7); }
__device__ __forceinline__ void release(uint32_t i8, uint32_t p) {
  asm volatile("{\n.reg .pred q;\nsetp.ne.u32 q, %1, 0;\n@q mbarrier.arrive.shared::cta.b64 _, [%0 + %2];\n}\n" ::"r"(i8 & 0x78), "r"(p), "n"(bar(B_EMPTY)) : "memory");
}
template <int MODE, int RELK, int FIRSTK, int N>
__device__ __forceinline__ bool kstep(float (&acc)[2][N], uint32_t hiA, uint32_t hiB, uint32_t& a, uint32_t& b, uint32_t inc, uint32_t& i8, uint32_t x) {
  constexpr uint32_t MI = MODE == 0 ? 64 : 512;
  wgmma_fence();
  if (FIRSTK == 2) { wgmma_z(acc[0], dsc(hiA, a), dsc(hiB, b)); wgmma_z(acc[1], dsc(hiA, a + MI), dsc(hiB, b)); }
  else { wgmma(acc[0], dsc(hiA, a), dsc(hiB, b)); wgmma(acc[1], dsc(hiA, a + MI), dsc(hiB, b)); }
  i8 += 8;
  const bool ok = full_test(i8);
#pragma unroll
  for (int k = 1; k < 4; k++) {
    wgmma(acc[0], dsc(hiA, a + 2 * k), dsc(hiB, b + 128 * k)); wgmma(acc[1], dsc(hiA, a + MI + 2 * k), dsc(hiB, b + 128 * k));
    if (k == RELK || k == 3) wgmma_commit();
    if (k == 3) { advance<MODE, LO_A>(a, inc); advance<MODE, LO_B>(b, inc); }
    if (!FIRSTK && k == RELK) {
      wgmma_wait<1>();
      release(i8, x);
    }
  }
  return ok;
}
template <int MODE, int N, class F, class G>
__device__ __forceinline__ void mainloop(float (&acc)[2][N], uint32_t sig, int t, int wg, uint32_t& sp, F&& prepare, G&& first_half) {
  const uint32_t turn = bar(B_TURN) + 8 * (wg ^ 1);
  constexpr uint32_t hiA = MODE == 0 ? 0x40000080u : 0x40000040u, hiB = 0x40000040u;
  constexpr Seg S0 = GEN.s.seg[0];
  uint32_t i8 = S0.i8 & 0xffff, nxt = S0.end8 & 0xffff, a = S0.a, b = S0.b, inc = S0.end8 >> 16;
  if (MODE != 0 || t != 0) {
    if (MODE == 2 || (MODE == 0 ? t != 12 : t != 4 && t != 15)) mbar_wait(bar(B_TURN) + 8 * wg, TURN_PH >> t);
    i8 = c_sched.seg[sp].i8 & 0xffff; nxt = c_sched.seg[sp].end8 & 0xffff; a = c_sched.seg[sp].a; b = c_sched.seg[sp].b; inc = c_sched.seg[sp].end8 >> 16;
  }
  uint32_t hiA_ = MODE == 1 && N == 64 ? hiA : hiA + (a >> 31);
  full_wait(i8);
  TL(t, 2);
  TS(i8, wg);
  bool ok = kstep<MODE, 3, MODE == 2 ? 1 : 2>(acc, hiA_, hiB, a, b, inc, i8, 0);
  if (MODE == 2 && (t == 2 || t == 13)) bar_sync(NB_OGO, 256);
#pragma unroll 1
  while (true) {
    uint32_t act;
    if (MODE == 1 && N == 64) hiA_ = hiA + (a >> 31);
    if (i8 == nxt) { sp++; nxt = c_sched.seg[sp].end8 & 0xffff; a = c_sched.seg[sp].a; b = c_sched.seg[sp].b; inc = c_sched.seg[sp].end8 >> 16; }
#pragma unroll 1
    while (true) {
      if (!ok) full_wait(i8);
      TS(i8, wg);
      ok = kstep<MODE, MODE == 1 ? 1 : 3, 0>(acc, hiA_, hiB, a, b, inc, i8, sig);
      if (__builtin_expect(i8 == nxt, 0)) {
        act = c_sched.seg[sp++].i8 >> 16;
        if (MODE == 1) mbar_arrive_if(turn, sig & (act >> 1));
        if (act & (MODE == 0 ? A_END | A_DRAIN | A_SYNC : MODE == 1 ? A_END | A_DRAIN : A_END)) break;
        nxt = c_sched.seg[sp].end8 & 0xffff; a = c_sched.seg[sp].a; b = c_sched.seg[sp].b;
        if (MODE == 1) inc = c_sched.seg[sp].end8 >> 16;
      }
    }
    if (MODE == 2 || (MODE == 1 && N == 64) || (act & A_END)) break;
    nxt = c_sched.seg[sp].end8 & 0xffff; a = c_sched.seg[sp].a; b = c_sched.seg[sp].b;
    if (MODE == 1) inc = c_sched.seg[sp].end8 >> 16;
    if (MODE == 0 && (act & A_SYNC)) bar_arrive(NB_PX, 256);
    wgmma_wait<0>();
    release(i8 + 8, sig);
    i8 = c_sched.seg[sp].i8 & 0xffff;
    if (MODE == 1 || (act & A_WAIT)) mbar_wait(bar(B_TURN) + 8 * wg, TURN_PH >> t);
    full_wait(i8);
    if (MODE == 0 && (act & A_SYNC)) bar_sync(NB_PY, 256);
    TS(i8, wg);
    ok = kstep<MODE, 3, 1>(acc, hiA_, hiB, a, b, inc, i8, 0);
  }
  if (MODE != 1) {
    constexpr int TL_ = MODE == 0 ? TAILQ : TAIL;
    uint32_t ta[TL_], tb[TL_];
#pragma unroll
    for (int x = 0; x < TL_; x++) {
      full_wait(i8 + 8 * x);
      TS(i8 + 8 * x, wg);
      ta[x] = a; tb[x] = b;
      advance<MODE, LO_A>(a, inc); advance<MODE, LO_B>(b, inc);
    }
#pragma unroll
    for (int h = 0; h < 2; h++) {
      const int mi = MODE == 0 ? 1 - h : h;
      wgmma_fence();
#pragma unroll
      for (int x = 0; x < TL_; x++)
#pragma unroll
        for (int k = 0; k < 4; k++) wgmma(acc[mi], dsc(hiA, ta[x] + mi * (MODE == 0 ? 64 : 512) + 2 * k), dsc(hiB, tb[x] + 128 * k));
      wgmma_commit();
      if (TL_ > 1 && h == 0) { wgmma_wait<1>(); release(i8 + 8, sig); prepare(); }
    }
    mbar_arrive_if(turn, sig);
    if (TL_ == 1) { wgmma_wait<2>(); release(i8 + 8, sig); prepare(); }
    wgmma_wait<1>();
    first_half();
    wgmma_wait<0>();
#pragma unroll
    for (int x = 0; x < TL_; x++) release(i8 + 16 + 8 * x, sig);
  } else {
    prepare();
    wgmma_wait<0>();
    release(i8 + 8, sig);
  }
}

template <int SWAP, int BY_SM>
__global__ void __launch_bounds__(384, 1) fused_kernel(Scratch* sc, const Ops* ops, const bf16* x0, bf16* out, const __grid_constant__ Params P) {
  extern __shared__ __align__(1024) uint8_t smem_raw[];
  const int tid = threadIdx.x;
  if (tid == 0) prefetch_tmap(&P.tm[M_X0]);
  if (tid == 128) prefetch_tmap(&P.tm[M_WQKV]);
  if (tid == 256) { mbar_init(bar(B_FULL), 2); fence_bar_init(); fence_proxy_async_smem(); }
  const int wg = __shfl_sync(0xffffffffu, tid >> 7, 0);
  const int w = __shfl_sync(0xffffffffu, (tid >> 5) & 3, 0);
  const int lane = tid & 31;
  const uint32_t t_entry = clock_now();
  int b = blockIdx.x;
  if (BY_SM) {
    uint32_t smid; asm volatile("mov.u32 %0, %%smid;" : "=r"(smid));
    const int tp = smid >> 1;
    const int q7 = (tp - 32) * 37 >> 8;
    const int v0 = (tp & 7) * 8 + (tp >> 3), v1 = tp * 8 - 244 - q7 * 55, v2 = tp < 62 ? tp + 4 : tp - 58;
    b = (tp < 32 ? v0 : tp < 60 ? v1 : v2) * 2 + (smid & 1);
  }
  const int mg = (b >> 5) & 3, m = mg * 4 + (b & 3);
  const int c = ((b >> 2) & 7) ^ (BY_SM ? 0 : (mg & 1) * 7);
  const int row0 = (m & 7) * 128, par = m >> 3;
  if (__builtin_expect(b >= NCTA, 0)) { helper_cta(P, sc, b - NCTA, wg, w); return; }
  if (wg == 2 && w == 0) {
    if (elect_one()) {
      tma4d(SB, &P.tm[M_X0], 0, row0, 0, par, bar(B_FULL));
      tma4d(SB + 16384, &P.tm[M_WQKV], c * 64, 0, 0, 0, bar(B_FULL));
      mbar_expect_tx(bar(B_FULL), 40960);
      mbar_arrive(bar(B_FULL));
    }
    __syncwarp();
    TLW(0, 1);
  } else {
    const int g = wg * 4 + w - (wg == 2);
    if (elect_one()) {
#pragma unroll
      for (int x = 1; x < 10; x++) mbar_init(bar(x) + g * 72, g < 4 ? 2 : g == 4 ? 4 : 1);
      fence_bar_init();
      fence_proxy_async_smem();
    }
    __syncwarp();
  }
  if (__builtin_expect(wg == 2, 0)) {
    reg_dealloc<40>();
    if (w < 2) {
      if (w == 0) producer<false>(P, ops, lane, c, row0, par, t_entry);
      else producer<true>(P, ops, lane, c, row0, par, t_entry);
    } else if (w == 2) {
      if (smem_u32(smem_raw) != SB) __trap();
      __syncthreads();
      const uint32_t tag = ld_epoch(sc->epoch + b);
      uint32_t* const flag = sc->flags[m * 8 + c];
      if (lane < 4) asm volatile("st.relaxed.gpu.global.v4.u32 [%0], {%1, %1, %1, %1};" ::"l"(flag + lane * 4), "r"(tag * 32 - 1) : "memory");
      __syncwarp();
      int ev = 0;
      uint32_t t_st = t_entry;
#pragma unroll 1
      for (int t = 0; t < 21; t++) {
        const int i = t >= 11 ? t - 11 : t;
        if (i == 8 || i == 9) continue;
        const bool od = i == 2 || i == 10, wide = i > 2 && i < 7;
        const uint32_t sig = c_sched.task[t].sig;
        const uint32_t pf = i == 0 ? 1 << M_OL | 1 << M_O | 1 << M_WO : i == 1 ? 1 << M_O24 | 1 << M_W13 | 1 << M_W1 | 1 << M_W3 | 1 << M_YL | 1 << M_Y : i == 3 ? 1 << M_HL :
                            i == 5 ? 1 << M_H | 1 << M_W2 : i == 10 ? 1 << M_WQKV | 1 << M_YL | 1 << M_Y : 0;
        if ((pf >> lane) & 1) prefetch_tmap(&P.tm[lane]);
        __syncwarp();
        if (od) {
          asm volatile("{\n.reg .pred pe, pw;\n.reg .u32 it;\nsetp.eq.u32 pe, %4, 1;\nmov.u32 it, 0;\n"
                       "WAIT_%=:\nmbarrier.try_wait.parity.shared::cta.b64 pw, [%0], %1;\n@pw bra.uni GO_%=;\n"
                       "add.u32 it, it, 1;\nsetp.lt.u32 pw, it, 0x10000;\n@pw bra.uni WAIT_%=;\ntrap;\n"
                       "GO_%=:\nfence.proxy.async.global;\nfence.acq_rel.gpu;\n"
                       "@pe red.relaxed.gpu.global.add.u32 [%2], %4;\n@pe mbarrier.arrive.shared::cta.b64 _, [%3];\n}\n"
                       ::"r"(bar(B_SIG + 1)), "r"(sig >> 1), "l"(&sc->cnt[mg][ev] + lane), "r"(bar(B_PUB) + 8 * ev), "r"(lane + 1) : "memory");
          ev++;
          TLW(t, 4);
        }
        if (i == 1) {
          mbar_wait(bar(B_SIG), sig);
          fence_proxy_async_smem();
#pragma unroll 1
          for (int r = 8; r < 128; r += 32) tma4d_store(&P.tm[M_O24], SM_STG + r * 128, row0 + r, 8 + c, par);
        } else {
          const CUtensorMap* mp = &P.tm[i == 0 ? M_OL : od ? M_YL : M_HL];
          const int nr = i && !od ? 64 : 128;
#pragma unroll 1
          for (int x = od ? 3 : i ? 0 : 1; x < (i == 0 || i == 7 ? 2 : 4); x += wide && (i & 1) ? 3 : 1) {
            const bool mine = wide && (x == 0 || x == 3);
            const int r0 = nr == 128 ? 0 : wide ? (x >> 1) * 64 : x * 64, gap = i == 0 ? GAP_O : od ? GAP_Y : i == 7 ? GAP_H6 : x == 0 ? GAP_H0 : GAP_H;
            const int blk = (od ? 1 : i == 0 ? 0 : i == 7 ? 6 : ((i - 3) >> 1) * 3 + (mine ? ((i - 3) & 1) * 2 : 1)) * 8 + c;
            const uint32_t src = od ? SB + ((c_sched.task[t].stg >> 8) & 31) * 8192 : mine ? SM_STG - 8192 : SM_STG + r0 * 128;
            mbar_wait(bar(B_SIG) + 8 * x, sig >> x);
            if (od) mbar_wait(bar(B_DEP - 1) + 8 * ev, 0);
            fence_proxy_async_smem();
            const uint32_t now = clock_now();
            if ((int)(now - t_st) > 0) t_st = now;
#pragma unroll 1
            for (int r = 0; r < nr; r += PROWS) {
              delay_until(t_st, 0);
              t_st += gap;
              tma4d_store(mp, src + r * 128, row0 + r0 + r, blk, par);
            }
            if (wide && x == 0) {
              if (elect_one()) { bulk_commit(); bulk_wait(); mbar_arrive(bar(B_FR0)); }
              __syncwarp();
            }
          }
        }
        if (elect_one()) { bulk_commit(); bulk_wait(); }
        __syncwarp();
        if (i == 1) mbar_wait(bar(B_SIG + 1), sig >> 1);
        if (elect_one()) {
          mbar_arrive(od ? bar(B_SF) : bar(B_FREE));
          if (i < 3 || i > 4) {
            asm volatile("fence.proxy.async.global;" ::: "memory");
            st_release(flag, tag * 32 + ev);
            mbar_arrive(bar(B_PUB) + 8 * ev);
          }
        }
        __syncwarp();
        if (i < 3 || i > 4) ev++;
        if (!od) TLW(t, 4);
      }
      if (lane == 0) sc->epoch[b] = tag;
    } else {
      __syncthreads();
      const uint32_t tag = ld_epoch(sc->epoch + b);
      delay_until(t_entry, WARM_T);
      asm volatile("st.shared.u32 [%0], %1;" ::"r"(SM_TAG + 4), "r"(reinterpret_cast<const uint32_t*>(&c_sched)[min(lane * 16, (int)sizeof(Sched) / 4 - 1)]) : "memory");
      int ncs = 0;
#pragma unroll 1
      for (int it = 0; it < 20; it++) {
        const int l = it >= 11, i = it - l * 11, e = i < 2 ? 0 : i - 2, ev = l * E_N + e;
#pragma unroll 1
        for (; ncs < (it < 2 ? it + 1 : it < 6 ? 2 : 9); ncs++) {
          uint4 v[2];
          ld_tag_wait<300>(v, &sc->cs[ncs][c][lane], tag);
          const uint32_t a = SM_CS + (ncs < 2 ? ncs * 768 : 512 + ncs * 512) + ((lane & 17) | (lane & 6) << 1 | (lane & 8) >> 2) * 4;
#pragma unroll
          for (int j = 0; j < 2; j++) {
            sts4f(a + j * 128, __uint_as_float(v[j].x)); sts4f(a + j * 128 + 256, __uint_as_float(v[j].y));
            if (ncs < 2) sts4f(a + j * 128 + 512, __uint_as_float(v[j].z));
          }
          mbar_arrive_warp(bar(B_CS) + 8 * ncs);
        }
        if (i == 0 || i == 2) {
          const int u = l * 2 + (i >> 1);
          uint4 v[6] = {};
          mbar_wait(bar(B_QT), u);
          if (m & 7) ld_tag_wait<0>(v, &sc->halo[u][m - 1][c][0][lane], tag);
          const uint32_t xa = xch(i, 0) + lane * 16;
          sts16(xa, v[0].x, v[0].y, v[0].z, v[1].x); sts16(xa + 512, v[1].y, v[1].z, v[2].x, v[2].y);
          sts16(xa + 1024, v[2].z, v[3].x, v[3].y, v[3].z); sts16(xa + 1536, v[4].x, v[4].y, v[4].z, v[5].x);
          if (lane < 4) sts16(stat(l * 2) - 64 + lane * 16, v[5].y, 0, v[5].z, 0);
          mbar_arrive_warp(bar(B_XCH));
          continue;
        }
        const bool all = e == E_YA || e == E_XA;
        const uint32_t* fp = all ? &sc->cnt[mg][ev] : sc->flags[m * 8 + (lane & 7)];
        uint32_t want = tag * 32 + (all ? 0 : ev);
        asm volatile("" : "+l"(fp), "+r"(want));
        mbar_wait(bar(B_PUB) + 8 * ev, 0);
        wait_flags(fp, want);
        mbar_arrive_warp(bar(B_DEP) + 8 * ev);
        if (e == E_YB || e == E_XB) {
          const int p = e == E_XB ? 1 : l * 2;
          if (elect_one()) {
            mbar_expect_tx(bar(B_SF + 1), 8192);
            asm volatile("cp.async.bulk.shared::cluster.global.mbarrier::complete_tx::bytes [%0], [%1], 8192, [%2];" ::"r"(SM_STG), "l"(&sc->stat[p][m][0][0]), "r"(bar(B_SF + 1)) : "memory");
          }
          __syncwarp();
          mbar_wait(bar(B_SF + 1), p);
#pragma unroll 1
          for (int h = 0; h < 2; h++) {
            float s0 = 0.f, q0 = 0.f, s1 = 0.f, q1 = 0.f;
#pragma unroll 4
            for (int j = 0; j < 8; j++) {
              float x0, x1, x2, x3;
              lds16f(SM_STG + j * 1024 + h * 512 + lane * 16, x0, x1, x2, x3);
              s0 += x0; q0 += x1; s1 += x2; q1 += x3;
            }
            const float2 r0 = ln_finish(s0, q0), r1 = ln_finish(s1, q1);
            sts16(stat(p + 1) + (h * 64 + lane * 2) * 8, __float_as_uint(r0.x), __float_as_uint(r0.y), __float_as_uint(r1.x), __float_as_uint(r1.y));
          }
          mbar_arrive_warp(bar(B_STAT) + 8 * (p + 1));
        }
      }
    }
  } else {
    const int tw = tid & 127;
    reg_alloc<232>();
    uint32_t sig;
    asm volatile("mov.u32 %0, %1;" : "=r"(sig) : "r"((uint32_t)(tw == 0)));
    __syncthreads();

    if (wg == 1) {
      const uint32_t tag = ld_epoch(sc->epoch + b);
      uint4* const mine = &sc->stat0[m][c * 16 + w * 4 + (lane >> 3)];
      if ((lane & 7) == 0) st_tag(mine, 0, 0, 0, 0);
      __syncwarp();
      delay_until(t_entry, ST_ROWS);
      const bf16* xr = x0 + (size_t)((row0 + c * 16 + w * 4 + (lane >> 3)) * 2 + par) * D_ + (lane & 7) * 8;
      float sum = 0.f, sq = 0.f;
#pragma unroll 1
      for (int j0 = 0; j0 < 16; j0 += 4) {
        uint4 xv[4];
#pragma unroll
        for (int j = 0; j < 4; j++) xv[j] = ldcg16(xr + (j0 + j) * 64);
#pragma unroll
        for (int j = 0; j < 4; j++) {
          const uint32_t x[4] = {xv[j].x, xv[j].y, xv[j].z, xv[j].w};
#pragma unroll
          for (int e = 0; e < 8; e++) { const float d = e & 1 ? bf_hi(x[e >> 1]) : bf_lo(x[e >> 1]); sum += d; sq = fmaf(d, d, sq); }
        }
      }
#pragma unroll
      for (int o = 4; o > 0; o >>= 1) { sum += __shfl_xor_sync(0xffffffffu, sum, o); sq += __shfl_xor_sync(0xffffffffu, sq, o); }
      const float2 fin = ln_finish(sum, sq);
      if ((lane & 7) == 0) st_tag(mine, __float_as_uint(fin.x), __float_as_uint(fin.y), 0, tag);
      __syncwarp();
      TL(22, 5);
      uint4 v[1];
      ld_tag_wait<200>(v, &sc->stat0[m][tw], tag);
      sts8f(stat(0) + tw * 8, __uint_as_float(v[0].x), __uint_as_float(v[0].y));
      if (tw == 0) { asm volatile("st.shared.u32 [%0], %1;" ::"r"(SM_TAG), "r"(tag) : "memory"); sts16(SM_ZERO, 0, 0, 0, 0); }
      mbar_arrive_warp(bar(B_STAT));
      TL(22, 6);
    }

    uint32_t sp = wg * NSEG;
#pragma unroll 1
    for (int t = wg; t < 22; t += 2) {
      const int l = t >= 11, i = t - l * 11;
      if (t == 0) TL(t, 0);
      if (i < 2) {
        float acc[2][96];
        if (w == 3 && (m & 7) < 7) {
#pragma unroll
          for (int j = 0; j < 6; j++) st_tag(&sc->halo[l * 2 + i][m][c][j][lane_now()], 0, 0, 0, 0);
        }
        uint32_t Q[4][8], K[4][8], V[4][8], sta, csa;
        float2 st[4];
        auto fix = [&](int g, int j, float2 cs) {
          const int mi = g & 1, half = g >> 1;
          return pack_bf16_v(fmaf(st[g].y, cs.x, acc[mi][j * 4 + half * 2]), fmaf(st[g].y, cs.y, acc[mi][j * 4 + half * 2 + 1]));
        };
        mainloop<0>(acc, sig, t, wg, sp, [&]() {
          const int lane = lane_now();
          mbar_wait(bar(B_FREE), FREE_PH >> t);
          mbar_wait(bar(B_STAT) + l * 16, 0);
          mbar_wait(bar(B_CS) + i * 8, 0);
          sta = stat(l * 2) + w * 256;
          csa = SM_CS + i * 768 + (lane & 3) * 16;
          st[1] = lds8f(sta + (8 + (lane >> 2)) * 8); st[3] = lds8f(sta + (24 + (lane >> 2)) * 8);
        }, [&]() {
          const int lane = lane_now();
          mbar_arrive_if(bar(B_QT), sig);
#pragma unroll
          for (int j = 0; j < 8; j += 2) {
            float2 c0, c1;
            lds16f(csa + (16 + j) * 32, c0.x, c0.y, c1.x, c1.y);
            V[3][j] = movmat(fix(3, 16 + j, c0)); V[3][j + 1] = movmat(fix(3, 17 + j, c1));
            lds16f(csa + (8 + j) * 32, c0.x, c0.y, c1.x, c1.y);
            K[3][j] = fix(3, 8 + j, c0); K[3][j + 1] = fix(3, 9 + j, c1);
          }
          if (w < 3) {
            const uint32_t xa = xch(i, w + 1) + lane * 16;
            sts16(xa, K[3][0], K[3][1], K[3][2], K[3][3]); sts16(xa + 512, K[3][4], K[3][5], K[3][6], K[3][7]);
            sts16(xa + 1024, V[3][0], V[3][1], V[3][2], V[3][3]); sts16(xa + 1536, V[3][4], V[3][5], V[3][6], V[3][7]);
            mbar_arrive_warp(bar(B_XCH));
          } else if ((m & 7) < 7) {
            const uint32_t tag = lds4(SM_TAG), r0 = lds4(sta + (24 + 2 * (lane & 3)) * 8), r1 = lds4(sta + (25 + 2 * (lane & 3)) * 8);
            uint4* const p = &sc->halo[l * 2 + i][m][c][0][lane];
            st_tag(p, K[3][0], K[3][1], K[3][2], tag); st_tag(p + 32, K[3][3], K[3][4], K[3][5], tag); st_tag(p + 64, K[3][6], K[3][7], V[3][0], tag);
            st_tag(p + 96, V[3][1], V[3][2], V[3][3], tag); st_tag(p + 128, V[3][4], V[3][5], V[3][6], tag); st_tag(p + 160, V[3][7], r0, r1, tag);
          }
        });
        TL(t, 3);
        const int lane = lane_now(), q = lane & 3, r8 = lane >> 2;
        st[0] = lds8f(sta + r8 * 8); st[2] = lds8f(sta + (16 + r8) * 8);
#pragma unroll
        for (int j0 = 22; j0 >= 0; j0 -= 2) {
          float2 cs[2];
          lds16f(csa + j0 * 32, cs[0].x, cs[0].y, cs[1].x, cs[1].y);
#pragma unroll
          for (int j = j0; j < j0 + 2; j++)
#pragma unroll
            for (int g = 0; g < (j < 8 ? 4 : 3); g++) {
              const uint32_t pk = fix(g, j, cs[j - j0]);
              if (j < 8) Q[g][j] = pk; else if (j < 16) K[g][j - 8] = pk; else V[g][j - 16] = movmat(pk);
            }
        }
        const bool up0 = (2 * q) > r8, up1 = (2 * q + 1) > r8;
        const uint32_t mskP = (up0 ? 0xffffu : 0u) | (up1 ? 0xffff0000u : 0u);
        uint32_t ka0 = sta + q * 16 - (up0 ? 64 : 0), ka1 = sta + q * 16 + (up1 ? -56 : 8);
        asm volatile("" : "+r"(ka0), "+r"(ka1));
        TL(t, 5);
        uint32_t Kp[8] = {}, Vp[8] = {}, PS[2][4] = {}, PP[2][4] = {};
        float sS[2][4][2], sP[2][4][2] = {}, O[2][4][4][2], z0, z1, z2, z3;
        auto receive = [&]() {
          const uint32_t xa = xch(i, w) + lane * 16;
          mbar_wait(bar(B_XCH), i);
          lds16(xa, Kp[0], Kp[1], Kp[2], Kp[3]); lds16(xa + 512, Kp[4], Kp[5], Kp[6], Kp[7]);
          lds16(xa + 1024, Vp[0], Vp[1], Vp[2], Vp[3]); lds16(xa + 1536, Vp[4], Vp[5], Vp[6], Vp[7]);
          TL(i == 0 ? 22 : 23, t < 11 ? 3 : 4);
        };
        auto score = [&](float& s0, float& s1, float& s2, float& s3, int g, const uint32_t (&k)[8], int j, bool first) {
          mma16816(s0, s1, s2, s3, Q[g][j], Q[g + 1][j], Q[g][j + 1], Q[g + 1][j + 1], k[j], k[j + 1], first ? z0 : s0, first ? z1 : s1, first ? z2 : s2, first ? z3 : s3);
        };
        auto score0 = [&]() {
          float d[2][2];
#pragma unroll
          for (int x = 0; x < 4; x++) score(sP[x & 1][0][0], sP[x & 1][0][1], d[x & 1][0], d[x & 1][1], 0, Kp, (x & 1) * 4 + (x & 2), x < 2);
        };
        auto softmax = [&](int g) {
          const float rk0 = lds4f(ka0 + g * 64), rk1 = lds4f(ka1 + g * 64);
          const float f = st[g].x * (0.17677669529663687f * LOG2E), f0 = f * rk0, f1 = f * rk1;
          const bool noprev = g == 0 && (m & 7) == 0 && w == 0;
#pragma unroll
          for (int h = 0; h < 2; h++) {
            float v0 = (up0 ? sP[h][g][0] : sS[h][g][0]) * f0, v1 = (up1 ? sP[h][g][1] : sS[h][g][1]) * f1;
            if (noprev && up0) v0 = -1e9f * LOG2E;
            if (noprev && up1) v1 = -1e9f * LOG2E;
            float mx = fmaxf(v0, v1);
            mx = fmaxf(mx, __shfl_xor_sync(0xffffffffu, mx, 1)); mx = fmaxf(mx, __shfl_xor_sync(0xffffffffu, mx, 2));
            const float e0 = ex2f(v0 - mx), e1 = ex2f(v1 - mx);
            float sum = e0 + e1;
            sum += __shfl_xor_sync(0xffffffffu, sum, 1); sum += __shfl_xor_sync(0xffffffffu, sum, 2);
            const float inv = rcpf(sum);
            const uint32_t pk = pack_bf16_v(e0 * rk0 * inv, e1 * rk1 * inv);
            PS[h][g] = pk & ~mskP; PP[h][g] = pk & mskP;
          }
        };
        const uint32_t sa = SM_STG + (w * 32 + (lane & 7)) * 128 + (((lane >> 3) ^ (lane & 7)) << 4);
        auto stage = [&](int g) {
#pragma unroll
          for (int h = 0; h < 2; h++)
            stsm4t((sa ^ (h * 64)) + g * 1024, pack_bf16_v(O[h][g][0][0], O[h][g][0][1]), pack_bf16_v(O[h][g][1][0], O[h][g][1][1]),
                  pack_bf16_v(O[h][g][2][0], O[h][g][2][1]), pack_bf16_v(O[h][g][3][0], O[h][g][3][1]));
        };
        if (i == 0) { receive(); bar_sync(NB_PX, 256); }
        lds16f(SM_ZERO, z0, z1, z2, z3);
        if (i == 0) score0();
        {
          float d[2][2];
#pragma unroll
          for (int x = 0; x < 4; x++) {
            const int h = x & 1, j = h * 4 + (x & 2);
#pragma unroll
            for (int g = 0; g < 3; g++) score(sS[h][g][0], sS[h][g][1], sP[h][g + 1][0], sP[h][g + 1][1], g, K[g], j, x < 2);
            score(d[h][0], d[h][1], sS[h][3][0], sS[h][3][1], 2, K[3], j, x < 2);
          }
        }
        if (i == 0) { bar_arrive(NB_PY, 256); softmax(0); }
#pragma unroll
        for (int g = 1; g < 4; g++) softmax(g);
        TL(23, i == 0 ? (t < 11 ? 5 : 6) : 7);
        if (i == 0) bar_sync(NB_PX + ((PS[0][1] | PS[0][2] | PS[0][3] | PS[1][1] | PS[1][2] | PS[1][3]) & __float_as_uint(z0)), 256);
        lds16f(SM_ZERO, z0, z1, z2, z3);
        auto pv = [&](int g, const uint32_t (&vp)[8]) {
#pragma unroll
          for (int x = 0; x < 8; x += 2) {
            const int h = x >> 2, j = x & 3;
            mma16816(O[h][g][j][0], O[h][g][j][1], O[h][g][j + 1][0], O[h][g][j + 1][1], vp[x], vp[x + 1], V[g][x], V[g][x + 1], PP[h][g], PS[h][g], z0, z1, z2, z3);
          }
        };
        pv(1, V[0]); pv(3, V[2]); pv(2, V[1]);
        if (i) {
          stage(1); stage(2); stage(3);
          mbar_arrive_warp(bar(B_SIG));
          receive(); score0(); softmax(0);
        }
        pv(0, Vp);
        if (i == 0) { bar_arrive(NB_PY, 256); stage(1); stage(2); stage(3); stage(0); }
        else { stage(0); copy_out<2>(SM_STG + w * 4096, sc->o, par * (S_ * D_) + (row0 + w * 32) * 128 + (8 + c) * PANEL, 128, lane); }
        mbar_arrive_warp(bar(B_SIG + 1));
        if (i) bar_arrive(NB_OGO, 256);
        TL(t, 6);
      } else if (i > 2 && i < 7) {
        float acc[2][96], hr[4], mn[16];
        float2 cs[24];
        uint32_t so, sta, csa, sv[8][4];
        const int odd = (i - 3) & 1, blk = ((i - 3) >> 1) * 3;
        auto own_sums = [&](int g) {
#pragma unroll
          for (int x = 0; x < 4; x++) { const int j = (x >> 1) * 8 + g * 4 + (x & 1) * 2; lds16f(csa + odd * 1024 + j * 32, cs[j].x, cs[j].y, cs[j + 1].x, cs[j + 1].y); }
        };
        mainloop<1>(acc, sig, t, wg, sp, [&]() {
          const int lane = lane_now();
          so = SM_STG - 8192 + (w * 16 + (lane & 7)) * 128 + (((lane >> 3) ^ (lane & 7)) << 4);
          sta = stat(l * 2 + 1) + (w * 16 + (lane >> 2)) * 8;
          csa = SM_CS + 1536 + blk * 512 + (lane & 3) * 16;
          mbar_wait(bar(B_STAT + 1) + l * 16, 0);
          mbar_wait(bar(B_CS + 3) + 8 * (blk + odd), 0);
#pragma unroll
          for (int j = 0; j < 4; j++) hr[j] = 0.5f * lds4f(sta + (j >> 1) * 512 + (j & 1) * 64);
          own_sums(0);
          mbar_wait(bar(B_FREE), FREE_PH >> t);
        }, []() {});
        TL(t, 3);
        auto fetch = [&](int x, bool up) {
          const int r = x < 4 ? x & 1 : x < 12 ? (x - 4) >> 1 : 2 + (x & 1);
          if (x < 16) mn[x] = __uint_as_float(lds4(sta + 4 + (r >> 1) * 512 + (r & 1) * 64));
          if (up && x >= 4 && x < 12) ldsm4((so ^ ((x & 1) * 64)) + 8192 + ((r >> 1) * 64 + (r & 1) * 8) * 128, sv[x - 4][0], sv[x - 4][1], sv[x - 4][2], sv[x - 4][3]);
          if (x == 2) own_sums(1);
          if (x == 3) {
#pragma unroll
            for (int j = 16; j < 24; j += 2) lds16f(csa + (SWAP ^ odd) * 256 + j * 32, cs[j].x, cs[j].y, cs[j + 1].x, cs[j + 1].y);
          }
        };
        auto silu = [&](float g, float h) { const float a = g * h; return fmaf(a, tanhf_(a), a); };
        auto own = [&](int mi) {
#pragma unroll
          for (int x = mi * 12; x < mi * 12 + 4; x++) {
            const int g = (x >> 1) & 1, half = x & 1;
            uint32_t v[4];
#pragma unroll
            for (int j = 0; j < 4; j++) {
              const int jg = g * 4 + j + SWAP * 8, ju = jg ^ 8;
              v[j] = pack_bf16(silu(fmaf(mn[x], cs[jg].x, acc[mi][jg * 4 + half * 2]), hr[mi * 2 + half]) * fmaf(mn[x], cs[ju].x, acc[mi][ju * 4 + half * 2]),
                               silu(fmaf(mn[x], cs[jg].y, acc[mi][jg * 4 + half * 2 + 1]), hr[mi * 2 + half]) * fmaf(mn[x], cs[ju].y, acc[mi][ju * 4 + half * 2 + 1]));
            }
            stsm4((so ^ (g * 64)) + half * 1024, v[0], v[1], v[2], v[3]);
            if ((x & 3) == 3) mbar_arrive_warp(bar(B_SIG + mi * 3));
            fetch(x + 2, true);
          }
        };
        auto shared = [&](bool up) {
#pragma unroll
          for (int x = 0; x < 8; x++) {
            const int mi = x >> 2, half = (x >> 1) & 1, g = x & 1;
            uint32_t v[4];
#pragma unroll
            for (int j = 0; j < 4; j++) {
              const int jx = 16 + g * 4 + j;
              const float x0 = fmaf(mn[x + 4], cs[jx].x, acc[mi][jx * 4 + half * 2]), x1 = fmaf(mn[x + 4], cs[jx].y, acc[mi][jx * 4 + half * 2 + 1]);
              v[j] = up ? pack_bf16(bf_lo(sv[x][j]) * x0, bf_hi(sv[x][j]) * x1) : pack_bf16(silu(x0, hr[x >> 1]), silu(x1, hr[x >> 1]));
            }
            stsm4((so ^ (g * 64)) + 8192 + (mi * 64 + half * 8) * 128, v[0], v[1], v[2], v[3]);
            if (up && (x & 3) == 3) mbar_arrive_warp(bar(B_SIG + 1 + mi));
            fetch(x + 6, up);
          }
        };
        fetch(0, false); fetch(1, false);
        own(0);
        if (odd) shared(true); else shared(false);
        TL(t, 5);
        mbar_wait(bar(B_FR0), odd);
        own(1);
        TL(t, 6);
      } else if (i == 7) {
        float acc[2][64];
        float2 cs[16];
        float hr[4];
        uint32_t so, sta;
        mainloop<1>(acc, sig, t, wg, sp, [&]() {
          const int lane = lane_now();
          so = SM_STG + (w * 16 + (lane & 7)) * 128 + (((lane >> 3) ^ (lane & 7)) << 4);
          sta = stat(l * 2 + 1) + (w * 16 + (lane >> 2)) * 8;
          mbar_wait(bar(B_STAT + 1) + l * 16, 0);
          mbar_wait(bar(B_CS + 8), 0);
#pragma unroll
          for (int j = 0; j < 16; j += 2) lds16f(SM_CS + 9 * 512 + (lane & 3) * 16 + j * 32, cs[j].x, cs[j].y, cs[j + 1].x, cs[j + 1].y);
#pragma unroll
          for (int j = 0; j < 4; j++) hr[j] = 0.5f * lds4f(sta + (j >> 1) * 512 + (j & 1) * 64);
        }, []() {});
        mbar_wait(bar(B_FREE), FREE_PH >> t);
        TL(t, 3);
        float mn[8];
#pragma unroll
        for (int x = 0; x < 2; x++) mn[x] = __uint_as_float(lds4(sta + 4 + (x >> 2) * 512 + ((x >> 1) & 1) * 64));
#pragma unroll
        for (int x = 0; x < 8; x++) {
          const int mi = x >> 2, half = (x >> 1) & 1, g = x & 1;
          uint32_t v[4];
#pragma unroll
          for (int j = 0; j < 4; j++) {
            const int jg = g * 4 + j + SWAP * 8, ju = jg ^ 8;
            const float2 cg = cs[jg], cu = cs[ju];
            const float g0 = fmaf(mn[x], cg.x, acc[mi][jg * 4 + half * 2]), g1 = fmaf(mn[x], cg.y, acc[mi][jg * 4 + half * 2 + 1]);
            const float u0 = fmaf(mn[x], cu.x, acc[mi][ju * 4 + half * 2]), u1 = fmaf(mn[x], cu.y, acc[mi][ju * 4 + half * 2 + 1]);
            const float a0 = g0 * hr[x >> 1], a1 = g1 * hr[x >> 1];
            v[j] = pack_bf16(fmaf(a0, tanhf_(a0), a0) * u0, fmaf(a1, tanhf_(a1), a1) * u1);
          }
          stsm4((so ^ (g * 64)) + (mi * 64 + half * 8) * 128, v[0], v[1], v[2], v[3]);
          if ((x & 3) == 3) mbar_arrive_warp(bar(B_SIG + mi));
          if (x + 2 < 8) mn[x + 2] = __uint_as_float(lds4(sta + 4 + ((x + 2) >> 2) * 512 + (((x + 2) >> 1) & 1) * 64));
        }
        TL(t, 6);
      } else if (i == 2 || i == 10) {
        float acc[2][64], rsc[4];
        {
          const int lane = lane_now();
          const uint32_t e = c_sched.task[t].res;
          const uint32_t ra = SB + (w * 16 + (lane & 7)) * 128 + (((lane >> 3) ^ (lane & 7)) << 4);
          float sd[4];
#pragma unroll
          for (int j = 0; j < 4; j++) {
            rsc[j] = i == 10 ? lds4f(stat(l * 2 + 1) + ((j >> 1) * 64 + w * 16 + (j & 1) * 8 + (lane >> 2)) * 8) : 1.f;
            sd[j] = rcpf(rsc[j]);
          }
          const uint32_t zero = lds4(SM_ZERO);
          mbar_wait(bar(B_RES), i == 10);
          uint32_t dep[16];
#pragma unroll
          for (int x = 0; x < 16; x++) {
            const int mi = x >> 3, half = (x >> 2) & 1, g = x & 3;
            uint32_t v[4];
            ldsm4(((e >> ((g >> 1) * 8)) & 31) * 8192 + ((ra ^ ((g & 1) * 64)) | (x >= RLA ? dep[x - RLA] : 0)) + (mi * 64 + half * 8) * 128, v[0], v[1], v[2], v[3]);
#pragma unroll
            for (int j = 0; j < 4; j++) {
              asm volatile("shl.b32 %0, %1, 16;" : "=f"(acc[mi][(g * 4 + j) * 4 + half * 2]) : "r"(v[j]));
              asm volatile("and.b32 %0, %1, 0xffff0000;" : "=f"(acc[mi][(g * 4 + j) * 4 + half * 2 + 1]) : "r"(v[j]));
              acc[mi][(g * 4 + j) * 4 + half * 2] *= sd[mi * 2 + half]; acc[mi][(g * 4 + j) * 4 + half * 2 + 1] *= sd[mi * 2 + half];
            }
            asm("and.b32 %0, %1, %2;" : "=r"(dep[x]) : "f"(acc[mi][(g * 4 + 3) * 4 + half * 2 + 1]), "r"(zero));
          }
          mbar_arrive_warp(bar(B_RF));
        }
        auto stage = [&](int mi, int hi) {
          const int lane = lane_now();
          const uint32_t sw = SB + ((c_sched.task[t].stg >> (8 * hi)) & 31) * 8192 + (mi * 64 + w * 16) * 128, so = sw + (lane & 7) * 128 + (((lane >> 3) ^ (lane & 7)) << 4);
#pragma unroll
          for (int half = 0; half < 2; half++)
#pragma unroll
            for (int g = 0; g < 2; g++) {
              uint32_t v[4];
#pragma unroll
              for (int j = 0; j < 4; j++) {
                acc[mi][(hi * 8 + g * 4 + j) * 4 + half * 2] *= rsc[mi * 2 + half]; acc[mi][(hi * 8 + g * 4 + j) * 4 + half * 2 + 1] *= rsc[mi * 2 + half];
                v[j] = pack_bf16(acc[mi][(hi * 8 + g * 4 + j) * 4 + half * 2], acc[mi][(hi * 8 + g * 4 + j) * 4 + half * 2 + 1]);
              }
              stsm4((so ^ (g * 64)) + half * 1024, v[0], v[1], v[2], v[3]);
            }
          if (mi && !hi) mbar_arrive_warp(bar(B_SIG));
          if (hi == 0 || t == 21) {
            const int pitch = t == 21 ? D_ * 4 : 128;
            copy_out<4>(sw, t == 21 ? out : sc->y, (row0 + mi * 64 + w * 16) * pitch + (t == 21 ? par * (D_ * 2) + (hi * 8 + c) * 128 : par * (S_ * D_) + c * PANEL), pitch, lane);
          }
        };
        mainloop<2>(acc, sig, t, wg, sp, []() {}, [&]() { stage(0, 0); stage(0, 1); });
        TL(t, 3);
        stage(1, 0); mbar_arrive_warp(bar(B_SIG + 1));
        TL(t, 6);
        stage(1, 1); mbar_arrive_warp(bar(B_SIG + 2));
        if (t < 21) {
          const int lane = lane_now(), q = lane & 3;
          const uint32_t zero = lds4(SM_ZERO);
          float s[4], s2[4];
#pragma unroll
          for (int x = 0; x < 4; x++) {
            float a0 = x ? __uint_as_float(__float_as_uint(s[x - 1]) & zero) : 0.f, b0 = x ? __uint_as_float(__float_as_uint(s2[x - 1]) & zero) : 0.f;
#pragma unroll
            for (int j = 0; j < 32; j++) { const float d = acc[x >> 1][(j >> 1) * 4 + (x & 1) * 2 + (j & 1)]; a0 += d; b0 = fmaf(d, d, b0); }
            s[x] = a0; s2[x] = b0;
          }
#pragma unroll
          for (int x = 0; x < 2; x++) {
            s[x] = (q & 2 ? s[x + 2] : s[x]) + __shfl_xor_sync(0xffffffffu, q & 2 ? s[x] : s[x + 2], 2);
            s2[x] = (q & 2 ? s2[x + 2] : s2[x]) + __shfl_xor_sync(0xffffffffu, q & 2 ? s2[x] : s2[x + 2], 2);
          }
          const float r = (q & 1 ? s[1] : s[0]) + __shfl_xor_sync(0xffffffffu, q & 1 ? s[0] : s[1], 1);
          const float r2 = (q & 1 ? s2[1] : s2[0]) + __shfl_xor_sync(0xffffffffu, q & 1 ? s2[0] : s2[1], 1);
          asm volatile("st.global.v2.f32 [%0], {%1, %2};" ::"l"(&sc->stat[i == 10 ? 1 : l * 2][m][c][(q >> 1) * 64 + w * 16 + (q & 1) * 8 + (lane >> 2)]), "f"(r), "f"(r2) : "memory");
          mbar_arrive_warp(bar(B_SIG + 3));
        }
      }
    }
  }
}

typedef CUresult (*PFN_encodeTiled)(CUtensorMap*, CUtensorMapDataType, cuuint32_t, void*, const cuuint64_t*, const cuuint64_t*, const cuuint32_t*,
                                    const cuuint32_t*, CUtensorMapInterleave, CUtensorMapSwizzle, CUtensorMapL2promotion, CUtensorMapFloatOOBfill);

void make_map(PFN_encodeTiled enc, CUtensorMap* mp, const void* ptr, int rank, const cuuint64_t* gd, const cuuint64_t* gs, const cuuint32_t* bd) {
  const cuuint32_t es[4] = {1, 1, 1, 1};
  enc(mp, CU_TENSOR_MAP_DATA_TYPE_BFLOAT16, rank, const_cast<void*>(ptr), gd, gs, bd, es, CU_TENSOR_MAP_INTERLEAVE_NONE, CU_TENSOR_MAP_SWIZZLE_128B,
      CU_TENSOR_MAP_L2_PROMOTION_L2_128B, CU_TENSOR_MAP_FLOAT_OOB_FILL_NONE);
}
void make_map_act(PFN_encodeTiled enc, CUtensorMap* mp, const void* ptr, uint64_t cols, uint64_t s1, uint64_t s2, uint64_t s3, uint32_t rows) {
  const cuuint64_t gd[4] = {64, S_ / 2, cols / 64, 2}, gs[3] = {s1, s2, s3};
  const cuuint32_t bd[4] = {64, rows, 1, 1};
  make_map(enc, mp, ptr, 4, gd, gs, bd);
}
void make_map_w(PFN_encodeTiled enc, CUtensorMap* mp, const void* ptr, uint64_t rows, uint64_t cols, uint32_t np, uint64_t sp, uint64_t tiles, uint32_t nt) {
  const cuuint64_t gd[4] = {512, rows, np, tiles}, gs[3] = {cols * 2, sp, 1024};
  const cuuint32_t bd[4] = {64, 64, np, nt};
  make_map(enc, mp, ptr, 4, gd, gs, bd);
}

}

extern "C" void kernel_launch(void* const* d_in, const int* in_sizes, int n_in, void* d_out, int out_size) {
  (void)in_sizes; (void)n_in; (void)out_size;
  static PFN_encodeTiled enc = nullptr;
  static void *p_sc, *p_ops, *p_w;
  static int by_sm = 0;
  void (*const kernels[4])(Scratch*, const Ops*, const bf16*, bf16*, Params) = {fused_kernel<0, 0>, fused_kernel<1, 0>, fused_kernel<0, 1>, fused_kernel<1, 1>};
  if (!enc) {
    void* fn = nullptr; cudaDriverEntryPointQueryResult qr;
    cudaGetDriverEntryPoint("cuTensorMapEncodeTiled", &fn, cudaEnableDefault, &qr);
    enc = (PFN_encodeTiled)fn;
    cudaGetSymbolAddress(&p_sc, g_sc); cudaGetSymbolAddress(&p_ops, g_ops); cudaGetSymbolAddress(&p_w, g_w13);
    for (int i = 0; i < 4; i++) cudaFuncSetAttribute(kernels[i], cudaFuncAttributeMaxDynamicSharedMemorySize, SM_TOTAL);
    int dev = 0, sms = 0;
    cudaGetDevice(&dev);
    cudaDeviceGetAttribute(&sms, cudaDevAttrMultiProcessorCount, dev);
    by_sm = sms == NCTA + NHELP;
    for (int i = 1; i < 4 && by_sm; i++) {
      cudaLaunchConfig_t cfg = {};
      cudaLaunchAttribute at;
      at.id = cudaLaunchAttributeClusterDimension; at.val.clusterDim.x = 1 << i; at.val.clusterDim.y = at.val.clusterDim.z = 1;
      cfg.gridDim = dim3(NCTA); cfg.blockDim = dim3(384); cfg.dynamicSmemBytes = SM_TOTAL; cfg.attrs = &at; cfg.numAttrs = 1;
      int n = 0;
      if (cudaOccupancyMaxActiveClusters(&n, kernels[0], &cfg) != cudaSuccess) { (void)cudaGetLastError(); n = 0; }
      by_sm = n == (i == 1 ? 66 : i == 2 ? 30 : 15);
    }
  }
  Params P;
  Scratch* const sc = (Scratch*)p_sc;
  make_map_act(enc, &P.tm[M_X0], d_in[0], D_, D_ * 4, 128, D_ * 2, 128);
  make_map_act(enc, &P.tm[M_O], sc->o, D_, 128, PANEL, S_ * D_, 128);
  make_map_act(enc, &P.tm[M_Y], sc->y, D_, 128, PANEL, S_ * D_, 128);
  make_map_act(enc, &P.tm[M_H], sc->h, F_, 128, PANEL, S_ * F_, 128);
  make_map_act(enc, &P.tm[M_OL], sc->o, D_, 128, PANEL, S_ * D_, PROWS);
  make_map_act(enc, &P.tm[M_YL], sc->y, D_, 128, PANEL, S_ * D_, PROWS);
  make_map_act(enc, &P.tm[M_HL], sc->h, F_, 128, PANEL, S_ * F_, PROWS);
  make_map_act(enc, &P.tm[M_O24], sc->o, D_, 128, PANEL, S_ * D_, 24);
  make_map_w(enc, &P.tm[M_WQKV], d_in[1], D_, 3 * D_, 3, D_ * 2, 2, 1);
  make_map_w(enc, &P.tm[M_WO], d_in[2], D_, D_, 2, 1024, 1, 1);
  make_map_w(enc, &P.tm[M_W2], d_in[6], F_, D_, 2, 1024, 1, 1);
  const char *w1 = (const char*)d_in[4], *w3 = (const char*)d_in[5];
  if (w1 == w3 || (uint64_t)(w1 < w3 ? w3 - w1 : w1 - w3) >> 39) {
    cudaMemcpyAsync(p_w, w1, (size_t)D_ * F_ * 2, cudaMemcpyDeviceToDevice);
    cudaMemcpyAsync((bf16*)p_w + D_ * F_, w3, (size_t)D_ * F_ * 2, cudaMemcpyDeviceToDevice);
    w1 = (const char*)p_w; w3 = w1 + (size_t)D_ * F_ * 2;
  }
  const bool swap = w3 < w1;
  make_map_w(enc, &P.tm[M_W13], swap ? w3 : w1, D_, F_, 2, swap ? w1 - w3 : w3 - w1, 7, 1);
  make_map_w(enc, &P.tm[M_W1], w1 + 1024, D_, F_, 1, 1024, 6, 1);
  make_map_w(enc, &P.tm[M_W3], w3 - 1024, D_, F_, 1, 1024, 7, 1);
  kernels[by_sm * 2 + swap]<<<NCTA + NHELP, 384, SM_TOTAL>>>(sc, (const Ops*)p_ops, (const bf16*)d_in[0], (bf16*)d_out, P);
}
```

```cpp
#include <cuda_runtime.h>
#include <cuda_bf16.h>
#include <cuda.h>
#include <stdint.h>
#include <stddef.h>

typedef __nv_bfloat16 bf16;
#define GU_E 4
#define G_N1 8
#define Q_P1 4
#define Q_P2 6
#define Q_P0 1
#define RES_O 3
#define RES_D 2
#define HOLD_O 6
#define PROWS 16
#define GAP_O 150
#define GAP_Y 100
#define GAP_H 350
#define GAP_H6 1000
#define ST_T1 600
#define ST_D1 700
#define ST_ROWS 3500
#define WARM_T 4000
#define CS_T 9000
#define G_HOLD 2
#define D_PAD 0
#define GAP_H0 150
#define RLA 3
#define PADS 0x10000000
constexpr int TAILQ = 1, TAIL = 2;

namespace {

constexpr int S_ = 2048, D_ = 1024, F_ = 3584;
constexpr int PANEL = S_ / 2 * 128;
constexpr int NCTA = 128;
constexpr int NHELP = 4;

constexpr uint32_t SB = 1024;
constexpr int NU = 25;
constexpr uint32_t SM_STG  = SB + NU * 8192;
__host__ __device__ constexpr uint32_t xch(int i, int w) { return i ? SM_STG - 8192 + w * 2048 : SM_STG + w * 4096; }
constexpr uint32_t BARS    = SM_STG + 16384;
constexpr uint32_t SM_STAT = BARS + 896;
__host__ __device__ constexpr uint32_t stat(int set) { return SM_STAT + set * 1088 + 64; }
constexpr uint32_t SM_CS   = SM_STAT + 4352;
constexpr uint32_t SM_END  = SM_CS + 5120;
constexpr int SM_TOTAL = SM_END - SB;
static_assert(BARS % 1024 == 0 && SM_TOTAL <= 232448, "smem");
constexpr int B_FULL = 0, B_EMPTY = 16, B_SIG = 37, B_XCH = 41, B_RF = 42, B_STAT = 45, B_TURN = 49, B_RES = 51, B_FREE = 52, B_SF = 53, B_QT = 55, B_PASS = 56,
              B_CS = 57, B_DEP = 66, B_PUB = 82, B_FR0 = 98, B_N = 100;
__host__ __device__ constexpr uint32_t bar(int i) { return BARS + 8 * i; }
constexpr uint32_t SM_TAG = BARS + 8 * B_N, SM_ZERO = SM_TAG + 16;
constexpr int NB_PX = 1, NB_PY = 2, NB_OGO = 3, NB_END = 4;

constexpr int E_O0 = 0, E_O1 = 1, E_YA = 2, E_YB = 3, E_H = 4, E_XA = 7, E_XB = 8, E_N = 9;

constexpr int M_X0 = 0, M_O = 1, M_Y = 2, M_H = 3;
constexpr int M_WQKV = 4, M_WO = 5, M_W13 = 6, M_W1 = 7, M_W3 = 8, M_W2 = 9;
constexpr int M_OL = 10, M_YL = 11, M_HL = 12, M_O24 = 13, M_N = 14;

constexpr int FIRST = 5;
constexpr int NBAT = 12, NSEG = 48;
constexpr uint32_t A_END = 1, A_TURN = 2, A_DRAIN = 4, A_WAIT = 8, A_SYNC = 16;
constexpr uint32_t A_MARK = 0;
constexpr uint32_t phases(bool turn) {
  uint32_t r = 0, n[2] = {turn ? 0u : 1u, 0};
  for (int t = turn; t < 22; t++) if (turn ? t % 11 < 8 || t % 11 == 10 : t % 11 < 8 && t % 11 != 2) r |= (n[turn ? t & 1 : 0]++ & 1) << t;
  return r;
}
constexpr uint32_t TURN_PH = phases(true), FREE_PH = phases(false);
struct Task { uint32_t stg, res, sig; };
struct Seg { uint32_t i8, end8, a, b; };
constexpr uint32_t LO_A = 0x10000 + SB / 16, LO_B = 0x2000000 + SB / 16;
struct Sched { Seg seg[2 * NSEG]; Task task[22]; };
struct Ops { uint32_t x[2][8][NBAT * 32]; uint64_t y[2][32]; };
struct Gen {
  Sched s{}; Ops o{};
  int n[2] = {0, 0}, nseg[2] = {0, NSEG}, cur = -1, pos = 0, err = 0, res = 0, nres = 0;
  int mask[400] = {}, sa[400] = {}, sb[400][2] = {}, own[NU][2] = {}, tok[NU] = {}, known[2][2] = {{-1, -1}, {-1, -1}};
  constexpr void emit(int p, int wait, int par, int dst, int map, int kb8, int arr, int load, int y) {
    if (cur < FIRST) return;
    const int j = n[p]++;
    if (j >= NBAT * 32) return;
    for (int c = 0; c < 8; c++) {
      const int k = (y & 63) + (((y >> 6) & 7) > c) + (y & (1 << 9) ? c : 0);
      o.x[p][c][j] = (uint32_t)((p ? ((y >> 10) & 7) | (y >> 13) << 22 | (load ? map - M_WQKV : 0) << 3 | k << 6 : k | (y >> 10) << 6 | map << 7) | load << 12 | dst << 13 |
                                (res ? B_RES : B_FULL + (cur & 15)) << 18 | wait << 24) | (uint32_t)(par & 1) << 31;
    }
    o.y[p][j & 31] |= (uint64_t)(kb8 | arr << 3 | (!p && arr && mask[cur] != 3 && !res) << 4) << (j >> 5) * 5;
  }
  constexpr bool done(int p, int x) const { return x < 0 || ((!(mask[x] & 1) || known[p][0] >= x) && (!(mask[x] & 2) || known[p][1] >= x)); }
  constexpr void op(int p, int dst, int nu, int map, int kb8, int arr, int y, int xw = -1, int xp = 0) {
    int w[8] = {}, wp[8] = {}, nw = 0;
    if (xw >= 0) { w[nw] = xw; wp[nw++] = xp; }
    for (int u = dst; u < dst + nu; u++) if (tok[u] && (u == dst || tok[u] != tok[u - 1])) { w[nw] = (tok[u] - 1) >> 1; wp[nw++] = tok[u] - 1; }
    for (int x = cur - 1; x >= 0; x--) {
      bool need = x <= cur - 12;
      for (int u = dst; u < dst + nu; u++) need = need || own[u][0] == x + 1 || own[u][1] == x + 1;
      if (!need || done(p, x)) continue;
      if (cur - x >= 16 || !done(p, x - 16)) err |= 1;
      w[nw] = B_EMPTY + ((x + 2) & 15); wp[nw++] = x >> 4;
      for (int g = 0; g < 2; g++) if (((mask[x] >> g) & 1) && known[p][g] < x) known[p][g] = x;
    }
    for (; nw > 1; nw--) emit(p, w[nw - 1], wp[nw - 1], 0, 0, 0, 0, 0, 0);
    emit(p, nw ? w[0] : B_PASS, nw ? wp[0] : 1, dst, map, kb8, arr, nu > 0, y);
    for (int u = dst; u < dst + nu; u++) { own[u][0] = cur + 1; own[u][1] = 0; tok[u] = 0; }
  }
  constexpr int step(int m) { mask[++cur] = m; return cur; }
  constexpr int slot() { int u = (pos + 1) & ~1; if (u >= 24) u = 0; pos = u + 2; return u; }
  constexpr int alloc(int nu) { if (pos + nu > 24) pos = 0; pos += nu; return pos - nu; }
  constexpr int qslot() { int u = (pos + 4) / 5 * 5; if (u >= NU) u = 0; pos = u + 5; return u; }
  constexpr void stage(int u, int first, int t) {
    first -= TAIL;
    for (int x = u; x < u + 2; x++) { if (own[x][0] > first || own[x][1] > first || tok[x]) err |= 2; own[x][0] = cur + 1; own[x][1] = 0; tok[x] = t; }
  }
  static constexpr int kown(int hi) { return hi * 8 | 1 << 9; }
  static constexpr int kskip(int hi, int j) { return (hi * 8 + j) | (j + 1) << 6; }
  static constexpr int kpos(int p) { return p < 2 ? kown(p) : p < 9 ? kskip(0, p - 2) : kskip(1, p - 9); }
  constexpr void segs(int t, const int* st, const uint32_t* act, int cnt, int tail, int inc0) {
    const int g = t & 1, wrap = inc0 == 5 ? NU : 24;
    int j0 = 0;
    for (int j = 0; j < cnt; j++) {
      const int x = st[j], inc = inc0 ? inc0 : j0 + 1 < cnt ? (sa[st[j0 + 1]] - sa[st[j0]] + wrap) % wrap : 0;
      const bool next = j + 1 < cnt && st[j + 1] == x + 1 && sa[x + 1] == (sa[x] + inc) % wrap && sb[x + 1][g] == (sb[x][g] + inc) % wrap;
      if (j >= cnt - tail - 1 && j + 1 < cnt && !next) err |= 4;
      if (j + 1 < cnt && st[j + 1] != x + 1 && !(act[j] & A_DRAIN)) err |= 8;
      if (j >= cnt - tail || (next && !act[j] && j != cnt - tail - 1)) continue;
      if (j == j0 && (j == 0 || (inc0 != 4 && (act[j - 1] & (A_DRAIN | A_SYNC))))) err |= act[j] ? 16 : 0;
      const int y = st[j0];
      s.seg[nseg[g]++] = Seg{(uint32_t)y * 8 | (act[j] | (j == cnt - tail - 1 ? A_END : 0)) << 16, (uint32_t)(x + 1) * 8 | inc * 512 << 16, LO_A + sa[y] * 512, LO_B + sb[y][g] * 512};
      j0 = j + 1;
    }
  }
  constexpr void residual(int t, int map, bool q) {
    const int u0 = q ? qslot() : slot(), u1 = q ? u0 + 2 : slot();
    res = 1;
    op(0, u0, 2, map, 4, 1, kown(0)); op(0, u1, 2, map, 0, 0, kown(1));
    res = 0;
    for (int x = 0; x < 4; x++) { const int u = (x < 2 ? u0 : u1) + (x & 1); own[u][0] = 0; tok[u] = 1 + B_RF * 2 + (nres & 1); }
    nres++;
    s.task[t].res = u0 | u1 << 8;
  }
  constexpr Gen() {
    int cs[4] = {};
    for (int t = 0; t < 22; t++) {
      const int i = t % 11, use = i == 0 ? 2 : i == 1 || i == 7 ? 3 : i == 3 || i == 5 ? 9 : i == 8 || i == 9 ? 0 : 15;
      for (int x = 0; x < 4; x++) if ((use >> x) & 1) s.task[t].sig |= (cs[x]++ & 1) << x;
    }
    for (int l = 0; l < 2; l++) {
      const int T = l * 11, dep = B_DEP + l * E_N;
      int st[7][56] = {};
      uint32_t act[7][56] = {};
      if (l == 1) {
        const int first = cur + 1;
        for (int j = 0; j < 4; j++) {
          const int x = st[j >> 1][j & 1] = step(1 << ((T + (j >> 1)) & 1)), u = qslot();
          sb[x][0] = sb[x][1] = u + 2;
          if (j < 2) {
            sa[x] = (u + 5) % NU; stage(sa[x], first, j ? 1 + B_SF * 2 + 1 : 0); s.task[10].stg |= sa[x] << (8 * j);
            op(0, 0, 0, 0, 0, 1, 1 << 10, B_SIG + 2 * j, s.task[10].sig >> (2 * j));
          }
          else { sa[x] = sa[x - 2]; own[sa[x]][1] = own[sa[x] + 1][1] = x + 1; op(0, 0, 0, 0, 0, 1, 0); }
          op(1, u + 2, 3, M_WQKV, 3, 1, kown(j & 1) | (j >> 1) << 10);
        }
        act[0][1] = A_DRAIN; act[1][1] = A_DRAIN | A_WAIT;
      }
      for (int i = 0; i < 2; i++) {
        for (int j = 2 * l; j < 16; j++) {
          if (i && j == 16 - RES_O) residual(T + 2, l ? M_Y : M_X0, true);
          const int x = st[i][j] = step(1 << ((T + i) & 1)), u = qslot(), k = l ? kpos(j) : j;
          sa[x] = u; sb[x][0] = sb[x][1] = u + 2;
          op(0, u, 2, l ? M_Y : M_X0, 2, 1, k, l && i == 0 && (j == 2 || j == 9) ? B_DEP + (j == 2 ? E_XA : E_XB) : -1);
          op(1, u + 2, 3, M_WQKV, 3, 1, k | i << 10);
        }
        if (i) act[1][Q_P1 - 1 + (l ? 2 : Q_P0)] = act[1][Q_P2 - 1 + (l ? 2 : Q_P0)] = A_SYNC;
        if (i && own[NU - 1][0] > cur - TAILQ) err |= 256;
        segs(T + i, st[i], act[i], 16, TAILQ, 5);
      }
      for (int j = 0; j < 16; j++) {
        const int x = st[0][j] = step(1 << (T & 1)), k = j < 8 ? j : j == 8 ? kown(1) : kskip(1, j - 9), hold = j == HOLD_O ? B_PUB + l * E_N + E_O1 : -1;
        act[0][j] = j == 8 ? A_MARK : 0;
        if (j != 8) { sa[x] = slot(); op(0, sa[x], 2, M_O, 2, 1, k, j == 0 ? dep + E_O0 : j == 9 ? dep + E_O1 : hold); }
        else { sa[x] = NU; op(0, 0, 0, 0, 0, 1, 1 << 10, B_SIG + 1, s.task[T + 1].sig >> 1); }
        sb[x][0] = sb[x][1] = slot();
        op(1, sb[x][0], 2, M_WO, 2, 1, k, hold);
      }
      segs(T + 2, st[0], act[0], 16, TAIL, 4);
      int beg[6] = {0, 16}, end[5] = {16, 32 - G_N1}, cnt[5] = {}, ord = 0, pm = 0, nrun = 0;
      for (int j = 2; j < 5; j++) { beg[j] = end[j - 2] + GU_E; end[j] = beg[j] + 16; }
      beg[5] = end[4];
      const int first = cur + 1;
      for (int j = 0; j < end[4]; j++) {
        int tl[2] = {-1, -1}, m = 0;
        for (int v = 0; v < 5; v++) if ((j >= beg[v] && j < end[v]) || (v == 1 && j < G_N1)) { const int g = (T + 3 + v) & 1; if (tl[g] >= 0) err |= 32; tl[g] = v; m |= 1 << g; }
        if (!m) err |= 32;
        if (j == end[4] - RES_D) residual(T + 10, M_Y, false);
        const int x = step(m), k = kpos(j < 16 ? j : (j + G_N1) & 15), v0 = m == 3 ? (tl[0] < tl[1] ? tl[0] : tl[1]) : tl[m >> 1];
        if (m != pm) {
          ord = 0;
          pos += ((uint64_t)PADS >> (4 * nrun++)) & 15;
          if (m == 3 && v0 < 3) { if ((0x92 >> (pos & 7)) & 1) pos++; ord = (pos & 7) == 5 ? 1 : (pos & 7) == 2 ? 2 : 0; }
          if (v0 == 4) { pos = (pos + 1) & ~1; for (int y = 0; y < (l ? 0 : D_PAD); y++) slot(); }
          pm = m;
        }
        if (m != 3 && v0 < 4) ord = pos == 20 || pos == 21 ? 1 : pos == 22 ? 0 : ord;
        int ub[2] = {}, n8 = 0;
        for (int y = 0, q = 0; y < (m == 3 ? 3 : 2); y++) {
          if (y == ord) sa[x] = alloc(2);
          else { const int nu = v0 + q < 4 ? 3 : 2; ub[q++] = alloc(nu); n8 += nu; }
        }
        if (j < 2) { stage(sa[x], first, j ? 1 + B_SF * 2 : 0); s.task[T + 2].stg |= sa[x] << (8 * j); op(0, 0, 0, 0, 0, 1, 1 << 10, B_SIG + 2 * j, s.task[T + 2].sig >> (2 * j)); }
        else op(0, sa[x], 2, M_Y, 2, 1, k, j == 2 ? dep + E_YA : j == 9 ? dep + E_YB : -1);
        for (int q = 0; q < (m == 3 ? 2 : 1); q++) {
          const int v = v0 + q, blk = (v >> 1) * 3 + (v & 1) * 2;
          op(1, ub[q], v < 4 ? 3 : 2, M_W13, q ? 0 : n8, !q, k | blk << 10 | (v < 4 ? 1 + (v & 1) : 0) << 13, j == G_HOLD && !q ? B_PUB + l * E_N + E_YA : -1);
          sb[x][(T + 3 + v) & 1] = ub[q];
          act[v][cnt[v]] = j == beg[v + 1] - 1 ? A_TURN : v == 1 && j == G_N1 - 1 ? A_DRAIN | A_WAIT : v == 0 && j == 1 ? A_MARK : 0;
          st[v][cnt[v]++] = x;
        }
      }
      for (int v = 0; v < 5; v++) { if (cnt[v] != 16) err |= 64; segs(T + 3 + v, st[v], act[v], 16, 0, 0); }
      for (int j = 0; j < 56; j++) {
        const int x = st[0][j] = step(1 << (T & 1));
        act[0][j] = 0;
        sa[x] = slot(); op(0, sa[x], 2, M_H, 2, 1, j, j == 0 ? dep + E_H : j == 32 ? dep + E_H + 1 : j == 48 ? dep + E_H + 2 : -1);
        sb[x][0] = sb[x][1] = slot(); op(1, sb[x][0], 2, M_W2, 2, 1, j);
      }
      segs(T + 10, st[0], act[0], 56, TAIL, 4);
    }
    { const int u0 = slot(), u1 = slot(); stage(u0, cur + 1, 0); stage(u1, cur + 1, 0); s.task[21].stg = u0 | u1 << 8; }
    if (n[0] > NBAT * 32 || n[1] > NBAT * 32 || nseg[0] >= NSEG || nseg[1] >= 2 * NSEG) err |= 128;
    for (int p = 0; p < 2; p++) for (int c = 0; c < 8; c++) for (int x = n[p]; x < NBAT * 32; x++) o.x[p][c][x] = B_PASS << 24 | 1u << 31;
  }
};
constexpr Gen GEN{};
static_assert(GEN.err == 0, "schedule");

struct __align__(64) Params {
  CUtensorMap tm[M_N];
};

}

__constant__ Sched c_sched = GEN.s;
__device__ const Ops g_ops = GEN.o;
struct __align__(1024) Scratch {
  float2 stat[3][16][8][128];
  uint4 stat0[16][128];
  uint4 halo[4][16][8][6][32];
  uint4 cs[9][8][64];
  uint32_t flags[NCTA][32];
  uint32_t cnt[4][32];
  uint32_t epoch[NCTA + NHELP];
  __align__(1024) bf16 o[S_ * D_];
  bf16 y[S_ * D_], h[S_ * F_];
};
__device__ Scratch g_sc;
__device__ __align__(1024) bf16 g_w13[2 * D_ * F_];

#define TL(t, i) do {} while (0)
#define TS(i8, wg) do {} while (0)
#define TLW(t, i) do {} while (0)
#define MB_LIMIT (1 << 16)
#define FL_LIMIT (1 << 21)

namespace {

__device__ __forceinline__ uint32_t smem_u32(const void* p) { return (uint32_t)__cvta_generic_to_shared(p); }
__device__ __forceinline__ void mbar_init(uint32_t br, uint32_t cnt) { asm volatile("mbarrier.init.shared::cta.b64 [%0], %1;" ::"r"(br), "r"(cnt)); }
__device__ __forceinline__ void mbar_expect_tx(uint32_t br, uint32_t bytes) { asm volatile("mbarrier.arrive.expect_tx.shared::cta.b64 _, [%0], %1;" ::"r"(br), "r"(bytes) : "memory"); }
__device__ __forceinline__ void mbar_arrive(uint32_t br) { asm volatile("mbarrier.arrive.shared::cta.b64 _, [%0];" ::"r"(br) : "memory"); }
__device__ __forceinline__ void mbar_arrive_if(uint32_t br, uint32_t p) {
  asm volatile("{\n.reg .pred q;\nsetp.ne.u32 q, %1, 0;\n@q mbarrier.arrive.shared::cta.b64 _, [%0];\n}\n" ::"r"(br), "r"(p) : "memory");
}
__device__ __forceinline__ void mbar_arrive_warp(uint32_t br) {
  asm volatile("{\n.reg .pred q;\nbar.warp.sync 0xffffffff;\nelect.sync _|q, 0xffffffff;\n@q mbarrier.arrive.shared::cta.b64 _, [%0];\n}\n" ::"r"(br) : "memory");
}
__device__ __forceinline__ bool mbar_try_wait(uint32_t br, uint32_t parity) {
  uint32_t ok;
  asm volatile("{\n.reg .pred p;\nmbarrier.try_wait.parity.shared::cta.b64 p, [%1], %2;\nselp.u32 %0, 1, 0, p;\n}\n" : "=r"(ok) : "r"(br), "r"(parity) : "memory");
  return ok;
}
__device__ __forceinline__ void mbar_wait(uint32_t br, uint32_t parity) {
#pragma unroll 1
  for (int it = 0; it < MB_LIMIT; ++it) { if (mbar_try_wait(br, parity)) return; }
  __trap();
}
__device__ __forceinline__ bool elect_one() { uint32_t p; asm volatile("{\n.reg .pred P;\nelect.sync _|P, 0xffffffff;\nselp.u32 %0, 1, 0, P;\n}\n" : "=r"(p)); return p; }
__device__ __forceinline__ void fence_proxy_async_smem() { asm volatile("fence.proxy.async.shared::cta;" ::: "memory"); }
__device__ __forceinline__ void tma4d(uint32_t dst, const CUtensorMap* m, int c0, int c1, int c2, int c3, uint32_t br) {
  asm volatile("cp.async.bulk.tensor.4d.shared::cluster.global.mbarrier::complete_tx::bytes [%0], [%1, {%3, %4, %5, %6}], [%2];" ::"r"(dst), "l"(m), "r"(br), "r"(c0), "r"(c1), "r"(c2), "r"(c3) : "memory");
}
__device__ __forceinline__ void tma4d_store(const CUtensorMap* m, uint32_t src, int c1, int c2, int c3) {
  asm volatile("{\n.reg .pred p;\nelect.sync _|p, 0xffffffff;\n@p cp.async.bulk.tensor.4d.global.shared::cta.bulk_group [%0, {%5, %2, %3, %4}], [%1];\n}\n" ::"l"(m), "r"(src), "r"(c1), "r"(c2), "r"(c3), "r"(0) : "memory");
}
__device__ __forceinline__ void stsm4(uint32_t a, uint32_t x, uint32_t y, uint32_t z, uint32_t w) {
  asm volatile("stmatrix.sync.aligned.m8n8.x4.shared.b16 [%0], {%1,%2,%3,%4};" ::"r"(a), "r"(x), "r"(y), "r"(z), "r"(w) : "memory");
}
__device__ __forceinline__ void stsm4t(uint32_t a, uint32_t x, uint32_t y, uint32_t z, uint32_t w) {
  asm volatile("stmatrix.sync.aligned.m8n8.x4.trans.shared.b16 [%0], {%1,%2,%3,%4};" ::"r"(a), "r"(x), "r"(y), "r"(z), "r"(w) : "memory");
}
__device__ __forceinline__ void ldsm4(uint32_t a, uint32_t& x, uint32_t& y, uint32_t& z, uint32_t& w) {
  asm volatile("ldmatrix.sync.aligned.m8n8.x4.shared.b16 {%0,%1,%2,%3}, [%4];" : "=r"(x), "=r"(y), "=r"(z), "=r"(w) : "r"(a) : "memory");
}
__device__ __forceinline__ void st_tag(uint4* p, uint32_t a, uint32_t b, uint32_t c, uint32_t tag) {
  asm volatile("{\n.reg .b64 x, y;\n.reg .b128 z;\nmov.b64 x, {%1, %2};\nmov.b64 y, {%3, %4};\nmov.b128 z, {x, y};\nst.relaxed.gpu.global.b128 [%0], z;\n}\n" ::"l"(p), "r"(a), "r"(b), "r"(c), "r"(tag) : "memory");
}
__device__ __forceinline__ uint4 ld_tag(const uint4* p) {
  uint4 v;
  asm volatile("{\n.reg .b64 x, y;\n.reg .b128 z;\nld.relaxed.gpu.global.b128 z, [%4];\nmov.b128 {x, y}, z;\nmov.b64 {%0, %1}, x;\nmov.b64 {%2, %3}, y;\n}\n" : "=r"(v.x), "=r"(v.y), "=r"(v.z), "=r"(v.w) : "l"(p) : "memory");
  return v;
}
template <int NAP, int N> __device__ __forceinline__ void ld_tag_wait(uint4 (&v)[N], const uint4* p, uint32_t tag) {
#pragma unroll 1
  for (int it = 0; it < FL_LIMIT; ++it) {
    uint32_t bad = 0;
#pragma unroll
    for (int j = 0; j < N; j++) v[j] = ld_tag(p + j * 32);
#pragma unroll
    for (int j = 0; j < N; j++) bad |= v[j].w ^ tag;
    if (__all_sync(0xffffffffu, bad == 0)) return;
    if (NAP) __nanosleep(NAP);
  }
  __trap();
}
__device__ __forceinline__ void prefetch_tmap(const CUtensorMap* m) { asm volatile("prefetch.tensormap [%0];" ::"l"(m) : "memory"); }
__device__ __forceinline__ void wgmma_fence() { asm volatile("wgmma.fence.sync.aligned;" ::: "memory"); }
__device__ __forceinline__ void wgmma_commit() { asm volatile("wgmma.commit_group.sync.aligned;" ::: "memory"); }
template <int N> __device__ __forceinline__ void wgmma_wait() { asm volatile("wgmma.wait_group.sync.aligned %0;" ::"n"(N) : "memory"); }
template <int R> __device__ __forceinline__ void reg_alloc() { asm volatile("setmaxnreg.inc.sync.aligned.u32 %0;" ::"n"(R)); }
template <int R> __device__ __forceinline__ void reg_dealloc() { asm volatile("setmaxnreg.dec.sync.aligned.u32 %0;" ::"n"(R)); }
__device__ __forceinline__ void bar_sync(int id, int n) { asm volatile("bar.sync %0, %1;" ::"r"(id), "r"(n) : "memory"); }
__device__ __forceinline__ void bar_arrive(int id, int n) { asm volatile("bar.arrive %0, %1;" ::"r"(id), "r"(n) : "memory"); }
__device__ __forceinline__ uint32_t ld_acquire(const uint32_t* p) { uint32_t v; asm volatile("ld.acquire.gpu.global.u32 %0, [%1];" : "=r"(v) : "l"(p) : "memory"); return v; }
__device__ __forceinline__ void st_release(uint32_t* p, uint32_t v) { asm volatile("st.release.gpu.global.u32 [%0], %1;" ::"l"(p), "r"(v) : "memory"); }
__device__ __forceinline__ uint4 ldcg16(const void* p) { uint4 v; asm volatile("ld.global.cg.v4.u32 {%0,%1,%2,%3}, [%4];" : "=r"(v.x), "=r"(v.y), "=r"(v.z), "=r"(v.w) : "l"(p) : "memory"); return v; }
__device__ __forceinline__ float2 lds8f(uint32_t a) { float2 v; asm volatile("ld.shared.v2.f32 {%0,%1}, [%2];" : "=f"(v.x), "=f"(v.y) : "r"(a)); return v; }
__device__ __forceinline__ float lds4f(uint32_t a) { float v; asm volatile("ld.shared.f32 %0, [%1];" : "=f"(v) : "r"(a)); return v; }
__device__ __forceinline__ uint32_t lds4(uint32_t a) { uint32_t v; asm volatile("ld.shared.u32 %0, [%1];" : "=r"(v) : "r"(a) : "memory"); return v; }
__device__ __forceinline__ void lds16f(uint32_t a, float& x, float& y, float& z, float& w) { asm volatile("ld.shared.v4.f32 {%0,%1,%2,%3}, [%4];" : "=f"(x), "=f"(y), "=f"(z), "=f"(w) : "r"(a) : "memory"); }
__device__ __forceinline__ void sts8f(uint32_t a, float x, float y) { asm volatile("st.shared.v2.f32 [%0], {%1,%2};" ::"r"(a), "f"(x), "f"(y) : "memory"); }
__device__ __forceinline__ void sts4f(uint32_t a, float x) { asm volatile("st.shared.f32 [%0], %1;" ::"r"(a), "f"(x) : "memory"); }
__device__ __forceinline__ void sts16(uint32_t a, uint32_t x, uint32_t y, uint32_t z, uint32_t w) { asm volatile("st.shared.v4.u32 [%0], {%1,%2,%3,%4};" ::"r"(a), "r"(x), "r"(y), "r"(z), "r"(w) : "memory"); }
__device__ __forceinline__ void lds16(uint32_t a, uint32_t& x, uint32_t& y, uint32_t& z, uint32_t& w) { asm volatile("ld.shared.v4.u32 {%0,%1,%2,%3}, [%4];" : "=r"(x), "=r"(y), "=r"(z), "=r"(w) : "r"(a) : "memory"); }
__device__ __forceinline__ uint32_t pack_bf16(float a, float b) { uint32_t r; asm("cvt.rn.bf16x2.f32 %0, %1, %2;" : "=r"(r) : "f"(b), "f"(a)); return r; }
__device__ __forceinline__ uint32_t pack_bf16_v(float a, float b) { uint32_t r; asm volatile("cvt.rn.bf16x2.f32 %0, %1, %2;" : "=r"(r) : "f"(b), "f"(a)); return r; }
__device__ __forceinline__ float bf_lo(uint32_t v) { return __uint_as_float(v << 16); }
__device__ __forceinline__ float bf_hi(uint32_t v) { return __uint_as_float(v & 0xffff0000u); }
constexpr float LOG2E = 1.4426950408889634f;
__device__ __forceinline__ float ex2f(float x) { float y; asm("ex2.approx.ftz.f32 %0, %1;" : "=f"(y) : "f"(x)); return y; }
__device__ __forceinline__ float tanhf_(float x) { float y; asm("tanh.approx.f32 %0, %1;" : "=f"(y) : "f"(x)); return y; }
__device__ __forceinline__ float rcpf(float x) { float y; asm("rcp.approx.ftz.f32 %0, %1;" : "=f"(y) : "f"(x)); return y; }
__device__ __forceinline__ float bf_round(float a) { return bf_lo(pack_bf16(a, 0.f)); }
__device__ __forceinline__ uint32_t movmat(uint32_t a) { uint32_t d; asm volatile("movmatrix.sync.aligned.m8n8.trans.b16 %0, %1;" : "=r"(d) : "r"(a)); return d; }
__device__ __forceinline__ void mma16816(float& d0, float& d1, float& d2, float& d3, uint32_t a0, uint32_t a1, uint32_t a2, uint32_t a3, uint32_t b0, uint32_t b1,
                                         float c0, float c1, float c2, float c3) {
  asm volatile("mma.sync.aligned.m16n8k16.row.col.f32.bf16.bf16.f32 {%0,%1,%2,%3}, {%4,%5,%6,%7}, {%8,%9}, {%10,%11,%12,%13};"
               : "=f"(d0), "=f"(d1), "=f"(d2), "=f"(d3) : "r"(a0), "r"(a1), "r"(a2), "r"(a3), "r"(b0), "r"(b1), "f"(c0), "f"(c1), "f"(c2), "f"(c3));
}
template <int N> __device__ __forceinline__ void copy_out(uint32_t a, void* base, uint32_t ofs, int pitch, int lane) {
  a += (lane >> 3) * 128 + (((lane ^ (lane >> 3)) & 7) << 4);
  char* const g = static_cast<char*>(base) + (ofs + (lane >> 3) * pitch + (lane & 7) * 16);
  uint32_t v[N][4];
  __syncwarp();
#pragma unroll
  for (int j = 0; j < N; j++) lds16((a ^ ((j & 1) * 64)) + j * 512, v[j][0], v[j][1], v[j][2], v[j][3]);
#pragma unroll
  for (int j = 0; j < N; j++) asm volatile("st.global.v4.u32 [%0], {%1, %2, %3, %4};" ::"l"(g + j * 4 * pitch), "r"(v[j][0]), "r"(v[j][1]), "r"(v[j][2]), "r"(v[j][3]) : "memory");
}
__device__ __forceinline__ int lane_now() { int v; asm volatile("mov.u32 %0, %%laneid;" : "=r"(v)); return v; }
__device__ __forceinline__ uint32_t uni(uint32_t x, int lane) { return __shfl_sync(0xffffffffu, x + lane, 0); }
__device__ __forceinline__ uint64_t dsc(uint32_t hi, uint32_t lo) { return ((uint64_t)hi << 32) | lo; }

#define R8(a, o) "+f"(a[o]), "+f"(a[o + 1]), "+f"(a[o + 2]), "+f"(a[o + 3]), "+f"(a[o + 4]), "+f"(a[o + 5]), "+f"(a[o + 6]), "+f"(a[o + 7])
#define R32(a, o) R8(a, o), R8(a, o + 8), R8(a, o + 16), R8(a, o + 24)
#define REG64 "%0, %1, %2, %3, %4, %5, %6, %7, %8, %9, %10, %11, %12, %13, %14, %15, %16, %17, %18, %19, %20, %21, %22, %23, %24, %25, %26, %27, %28, %29, %30, %31, " \
              "%32, %33, %34, %35, %36, %37, %38, %39, %40, %41, %42, %43, %44, %45, %46, %47, %48, %49, %50, %51, %52, %53, %54, %55, %56, %57, %58, %59, %60, %61, %62, %63"
#define REG96 REG64 ", %64, %65, %66, %67, %68, %69, %70, %71, %72, %73, %74, %75, %76, %77, %78, %79, %80, %81, %82, %83, %84, %85, %86, %87, %88, %89, %90, %91, %92, %93, %94, %95"
__device__ __forceinline__ void wgmma(float (&d)[64], uint64_t da, uint64_t db) {
  asm volatile("wgmma.mma_async.sync.aligned.m64n128k16.f32.bf16.bf16 {" REG64 "}, %64, %65, 1, 1, 1, 0, 1;\n"
               : R32(d, 0), R32(d, 32) : "l"(da), "l"(db));
}
__device__ __forceinline__ void wgmma(float (&d)[96], uint64_t da, uint64_t db) {
  asm volatile("wgmma.mma_async.sync.aligned.m64n192k16.f32.bf16.bf16 {" REG96 "}, %96, %97, 1, 1, 1, 0, 1;\n"
               : R32(d, 0), R32(d, 32), R32(d, 64) : "l"(da), "l"(db));
}
#define W8(a, o) "=f"(a[o]), "=f"(a[o + 1]), "=f"(a[o + 2]), "=f"(a[o + 3]), "=f"(a[o + 4]), "=f"(a[o + 5]), "=f"(a[o + 6]), "=f"(a[o + 7])
#define W32(a, o) W8(a, o), W8(a, o + 8), W8(a, o + 16), W8(a, o + 24)
__device__ __forceinline__ void wgmma_z(float (&d)[64], uint64_t da, uint64_t db) {
  asm volatile("wgmma.mma_async.sync.aligned.m64n128k16.f32.bf16.bf16 {" REG64 "}, %64, %65, 0, 1, 1, 0, 1;\n"
               : W32(d, 0), W32(d, 32) : "l"(da), "l"(db));
}
__device__ __forceinline__ void wgmma_z(float (&d)[96], uint64_t da, uint64_t db) {
  asm volatile("wgmma.mma_async.sync.aligned.m64n192k16.f32.bf16.bf16 {" REG96 "}, %96, %97, 0, 1, 1, 0, 1;\n"
               : W32(d, 0), W32(d, 32), W32(d, 64) : "l"(da), "l"(db));
}

__device__ __forceinline__ void wgmma_cs(float (&d)[4], uint64_t da, uint64_t db) {
  asm volatile("wgmma.mma_async.sync.aligned.m64n8k16.f32.bf16.bf16 {%0, %1, %2, %3}, %4, %5, 1, 1, 1, 1, 0;\n" : "+f"(d[0]), "+f"(d[1]), "+f"(d[2]), "+f"(d[3]) : "l"(da), "l"(db));
}
__device__ __forceinline__ void bulk_commit() { asm volatile("cp.async.bulk.commit_group;" ::: "memory"); }
__device__ __forceinline__ void bulk_wait() { asm volatile("cp.async.bulk.wait_group 0;" ::: "memory"); }
__device__ __forceinline__ void fence_bar_init() { asm volatile("fence.mbarrier_init.release.cluster;" ::: "memory"); }

__device__ __forceinline__ uint32_t clock_now() { uint32_t v; asm volatile("mov.u32 %0, %%clock;" : "=r"(v)); return v; }
__device__ __forceinline__ void delay_until(uint32_t t0, int cycles) {
#pragma unroll 1
  for (int it = 0; it < 1000 && (int)(clock_now() - t0) < cycles; it++) __nanosleep(40);
}
__device__ __forceinline__ uint32_t ld_epoch(const uint32_t* p) { uint32_t v; asm volatile("ld.global.u32 %0, [%1];" : "=r"(v) : "l"(p) : "memory"); return v + 1; }
__device__ __forceinline__ void wait_flags(const uint32_t* f, uint32_t tag) {
#pragma unroll 1
  for (int it = 0; it < FL_LIMIT; ++it) if (__all_sync(0xffffffffu, (int)(ld_acquire(f) - tag) >= 0)) return;
  __trap();
}

__device__ __forceinline__ float2 ln_finish(float sum, float sq) {
  const float mean = sum * (1.f / D_), var = fmaxf(fmaf(-mean, mean, sq * (1.f / D_)), 0.f);
  const float mb = bf_round(mean);
  const float vb = bf_round(var);
  const float sd = bf_round(sqrtf(bf_round(vb + 1e-5f)));
  return make_float2(1.0f / sd, -mb);
}

__device__ __forceinline__ void helper_cta(const Params& P, Scratch* sc, int e, int wg, int w) {
  const int tid = threadIdx.x;
  if (tid == 256) {
#pragma unroll
    for (int i = 0; i < 16; i++) mbar_init(bar(i), 1);
    fence_bar_init();
  }
  if (tid < 64) sts16(SM_STG + tid * 16, 0x3f803f80u, 0x3f803f80u, 0x3f803f80u, 0x3f803f80u);
  fence_proxy_async_smem();
  __syncthreads();
  if (wg == 2) {
    if (w == 0) {
#pragma unroll 1
      for (int n = 0; n < 9 * 32; n++) {
        const int job = n >> 5;
        const uint32_t fb = bar(n & 7), dst = SB + (n & 7) * 24576;
        mbar_wait(bar(8 + (n & 7)), (n >> 3) + 1);
        if (elect_one()) {
          mbar_expect_tx(fb, job < 2 ? 24576 : 16384);
          tma4d(dst, &P.tm[job < 2 ? M_WQKV : M_W13], (e * 2 + (n & 1)) * 64, (n & 30) * 32, 0, job < 2 ? job : job - 2, fb);
        }
        __syncwarp();
      }
    }
  } else {
    const uint32_t tag = ld_epoch(sc->epoch + NCTA + e);
    const int lane = tid & 31;
#pragma unroll 1
    for (int job = 0; job < 9; job++) {
      float s[3][4] = {};
#pragma unroll 1
      for (int n = job * 32 + wg; n < job * 32 + 32; n += 2) {
        mbar_wait(bar(n & 7), n >> 3);
        wgmma_fence();
        const uint32_t a = ((SB + (n & 7) * 24576) >> 4) + 0x2000000;
#pragma unroll
        for (int k = 0; k < 8; k++) wgmma_cs(s[k & 1], dsc(0x40000040u, a + (k & 1) * 512 + (k >> 1) * 128), dsc(0x40000040u, (SM_STG >> 4) + 0x10000));
        if (job < 2) {
          wgmma_fence();
#pragma unroll
          for (int k = 0; k < 4; k++) wgmma_cs(s[2], dsc(0x40000040u, a + 1024 + k * 128), dsc(0x40000040u, (SM_STG >> 4) + 0x10000));
        }
        wgmma_commit();
        wgmma_wait<0>();
        mbar_arrive_if(bar(8 + (n & 7)), (tid & 127) == 0);
      }
      if (!(lane & 2))
        st_tag(&sc->cs[job][e * 2 + wg][w * 16 + (lane & 1) * 8 + (lane >> 2)], __float_as_uint(lane & 1 ? s[0][2] : s[0][0]), __float_as_uint(lane & 1 ? s[1][2] : s[1][0]),
               __float_as_uint(lane & 1 ? s[2][2] : s[2][0]), tag);
      __syncwarp();
    }
    bar_sync(NB_END, 256);
    if (tid == 0) sc->epoch[NCTA + e] = tag;
  }
}

template <bool WEIGHTS>
__device__ __forceinline__ void producer(const Params& P, const Ops* ops, int lane, int c, int row, int par, uint32_t t_entry) {
  uint64_t pol;
  asm volatile("createpolicy.fractional.L2::evict_first.b64 %0, 1.0;" : "=l"(pol));
  __syncthreads();
  constexpr int NB = (GEN.n[WEIGHTS] + 31) / 32;
  uint32_t xs[NB + 1];
#pragma unroll
  for (int j = 0; j < NB; j++) xs[j] = __ldg(&ops->x[WEIGHTS][c][j * 32 + lane]);
  xs[NB] = 0;
  uint64_t ys = __ldg(&ops->y[WEIGHTS][lane]);
#pragma unroll 1
  for (int j = 1; j < FIRST; j++) {
    delay_until(t_entry, ST_T1 + (j - 1) * ST_D1);
    if (elect_one()) {
      mbar_expect_tx(bar(B_FULL) + 8 * j, WEIGHTS ? 24576 : 16384);
      if (WEIGHTS) tma4d(SB + j * 40960 + 16384, &P.tm[M_WQKV], c * 64, j * 64, 0, 0, bar(B_FULL) + 8 * j);
      else tma4d(SB + j * 40960, &P.tm[M_X0], 0, row, j, par, bar(B_FULL) + 8 * j);
    }
    __syncwarp();
  }
  if (!WEIGHTS && lane == 0) {
#pragma unroll
    for (int j = 0; j < FIRST; j++) mbar_arrive(bar(B_EMPTY + 2 + j));
  }
  __syncwarp();
  uint32_t xn = __shfl_sync(0xffffffffu, xs[0], 0);
  const uint64_t maps = reinterpret_cast<uint64_t>(&P.tm[WEIGHTS ? M_WQKV : 0]);
  if ((uint32_t)maps > 0xfffffcffu) __trap();
  const uint32_t sb = uni(SB, lane), bars = uni(BARS, lane), zero = uni(0, lane), mlo = uni((uint32_t)maps, lane), mhi = uni(maps >> 32, lane);
#pragma unroll 1
  for (int bt = 0; bt < NB; bt++) {
    const uint32_t xw = lane ? xs[0] : xs[1], y = (uint32_t)ys, bytes = (y & 7) << 13, eb = ((xs[0] >> 15) + 16) & 0x78;
    const int arr = y & 8 ? lane + 1 : 0, solo = y & 16 ? lane + 1 : 0;
    ys >>= 5;
#pragma unroll
    for (int j = 0; j < NB; j++) xs[j] = xs[j + 1];
#pragma unroll 1
    for (int j = 1; j <= 32; j++) {
      const uint32_t x = xn;
      xn = __shfl_sync(0xffffffffu, xw, j);
#define OP_WAIT(X) "{\n.reg .pred pe, pa, pn, ps, pw;\n.reg .u32 it;\n" \
                "elect.sync _|pe, 0xffffffff;\nsetp.eq.u32 pa, %0, %1;\nsetp.ne.and.u32 pn, %2, 0, pe;\n" X \
                "mov.u32 it, 0;\n" \
                "WAIT_%=:\n" \
                "mbarrier.try_wait.parity.shared::cta.b64 pw, [%3 + %9], %4;\n" \
                "@pw bra.uni GO_%=;\n" \
                "add.u32 it, it, 1;\nsetp.lt.u32 pw, it, 0x10000;\n" \
                "@pw bra.uni WAIT_%=;\n" \
                "trap;\n" \
                "GO_%=:\n"
#define OP_ARGS "r"(arr), "r"(j), "r"(x & (1 << 12)), "r"((x >> 21) & 0x3f8), "r"(x >> 31), "r"(((x >> 15) & (WEIGHTS ? 0x78 : 0x1f8)) | bars), "r"(bytes), "r"((x & 0x3e000) | sb), \
                "l"(dsc(mhi, mlo + (WEIGHTS ? (x & 0x38) * 16 : x & 0x180))), "n"(BARS), "r"(x & (WEIGHTS ? 0xfc0 : 63)), "r"(x & (WEIGHTS ? 7 : 64))
      if (WEIGHTS)
        asm volatile(OP_WAIT("setp.ne.and.u32 ps, %17, 0, pe;\n")
                     "@pn cp.async.bulk.tensor.4d.shared::cluster.global.mbarrier::complete_tx::bytes.L2::cache_hint [%7], [%8, {%12, %10, %13, %11}], [%5], %14;\n"
                     "@ps cp.async.bulk.tensor.4d.shared::cluster.global.mbarrier::complete_tx::bytes.L2::cache_hint [%15], [%16, {%12, %10, %13, %11}], [%5], %14;\n"
                     "@pa mbarrier.arrive.expect_tx.shared::cta.b64 _, [%5], %6;\n"
                     "}\n" ::OP_ARGS, "r"(c * 64), "r"(zero), "l"(pol), "r"(((x & 0x3e000) | sb) + 16384),
                     "l"(dsc(mhi, mlo + (M_W13 - M_WQKV) * 128 + ((x >> 15) & 0x180))), "r"((x >> 15) & 0x180) : "memory");
      else
        asm volatile(OP_WAIT(".reg .pred pf;\nsetp.ne.u32 pf, %11, 0;\nsetp.eq.u32 ps, %14, %1;\n")
                     "@pn cp.async.bulk.tensor.4d.shared::cluster.global.mbarrier::complete_tx::bytes [%7], [%8, {%17, %12, %10, %13}], [%5];\n"
                     "@pf fence.proxy.async.shared::cta;\n"
                     "@pa mbarrier.arrive.expect_tx.shared::cta.b64 _, [%5], %6;\n"
                     "@ps mbarrier.arrive.shared::cta.b64 _, [%15 + %16];\n"
                     "}\n" ::OP_ARGS, "r"(row), "r"(par), "r"(solo), "r"(eb), "n"(bar(B_EMPTY)), "r"(zero) : "memory");
    }
  }
}

template <int MODE, uint32_t LO> __device__ __forceinline__ void advance(uint32_t& x, uint32_t inc) {
  constexpr uint32_t LEN = (MODE == 0 ? NU : 24) * 512;
  x += inc; if (x >= LO + LEN) x -= LEN;
}
__device__ __forceinline__ bool full_test(uint32_t i8) {
  uint32_t ok;
  asm volatile("{\n.reg .pred p;\nmbarrier.test_wait.parity.shared::cta.b64 p, [%1 + %3], %2;\nselp.u32 %0, 1, 0, p;\n}\n" : "=r"(ok) : "r"(i8 & 0x78), "r"(i8 >> 7), "n"(bar(B_FULL)) : "memory");
  return ok;
}
__device__ __forceinline__ void full_wait(uint32_t i8) { mbar_wait(bar(B_FULL) + (i8 & 0x78), i8 >> 7); }
__device__ __forceinline__ void release(uint32_t i8, uint32_t p) {
  asm volatile("{\n.reg .pred q;\nsetp.ne.u32 q, %1, 0;\n@q mbarrier.arrive.shared::cta.b64 _, [%0 + %2];\n}\n" ::"r"(i8 & 0x78), "r"(p), "n"(bar(B_EMPTY)) : "memory");
}
template <int MODE, int RELK, int FIRSTK, int N>
__device__ __forceinline__ bool kstep(float (&acc)[2][N], uint32_t hiA, uint32_t hiB, uint32_t& a, uint32_t& b, uint32_t inc, uint32_t& i8, uint32_t x) {
  constexpr uint32_t MI = MODE == 0 ? 64 : 512;
  wgmma_fence();
  if (FIRSTK == 2) { wgmma_z(acc[0], dsc(hiA, a), dsc(hiB, b)); wgmma_z(acc[1], dsc(hiA, a + MI), dsc(hiB, b)); }
  else { wgmma(acc[0], dsc(hiA, a), dsc(hiB, b)); wgmma(acc[1], dsc(hiA, a + MI), dsc(hiB, b)); }
  i8 += 8;
  const bool ok = full_test(i8);
#pragma unroll
  for (int k = 1; k < 4; k++) {
    wgmma(acc[0], dsc(hiA, a + 2 * k), dsc(hiB, b + 128 * k)); wgmma(acc[1], dsc(hiA, a + MI + 2 * k), dsc(hiB, b + 128 * k));
    if (k == RELK || k == 3) wgmma_commit();
    if (k == 3) { advance<MODE, LO_A>(a, inc); advance<MODE, LO_B>(b, inc); }
    if (!FIRSTK && k == RELK) {
      wgmma_wait<1>();
      release(i8, x);
    }
  }
  return ok;
}
template <int MODE, int N, class F, class G>
__device__ __forceinline__ void mainloop(float (&acc)[2][N], uint32_t sig, int t, int wg, uint32_t& sp, F&& prepare, G&& first_half) {
  const uint32_t turn = bar(B_TURN) + 8 * (wg ^ 1);
  constexpr uint32_t hiA = MODE == 0 ? 0x40000080u : 0x40000040u, hiB = 0x40000040u;
  constexpr Seg S0 = GEN.s.seg[0];
  uint32_t i8 = S0.i8 & 0xffff, nxt = S0.end8 & 0xffff, a = S0.a, b = S0.b, inc = S0.end8 >> 16;
  if (MODE != 0 || t != 0) {
    if (MODE == 2 || (MODE == 0 ? t != 12 : t != 4 && t != 15)) mbar_wait(bar(B_TURN) + 8 * wg, TURN_PH >> t);
    i8 = c_sched.seg[sp].i8 & 0xffff; nxt = c_sched.seg[sp].end8 & 0xffff; a = c_sched.seg[sp].a; b = c_sched.seg[sp].b; inc = c_sched.seg[sp].end8 >> 16;
  }
  const uint32_t hiA_ = hiA + (a >> 31);
  full_wait(i8);
  TL(t, 2);
  TS(i8, wg);
  bool ok = kstep<MODE, 3, MODE == 2 ? 1 : 2>(acc, hiA_, hiB, a, b, inc, i8, 0);
  if (MODE == 2 && (t == 2 || t == 13)) bar_sync(NB_OGO, 256);
#pragma unroll 1
  while (true) {
    uint32_t act;
    if (i8 == nxt) { sp++; nxt = c_sched.seg[sp].end8 & 0xffff; a = c_sched.seg[sp].a; b = c_sched.seg[sp].b; inc = c_sched.seg[sp].end8 >> 16; }
#pragma unroll 1
    while (true) {
      if (!ok) full_wait(i8);
      TS(i8, wg);
      ok = kstep<MODE, MODE == 1 ? 1 : 3, 0>(acc, hiA_, hiB, a, b, inc, i8, sig);
      if (__builtin_expect(i8 == nxt, 0)) {
        act = c_sched.seg[sp++].i8 >> 16;
        if (MODE == 1) mbar_arrive_if(turn, sig & (act >> 1));
        if (act & (MODE == 0 ? A_END | A_DRAIN | A_SYNC : MODE == 1 ? A_END | A_DRAIN : A_END)) break;
        nxt = c_sched.seg[sp].end8 & 0xffff; a = c_sched.seg[sp].a; b = c_sched.seg[sp].b;
        if (MODE == 1) inc = c_sched.seg[sp].end8 >> 16;
      }
    }
    if (MODE == 2 || (MODE == 1 && N == 64) || (act & A_END)) break;
    nxt = c_sched.seg[sp].end8 & 0xffff; a = c_sched.seg[sp].a; b = c_sched.seg[sp].b;
    if (MODE == 1) inc = c_sched.seg[sp].end8 >> 16;
    if (MODE == 0 && (act & A_SYNC)) bar_arrive(NB_PX, 256);
    wgmma_wait<0>();
    release(i8 + 8, sig);
    i8 = c_sched.seg[sp].i8 & 0xffff;
    if (MODE == 1 || (act & A_WAIT)) mbar_wait(bar(B_TURN) + 8 * wg, TURN_PH >> t);
    full_wait(i8);
    if (MODE == 0 && (act & A_SYNC)) bar_sync(NB_PY, 256);
    TS(i8, wg);
    ok = kstep<MODE, 3, 1>(acc, hiA_, hiB, a, b, inc, i8, 0);
  }
  if (MODE != 1) {
    constexpr int TL_ = MODE == 0 ? TAILQ : TAIL;
    uint32_t ta[TL_], tb[TL_];
#pragma unroll
    for (int x = 0; x < TL_; x++) {
      full_wait(i8 + 8 * x);
      TS(i8 + 8 * x, wg);
      ta[x] = a; tb[x] = b;
      advance<MODE, LO_A>(a, inc); advance<MODE, LO_B>(b, inc);
    }
#pragma unroll
    for (int h = 0; h < 2; h++) {
      const int mi = MODE == 0 ? 1 - h : h;
      wgmma_fence();
#pragma unroll
      for (int x = 0; x < TL_; x++)
#pragma unroll
        for (int k = 0; k < 4; k++) wgmma(acc[mi], dsc(hiA, ta[x] + mi * (MODE == 0 ? 64 : 512) + 2 * k), dsc(hiB, tb[x] + 128 * k));
      wgmma_commit();
      if (TL_ > 1 && h == 0) { wgmma_wait<1>(); release(i8 + 8, sig); prepare(); }
    }
    mbar_arrive_if(turn, sig);
    if (TL_ == 1) { wgmma_wait<2>(); release(i8 + 8, sig); prepare(); }
    wgmma_wait<1>();
    first_half();
    wgmma_wait<0>();
#pragma unroll
    for (int x = 0; x < TL_; x++) release(i8 + 16 + 8 * x, sig);
  } else {
    prepare();
    wgmma_wait<0>();
    release(i8 + 8, sig);
  }
}

template <int SWAP, int BY_SM>
__global__ void __launch_bounds__(384, 1) fused_kernel(Scratch* sc, const Ops* ops, const bf16* x0, bf16* out, const __grid_constant__ Params P) {
  extern __shared__ __align__(1024) uint8_t smem_raw[];
  const int tid = threadIdx.x;
  if (tid == 0) prefetch_tmap(&P.tm[M_X0]);
  if (tid == 128) prefetch_tmap(&P.tm[M_WQKV]);
  if (tid == 256) { mbar_init(bar(B_FULL), 2); fence_bar_init(); fence_proxy_async_smem(); }
  const int wg = __shfl_sync(0xffffffffu, tid >> 7, 0);
  const int w = __shfl_sync(0xffffffffu, (tid >> 5) & 3, 0);
  const int lane = tid & 31;
  const uint32_t t_entry = clock_now();
  int b = blockIdx.x;
  if (BY_SM) {
    uint32_t smid; asm volatile("mov.u32 %0, %%smid;" : "=r"(smid));
    const int tp = smid >> 1;
    const int q7 = (tp - 32) * 37 >> 8;
    const int v0 = (tp & 7) * 8 + (tp >> 3), v1 = tp * 8 - 244 - q7 * 55, v2 = tp < 62 ? tp + 4 : tp - 58;
    b = (tp < 32 ? v0 : tp < 60 ? v1 : v2) * 2 + (smid & 1);
  }
  const int mg = (b >> 5) & 3, m = mg * 4 + (b & 3);
  const int c = ((b >> 2) & 7) ^ (BY_SM ? 0 : (mg & 1) * 7);
  const int row0 = (m & 7) * 128, par = m >> 3;
  if (__builtin_expect(b >= NCTA, 0)) { helper_cta(P, sc, b - NCTA, wg, w); return; }
  if (wg == 2 && w == 0) {
    if (elect_one()) {
      tma4d(SB, &P.tm[M_X0], 0, row0, 0, par, bar(B_FULL));
      tma4d(SB + 16384, &P.tm[M_WQKV], c * 64, 0, 0, 0, bar(B_FULL));
      mbar_expect_tx(bar(B_FULL), 40960);
      mbar_arrive(bar(B_FULL));
    }
    __syncwarp();
    TLW(0, 1);
  } else {
    const int g = wg * 4 + w - (wg == 2);
    if (elect_one()) {
#pragma unroll
      for (int x = 1; x < 10; x++) mbar_init(bar(x) + g * 72, g < 4 ? 2 : g == 4 ? 4 : 1);
      fence_bar_init();
      fence_proxy_async_smem();
    }
    __syncwarp();
  }
  if (__builtin_expect(wg == 2, 0)) {
    reg_dealloc<40>();
    if (w < 2) {
      if (w == 0) producer<false>(P, ops, lane, c, row0, par, t_entry);
      else producer<true>(P, ops, lane, c, row0, par, t_entry);
    } else if (w == 2) {
      if (smem_u32(smem_raw) != SB) __trap();
      __syncthreads();
      const uint32_t tag = ld_epoch(sc->epoch + b);
      uint32_t* const flag = sc->flags[m * 8 + c];
      if (lane < 4) asm volatile("st.relaxed.gpu.global.v4.u32 [%0], {%1, %1, %1, %1};" ::"l"(flag + lane * 4), "r"(tag * 32 - 1) : "memory");
      __syncwarp();
      delay_until(t_entry, WARM_T);
      asm volatile("st.shared.u32 [%0], %1;" ::"r"(SM_TAG + 4), "r"(reinterpret_cast<const uint32_t*>(&c_sched)[min(lane * 16, (int)sizeof(Sched) / 4 - 1)]) : "memory");
      int ev = 0;
      uint32_t t_st = t_entry;
#pragma unroll 1
      for (int t = 0; t < 21; t++) {
        const int i = t >= 11 ? t - 11 : t;
        if (i == 8 || i == 9) continue;
        const bool od = i == 2 || i == 10, wide = i > 2 && i < 7;
        const uint32_t sig = c_sched.task[t].sig;
        const uint32_t pf = i == 0 ? 1 << M_OL | 1 << M_O | 1 << M_WO : i == 1 ? 1 << M_O24 | 1 << M_W13 | 1 << M_W1 | 1 << M_W3 | 1 << M_YL | 1 << M_Y : i == 3 ? 1 << M_HL :
                            i == 5 ? 1 << M_H | 1 << M_W2 : i == 10 ? 1 << M_WQKV | 1 << M_YL | 1 << M_Y : 0;
        if ((pf >> lane) & 1) prefetch_tmap(&P.tm[lane]);
        __syncwarp();
        if (od) {
          asm volatile("{\n.reg .pred pe, pw;\n.reg .u32 it;\nsetp.eq.u32 pe, %4, 1;\nmov.u32 it, 0;\n"
                       "WAIT_%=:\nmbarrier.try_wait.parity.shared::cta.b64 pw, [%0], %1;\n@pw bra.uni GO_%=;\n"
                       "add.u32 it, it, 1;\nsetp.lt.u32 pw, it, 0x10000;\n@pw bra.uni WAIT_%=;\ntrap;\n"
                       "GO_%=:\nfence.proxy.async.global;\nfence.acq_rel.gpu;\n"
                       "@pe red.relaxed.gpu.global.add.u32 [%2], %4;\n@pe mbarrier.arrive.shared::cta.b64 _, [%3];\n}\n"
                       ::"r"(bar(B_SIG + 1)), "r"(sig >> 1), "l"(&sc->cnt[mg][ev] + lane), "r"(bar(B_PUB) + 8 * ev), "r"(lane + 1) : "memory");
          ev++;
          TLW(t, 4);
        }
        if (i == 1) {
          mbar_wait(bar(B_SIG), sig);
          fence_proxy_async_smem();
#pragma unroll 1
          for (int r = 8; r < 128; r += 32) tma4d_store(&P.tm[M_O24], SM_STG + r * 128, row0 + r, 8 + c, par);
        } else {
          const CUtensorMap* mp = &P.tm[i == 0 ? M_OL : od ? M_YL : M_HL];
          const int nr = i && !od ? 64 : 128;
#pragma unroll 1
          for (int x = od ? 3 : i ? 0 : 1; x < (i == 0 || i == 7 ? 2 : 4); x += wide && (i & 1) ? 3 : 1) {
            const bool mine = wide && (x == 0 || x == 3);
            const int r0 = nr == 128 ? 0 : wide ? (x >> 1) * 64 : x * 64, gap = i == 0 ? GAP_O : od ? GAP_Y : i == 7 ? GAP_H6 : x == 0 ? GAP_H0 : GAP_H;
            const int blk = (od ? 1 : i == 0 ? 0 : i == 7 ? 6 : ((i - 3) >> 1) * 3 + (mine ? ((i - 3) & 1) * 2 : 1)) * 8 + c;
            const uint32_t src = od ? SB + ((c_sched.task[t].stg >> 8) & 31) * 8192 : mine ? SM_STG - 8192 : SM_STG + r0 * 128;
            mbar_wait(bar(B_SIG) + 8 * x, sig >> x);
            if (od) mbar_wait(bar(B_DEP - 1) + 8 * ev, 0);
            fence_proxy_async_smem();
            const uint32_t now = clock_now();
            if ((int)(now - t_st) > 0) t_st = now;
#pragma unroll 1
            for (int r = 0; r < nr; r += PROWS) {
              delay_until(t_st, 0);
              t_st += gap;
              tma4d_store(mp, src + r * 128, row0 + r0 + r, blk, par);
            }
            if (wide && x == 0) {
              if (elect_one()) { bulk_commit(); bulk_wait(); mbar_arrive(bar(B_FR0)); }
              __syncwarp();
            }
          }
        }
        if (elect_one()) { bulk_commit(); bulk_wait(); }
        __syncwarp();
        if (i == 1) mbar_wait(bar(B_SIG + 1), sig >> 1);
        if (elect_one()) {
          mbar_arrive(od ? bar(B_SF) : bar(B_FREE));
          if (i < 3 || i > 4) {
            asm volatile("fence.proxy.async.global;" ::: "memory");
            st_release(flag, tag * 32 + ev);
            mbar_arrive(bar(B_PUB) + 8 * ev);
          }
        }
        __syncwarp();
        if (i < 3 || i > 4) ev++;
        if (!od) TLW(t, 4);
      }
      if (lane == 0) sc->epoch[b] = tag;
    } else {
      __syncthreads();
      const uint32_t tag = ld_epoch(sc->epoch + b);
      delay_until(t_entry, CS_T);
      int ncs = 0;
#pragma unroll 1
      for (int it = 0; it < 20; it++) {
        const int l = it >= 11, i = it - l * 11, e = i < 2 ? 0 : i - 2, ev = l * E_N + e;
#pragma unroll 1
        for (; ncs < (it < 2 ? it + 1 : it < 6 ? 2 : 9); ncs++) {
          uint4 v[2];
          ld_tag_wait<300>(v, &sc->cs[ncs][c][lane], tag);
          const uint32_t a = SM_CS + (ncs < 2 ? ncs * 768 : 512 + ncs * 512) + ((lane & 17) | (lane & 6) << 1 | (lane & 8) >> 2) * 4;
#pragma unroll
          for (int j = 0; j < 2; j++) {
            sts4f(a + j * 128, __uint_as_float(v[j].x)); sts4f(a + j * 128 + 256, __uint_as_float(v[j].y));
            if (ncs < 2) sts4f(a + j * 128 + 512, __uint_as_float(v[j].z));
          }
          mbar_arrive_warp(bar(B_CS) + 8 * ncs);
        }
        if (i == 0 || i == 2) {
          const int u = l * 2 + (i >> 1);
          uint4 v[6] = {};
          mbar_wait(bar(B_QT), u);
          if (m & 7) ld_tag_wait<0>(v, &sc->halo[u][m - 1][c][0][lane], tag);
          const uint32_t xa = xch(i, 0) + lane * 16;
          sts16(xa, v[0].x, v[0].y, v[0].z, v[1].x); sts16(xa + 512, v[1].y, v[1].z, v[2].x, v[2].y);
          sts16(xa + 1024, v[2].z, v[3].x, v[3].y, v[3].z); sts16(xa + 1536, v[4].x, v[4].y, v[4].z, v[5].x);
          if (lane < 4) sts16(stat(l * 2) - 64 + lane * 16, v[5].y, 0, v[5].z, 0);
          mbar_arrive_warp(bar(B_XCH));
          continue;
        }
        const bool all = e == E_YA || e == E_XA;
        const uint32_t* fp = all ? &sc->cnt[mg][ev] : sc->flags[m * 8 + (lane & 7)];
        uint32_t want = tag * 32 + (all ? 0 : ev);
        asm volatile("" : "+l"(fp), "+r"(want));
        mbar_wait(bar(B_PUB) + 8 * ev, 0);
        wait_flags(fp, want);
        mbar_arrive_warp(bar(B_DEP) + 8 * ev);
        if (e == E_YB || e == E_XB) {
          const int p = e == E_XB ? 1 : l * 2;
          if (elect_one()) {
            mbar_expect_tx(bar(B_SF + 1), 8192);
            asm volatile("cp.async.bulk.shared::cluster.global.mbarrier::complete_tx::bytes [%0], [%1], 8192, [%2];" ::"r"(SM_STG), "l"(&sc->stat[p][m][0][0]), "r"(bar(B_SF + 1)) : "memory");
          }
          __syncwarp();
          mbar_wait(bar(B_SF + 1), p);
#pragma unroll 1
          for (int h = 0; h < 2; h++) {
            float s0 = 0.f, q0 = 0.f, s1 = 0.f, q1 = 0.f;
#pragma unroll 4
            for (int j = 0; j < 8; j++) {
              float x0, x1, x2, x3;
              lds16f(SM_STG + j * 1024 + h * 512 + lane * 16, x0, x1, x2, x3);
              s0 += x0; q0 += x1; s1 += x2; q1 += x3;
            }
            const float2 r0 = ln_finish(s0, q0), r1 = ln_finish(s1, q1);
            sts16(stat(p + 1) + (h * 64 + lane * 2) * 8, __float_as_uint(r0.x), __float_as_uint(r0.y), __float_as_uint(r1.x), __float_as_uint(r1.y));
          }
          mbar_arrive_warp(bar(B_STAT) + 8 * (p + 1));
        }
      }
    }
  } else {
    const int tw = tid & 127;
    reg_alloc<232>();
    uint32_t sig;
    asm volatile("mov.u32 %0, %1;" : "=r"(sig) : "r"((uint32_t)(tw == 0)));
    __syncthreads();

    if (wg == 1) {
      const uint32_t tag = ld_epoch(sc->epoch + b);
      uint4* const mine = &sc->stat0[m][c * 16 + w * 4 + (lane >> 3)];
      if ((lane & 7) == 0) st_tag(mine, 0, 0, 0, 0);
      __syncwarp();
      delay_until(t_entry, ST_ROWS);
      const bf16* xr = x0 + (size_t)((row0 + c * 16 + w * 4 + (lane >> 3)) * 2 + par) * D_ + (lane & 7) * 8;
      float sum = 0.f, sq = 0.f;
#pragma unroll 1
      for (int j0 = 0; j0 < 16; j0 += 4) {
        uint4 xv[4];
#pragma unroll
        for (int j = 0; j < 4; j++) xv[j] = ldcg16(xr + (j0 + j) * 64);
#pragma unroll
        for (int j = 0; j < 4; j++) {
          const uint32_t x[4] = {xv[j].x, xv[j].y, xv[j].z, xv[j].w};
#pragma unroll
          for (int e = 0; e < 8; e++) { const float d = e & 1 ? bf_hi(x[e >> 1]) : bf_lo(x[e >> 1]); sum += d; sq = fmaf(d, d, sq); }
        }
      }
#pragma unroll
      for (int o = 4; o > 0; o >>= 1) { sum += __shfl_xor_sync(0xffffffffu, sum, o); sq += __shfl_xor_sync(0xffffffffu, sq, o); }
      const float2 fin = ln_finish(sum, sq);
      if ((lane & 7) == 0) st_tag(mine, __float_as_uint(fin.x), __float_as_uint(fin.y), 0, tag);
      __syncwarp();
      TL(22, 5);
      uint4 v[1];
      ld_tag_wait<200>(v, &sc->stat0[m][tw], tag);
      sts8f(stat(0) + tw * 8, __uint_as_float(v[0].x), __uint_as_float(v[0].y));
      if (tw == 0) { asm volatile("st.shared.u32 [%0], %1;" ::"r"(SM_TAG), "r"(tag) : "memory"); sts16(SM_ZERO, 0, 0, 0, 0); }
      mbar_arrive_warp(bar(B_STAT));
      TL(22, 6);
    }

    uint32_t sp = wg * NSEG;
#pragma unroll 1
    for (int t = wg; t < 22; t += 2) {
      const int l = t >= 11, i = t - l * 11;
      if (t == 0) TL(t, 0);
      if (i < 2) {
        float acc[2][96];
        if (w == 3 && (m & 7) < 7) {
#pragma unroll
          for (int j = 0; j < 6; j++) st_tag(&sc->halo[l * 2 + i][m][c][j][lane_now()], 0, 0, 0, 0);
        }
        uint32_t Q[4][8], K[4][8], V[4][8], sta, csa;
        float2 st[4];
        auto fix = [&](int g, int j, float2 cs) {
          const int mi = g & 1, half = g >> 1;
          return pack_bf16_v(fmaf(st[g].y, cs.x, acc[mi][j * 4 + half * 2]), fmaf(st[g].y, cs.y, acc[mi][j * 4 + half * 2 + 1]));
        };
        mainloop<0>(acc, sig, t, wg, sp, [&]() {
          const int lane = lane_now();
          mbar_wait(bar(B_FREE), FREE_PH >> t);
          mbar_wait(bar(B_STAT) + l * 16, 0);
          mbar_wait(bar(B_CS) + i * 8, 0);
          sta = stat(l * 2) + w * 256;
          csa = SM_CS + i * 768 + (lane & 3) * 16;
          st[1] = lds8f(sta + (8 + (lane >> 2)) * 8); st[3] = lds8f(sta + (24 + (lane >> 2)) * 8);
        }, [&]() {
          const int lane = lane_now();
          mbar_arrive_if(bar(B_QT), sig);
#pragma unroll
          for (int j = 0; j < 8; j += 2) {
            float2 c0, c1;
            lds16f(csa + (16 + j) * 32, c0.x, c0.y, c1.x, c1.y);
            V[3][j] = movmat(fix(3, 16 + j, c0)); V[3][j + 1] = movmat(fix(3, 17 + j, c1));
            lds16f(csa + (8 + j) * 32, c0.x, c0.y, c1.x, c1.y);
            K[3][j] = fix(3, 8 + j, c0); K[3][j + 1] = fix(3, 9 + j, c1);
          }
          if (w < 3) {
            const uint32_t xa = xch(i, w + 1) + lane * 16;
            sts16(xa, K[3][0], K[3][1], K[3][2], K[3][3]); sts16(xa + 512, K[3][4], K[3][5], K[3][6], K[3][7]);
            sts16(xa + 1024, V[3][0], V[3][1], V[3][2], V[3][3]); sts16(xa + 1536, V[3][4], V[3][5], V[3][6], V[3][7]);
            mbar_arrive_warp(bar(B_XCH));
          } else if ((m & 7) < 7) {
            const uint32_t tag = lds4(SM_TAG), r0 = lds4(sta + (24 + 2 * (lane & 3)) * 8), r1 = lds4(sta + (25 + 2 * (lane & 3)) * 8);
            uint4* const p = &sc->halo[l * 2 + i][m][c][0][lane];
            st_tag(p, K[3][0], K[3][1], K[3][2], tag); st_tag(p + 32, K[3][3], K[3][4], K[3][5], tag); st_tag(p + 64, K[3][6], K[3][7], V[3][0], tag);
            st_tag(p + 96, V[3][1], V[3][2], V[3][3], tag); st_tag(p + 128, V[3][4], V[3][5], V[3][6], tag); st_tag(p + 160, V[3][7], r0, r1, tag);
          }
        });
        TL(t, 3);
        const int lane = lane_now(), q = lane & 3, r8 = lane >> 2;
        st[0] = lds8f(sta + r8 * 8); st[2] = lds8f(sta + (16 + r8) * 8);
#pragma unroll
        for (int j0 = 22; j0 >= 0; j0 -= 2) {
          float2 cs[2];
          lds16f(csa + j0 * 32, cs[0].x, cs[0].y, cs[1].x, cs[1].y);
#pragma unroll
          for (int j = j0; j < j0 + 2; j++)
#pragma unroll
            for (int g = 0; g < (j < 8 ? 4 : 3); g++) {
              const uint32_t pk = fix(g, j, cs[j - j0]);
              if (j < 8) Q[g][j] = pk; else if (j < 16) K[g][j - 8] = pk; else V[g][j - 16] = movmat(pk);
            }
        }
        const bool up0 = (2 * q) > r8, up1 = (2 * q + 1) > r8;
        const uint32_t mskP = (up0 ? 0xffffu : 0u) | (up1 ? 0xffff0000u : 0u);
        uint32_t ka0 = sta + q * 16 - (up0 ? 64 : 0), ka1 = sta + q * 16 + (up1 ? -56 : 8);
        asm volatile("" : "+r"(ka0), "+r"(ka1));
        TL(t, 5);
        uint32_t Kp[8] = {}, Vp[8] = {}, PS[2][4] = {}, PP[2][4] = {};
        float sS[2][4][2], sP[2][4][2] = {}, O[2][4][4][2], z0, z1, z2, z3;
        auto receive = [&]() {
          const uint32_t xa = xch(i, w) + lane * 16;
          mbar_wait(bar(B_XCH), i);
          lds16(xa, Kp[0], Kp[1], Kp[2], Kp[3]); lds16(xa + 512, Kp[4], Kp[5], Kp[6], Kp[7]);
          lds16(xa + 1024, Vp[0], Vp[1], Vp[2], Vp[3]); lds16(xa + 1536, Vp[4], Vp[5], Vp[6], Vp[7]);
          TL(i == 0 ? 22 : 23, t < 11 ? 3 : 4);
        };
        auto score = [&](float& s0, float& s1, float& s2, float& s3, int g, const uint32_t (&k)[8], int j, bool first) {
          mma16816(s0, s1, s2, s3, Q[g][j], Q[g + 1][j], Q[g][j + 1], Q[g + 1][j + 1], k[j], k[j + 1], first ? z0 : s0, first ? z1 : s1, first ? z2 : s2, first ? z3 : s3);
        };
        auto score0 = [&]() {
          float d[2][2];
#pragma unroll
          for (int x = 0; x < 4; x++) score(sP[x & 1][0][0], sP[x & 1][0][1], d[x & 1][0], d[x & 1][1], 0, Kp, (x & 1) * 4 + (x & 2), x < 2);
        };
        auto softmax = [&](int g) {
          const float rk0 = lds4f(ka0 + g * 64), rk1 = lds4f(ka1 + g * 64);
          const float f = st[g].x * (0.17677669529663687f * LOG2E), f0 = f * rk0, f1 = f * rk1;
          const bool noprev = g == 0 && (m & 7) == 0 && w == 0;
#pragma unroll
          for (int h = 0; h < 2; h++) {
            float v0 = (up0 ? sP[h][g][0] : sS[h][g][0]) * f0, v1 = (up1 ? sP[h][g][1] : sS[h][g][1]) * f1;
            if (noprev && up0) v0 = -1e9f * LOG2E;
            if (noprev && up1) v1 = -1e9f * LOG2E;
            float mx = fmaxf(v0, v1);
            mx = fmaxf(mx, __shfl_xor_sync(0xffffffffu, mx, 1)); mx = fmaxf(mx, __shfl_xor_sync(0xffffffffu, mx, 2));
            const float e0 = ex2f(v0 - mx), e1 = ex2f(v1 - mx);
            float sum = e0 + e1;
            sum += __shfl_xor_sync(0xffffffffu, sum, 1); sum += __shfl_xor_sync(0xffffffffu, sum, 2);
            const float inv = rcpf(sum);
            const uint32_t pk = pack_bf16_v(e0 * rk0 * inv, e1 * rk1 * inv);
            PS[h][g] = pk & ~mskP; PP[h][g] = pk & mskP;
          }
        };
        const uint32_t sa = SM_STG + (w * 32 + (lane & 7)) * 128 + (((lane >> 3) ^ (lane & 7)) << 4);
        auto stage = [&](int g) {
#pragma unroll
          for (int h = 0; h < 2; h++)
            stsm4t((sa ^ (h * 64)) + g * 1024, pack_bf16_v(O[h][g][0][0], O[h][g][0][1]), pack_bf16_v(O[h][g][1][0], O[h][g][1][1]),
                  pack_bf16_v(O[h][g][2][0], O[h][g][2][1]), pack_bf16_v(O[h][g][3][0], O[h][g][3][1]));
        };
        if (i == 0) { receive(); bar_sync(NB_PX, 256); }
        lds16f(SM_ZERO, z0, z1, z2, z3);
        if (i == 0) score0();
        {
          float d[2][2];
#pragma unroll
          for (int x = 0; x < 4; x++) {
            const int h = x & 1, j = h * 4 + (x & 2);
#pragma unroll
            for (int g = 0; g < 3; g++) score(sS[h][g][0], sS[h][g][1], sP[h][g + 1][0], sP[h][g + 1][1], g, K[g], j, x < 2);
            score(d[h][0], d[h][1], sS[h][3][0], sS[h][3][1], 2, K[3], j, x < 2);
          }
        }
        if (i == 0) { bar_arrive(NB_PY, 256); softmax(0); }
#pragma unroll
        for (int g = 1; g < 4; g++) softmax(g);
        TL(23, i == 0 ? (t < 11 ? 5 : 6) : 7);
        if (i == 0) bar_sync(NB_PX + ((PS[0][1] | PS[0][2] | PS[0][3] | PS[1][1] | PS[1][2] | PS[1][3]) & __float_as_uint(z0)), 256);
        lds16f(SM_ZERO, z0, z1, z2, z3);
        auto pv = [&](int g, const uint32_t (&vp)[8]) {
#pragma unroll
          for (int x = 0; x < 8; x += 2) {
            const int h = x >> 2, j = x & 3;
            mma16816(O[h][g][j][0], O[h][g][j][1], O[h][g][j + 1][0], O[h][g][j + 1][1], vp[x], vp[x + 1], V[g][x], V[g][x + 1], PP[h][g], PS[h][g], z0, z1, z2, z3);
          }
        };
        pv(1, V[0]); pv(3, V[2]); pv(2, V[1]);
        if (i) {
          stage(1); stage(2); stage(3);
          mbar_arrive_warp(bar(B_SIG));
          receive(); score0(); softmax(0);
        }
        pv(0, Vp);
        if (i == 0) { bar_arrive(NB_PY, 256); stage(1); stage(2); stage(3); stage(0); }
        else { stage(0); copy_out<2>(SM_STG + w * 4096, sc->o, par * (S_ * D_) + (row0 + w * 32) * 128 + (8 + c) * PANEL, 128, lane); }
        mbar_arrive_warp(bar(B_SIG + 1));
        if (i) bar_arrive(NB_OGO, 256);
        TL(t, 6);
      } else if (i > 2 && i < 7) {
        float acc[2][96], hr[4], mn[16], m4[4];
        float2 cs[24];
        uint32_t so, sta, csa, sv[8][4];
        const int odd = (i - 3) & 1, blk = ((i - 3) >> 1) * 3;
        auto own_sums = [&](int g) {
#pragma unroll
          for (int x = 0; x < 4; x++) { const int j = (x >> 1) * 8 + g * 4 + (x & 1) * 2; lds16f(csa + odd * 1024 + j * 32, cs[j].x, cs[j].y, cs[j + 1].x, cs[j + 1].y); }
        };
        mainloop<1>(acc, sig, t, wg, sp, [&]() {
          const int lane = lane_now();
          so = SM_STG - 8192 + (w * 16 + (lane & 7)) * 128 + (((lane >> 3) ^ (lane & 7)) << 4);
          sta = stat(l * 2 + 1) + (w * 16 + (lane >> 2)) * 8;
          csa = SM_CS + 1536 + blk * 512 + (lane & 3) * 16;
          mbar_wait(bar(B_STAT + 1) + l * 16, 0);
          mbar_wait(bar(B_CS + 3) + 8 * (blk + odd), 0);
#pragma unroll
          for (int j = 0; j < 4; j++) hr[j] = 0.5f * lds4f(sta + (j >> 1) * 512 + (j & 1) * 64);
          own_sums(0);
          mbar_wait(bar(B_FREE), FREE_PH >> t);
        }, []() {});
        TL(t, 3);
        auto fetch = [&](int x, bool up) {
          const int r = x < 4 ? x & 1 : x < 12 ? (x - 4) >> 1 : 2 + (x & 1);
          if (up && x >= 6 && x < 12) mn[x] = m4[r];
          else if (x < 16) mn[x] = __uint_as_float(lds4(sta + 4 + (r >> 1) * 512 + (r & 1) * 64));
          if (x == 3) { m4[1] = mn[3]; m4[2] = __uint_as_float(lds4(sta + 4 + 512)); m4[3] = __uint_as_float(lds4(sta + 4 + 576)); }
          if (up && x >= 4 && x < 12) ldsm4((so ^ ((x & 1) * 64)) + 8192 + ((r >> 1) * 64 + (r & 1) * 8) * 128, sv[x - 4][0], sv[x - 4][1], sv[x - 4][2], sv[x - 4][3]);
          if (x == 2) own_sums(1);
          if (x == 3) {
#pragma unroll
            for (int j = 16; j < 24; j += 2) lds16f(csa + (SWAP ^ odd) * 256 + j * 32, cs[j].x, cs[j].y, cs[j + 1].x, cs[j + 1].y);
          }
        };
        auto silu = [&](float g, float h) { const float a = g * h; return fmaf(a, tanhf_(a), a); };
        auto own = [&](int mi) {
#pragma unroll
          for (int x = mi * 12; x < mi * 12 + 4; x++) {
            const int g = (x >> 1) & 1, half = x & 1;
            uint32_t v[4];
#pragma unroll
            for (int j = 0; j < 4; j++) {
              const int jg = g * 4 + j + SWAP * 8, ju = jg ^ 8;
              v[j] = pack_bf16(silu(fmaf(mn[x], cs[jg].x, acc[mi][jg * 4 + half * 2]), hr[mi * 2 + half]) * fmaf(mn[x], cs[ju].x, acc[mi][ju * 4 + half * 2]),
                               silu(fmaf(mn[x], cs[jg].y, acc[mi][jg * 4 + half * 2 + 1]), hr[mi * 2 + half]) * fmaf(mn[x], cs[ju].y, acc[mi][ju * 4 + half * 2 + 1]));
            }
            stsm4((so ^ (g * 64)) + half * 1024, v[0], v[1], v[2], v[3]);
            if ((x & 3) == 3) mbar_arrive_warp(bar(B_SIG + mi * 3));
            fetch(x + 2, true);
          }
        };
        auto shared = [&](bool up) {
#pragma unroll
          for (int x = 0; x < 8; x++) {
            const int mi = x >> 2, half = (x >> 1) & 1, g = x & 1;
            uint32_t v[4];
#pragma unroll
            for (int j = 0; j < 4; j++) {
              const int jx = 16 + g * 4 + j;
              const float x0 = fmaf(mn[x + 4], cs[jx].x, acc[mi][jx * 4 + half * 2]), x1 = fmaf(mn[x + 4], cs[jx].y, acc[mi][jx * 4 + half * 2 + 1]);
              v[j] = up ? pack_bf16(bf_lo(sv[x][j]) * x0, bf_hi(sv[x][j]) * x1) : pack_bf16(silu(x0, hr[x >> 1]), silu(x1, hr[x >> 1]));
            }
            stsm4((so ^ (g * 64)) + 8192 + (mi * 64 + half * 8) * 128, v[0], v[1], v[2], v[3]);
            if (up && (x & 3) == 3) mbar_arrive_warp(bar(B_SIG + 1 + mi));
            fetch(x + 6, up);
          }
        };
        fetch(0, false); fetch(1, false);
        own(0);
        if (odd) shared(true); else shared(false);
        TL(t, 5);
        mbar_wait(bar(B_FR0), odd);
        own(1);
        TL(t, 6);
      } else if (i == 7) {
        float acc[2][64];
        float2 cs[16];
        float hr[4];
        uint32_t so, sta;
        mainloop<1>(acc, sig, t, wg, sp, [&]() {
          const int lane = lane_now();
          so = SM_STG + (w * 16 + (lane & 7)) * 128 + (((lane >> 3) ^ (lane & 7)) << 4);
          sta = stat(l * 2 + 1) + (w * 16 + (lane >> 2)) * 8;
          mbar_wait(bar(B_STAT + 1) + l * 16, 0);
          mbar_wait(bar(B_CS + 8), 0);
#pragma unroll
          for (int j = 0; j < 16; j += 2) lds16f(SM_CS + 9 * 512 + (lane & 3) * 16 + j * 32, cs[j].x, cs[j].y, cs[j + 1].x, cs[j + 1].y);
#pragma unroll
          for (int j = 0; j < 4; j++) hr[j] = 0.5f * lds4f(sta + (j >> 1) * 512 + (j & 1) * 64);
        }, []() {});
        mbar_wait(bar(B_FREE), FREE_PH >> t);
        TL(t, 3);
        float mn[8];
#pragma unroll
        for (int x = 0; x < 2; x++) mn[x] = __uint_as_float(lds4(sta + 4 + (x >> 2) * 512 + ((x >> 1) & 1) * 64));
#pragma unroll
        for (int x = 0; x < 8; x++) {
          const int mi = x >> 2, half = (x >> 1) & 1, g = x & 1;
          uint32_t v[4];
#pragma unroll
          for (int j = 0; j < 4; j++) {
            const int jg = g * 4 + j + SWAP * 8, ju = jg ^ 8;
            const float2 cg = cs[jg], cu = cs[ju];
            const float g0 = fmaf(mn[x], cg.x, acc[mi][jg * 4 + half * 2]), g1 = fmaf(mn[x], cg.y, acc[mi][jg * 4 + half * 2 + 1]);
            const float u0 = fmaf(mn[x], cu.x, acc[mi][ju * 4 + half * 2]), u1 = fmaf(mn[x], cu.y, acc[mi][ju * 4 + half * 2 + 1]);
            const float a0 = g0 * hr[x >> 1], a1 = g1 * hr[x >> 1];
            v[j] = pack_bf16(fmaf(a0, tanhf_(a0), a0) * u0, fmaf(a1, tanhf_(a1), a1) * u1);
          }
          stsm4((so ^ (g * 64)) + (mi * 64 + half * 8) * 128, v[0], v[1], v[2], v[3]);
          if ((x & 3) == 3) mbar_arrive_warp(bar(B_SIG + mi));
          if (x + 2 < 8) mn[x + 2] = __uint_as_float(lds4(sta + 4 + ((x + 2) >> 2) * 512 + (((x + 2) >> 1) & 1) * 64));
        }
        TL(t, 6);
      } else if (i == 2 || i == 10) {
        float acc[2][64], rsc[4];
        {
          const int lane = lane_now();
          const uint32_t e = c_sched.task[t].res;
          const uint32_t ra = SB + (w * 16 + (lane & 7)) * 128 + (((lane >> 3) ^ (lane & 7)) << 4);
          float sd[4];
#pragma unroll
          for (int j = 0; j < 4; j++) {
            rsc[j] = i == 10 ? lds4f(stat(l * 2 + 1) + ((j >> 1) * 64 + w * 16 + (j & 1) * 8 + (lane >> 2)) * 8) : 1.f;
            sd[j] = rcpf(rsc[j]);
          }
          const uint32_t zero = lds4(SM_ZERO);
          mbar_wait(bar(B_RES), i == 10);
          uint32_t dep[16];
#pragma unroll
          for (int x = 0; x < 16; x++) {
            const int mi = x >> 3, half = (x >> 2) & 1, g = x & 3;
            uint32_t v[4];
            ldsm4(((e >> ((g >> 1) * 8)) & 31) * 8192 + ((ra ^ ((g & 1) * 64)) | (x >= RLA ? dep[x - RLA] : 0)) + (mi * 64 + half * 8) * 128, v[0], v[1], v[2], v[3]);
#pragma unroll
            for (int j = 0; j < 4; j++) {
              asm volatile("shl.b32 %0, %1, 16;" : "=f"(acc[mi][(g * 4 + j) * 4 + half * 2]) : "r"(v[j]));
              asm volatile("and.b32 %0, %1, 0xffff0000;" : "=f"(acc[mi][(g * 4 + j) * 4 + half * 2 + 1]) : "r"(v[j]));
              acc[mi][(g * 4 + j) * 4 + half * 2] *= sd[mi * 2 + half]; acc[mi][(g * 4 + j) * 4 + half * 2 + 1] *= sd[mi * 2 + half];
            }
            asm("and.b32 %0, %1, %2;" : "=r"(dep[x]) : "f"(acc[mi][(g * 4 + 3) * 4 + half * 2 + 1]), "r"(zero));
          }
          mbar_arrive_warp(bar(B_RF));
        }
        auto stage = [&](int mi, int hi) {
          const int lane = lane_now();
          const uint32_t sw = SB + ((c_sched.task[t].stg >> (8 * hi)) & 31) * 8192 + (mi * 64 + w * 16) * 128, so = sw + (lane & 7) * 128 + (((lane >> 3) ^ (lane & 7)) << 4);
#pragma unroll
          for (int half = 0; half < 2; half++)
#pragma unroll
            for (int g = 0; g < 2; g++) {
              uint32_t v[4];
#pragma unroll
              for (int j = 0; j < 4; j++) {
                acc[mi][(hi * 8 + g * 4 + j) * 4 + half * 2] *= rsc[mi * 2 + half]; acc[mi][(hi * 8 + g * 4 + j) * 4 + half * 2 + 1] *= rsc[mi * 2 + half];
                v[j] = pack_bf16(acc[mi][(hi * 8 + g * 4 + j) * 4 + half * 2], acc[mi][(hi * 8 + g * 4 + j) * 4 + half * 2 + 1]);
              }
              stsm4((so ^ (g * 64)) + half * 1024, v[0], v[1], v[2], v[3]);
            }
          if (mi && !hi) mbar_arrive_warp(bar(B_SIG));
          if (hi == 0 || t == 21) {
            const int pitch = t == 21 ? D_ * 4 : 128;
            copy_out<4>(sw, t == 21 ? out : sc->y, (row0 + mi * 64 + w * 16) * pitch + (t == 21 ? par * (D_ * 2) + (hi * 8 + c) * 128 : par * (S_ * D_) + c * PANEL), pitch, lane);
          }
        };
        mainloop<2>(acc, sig, t, wg, sp, []() {}, [&]() { stage(0, 0); stage(0, 1); });
        TL(t, 3);
        stage(1, 0); mbar_arrive_warp(bar(B_SIG + 1));
        TL(t, 6);
        stage(1, 1); mbar_arrive_warp(bar(B_SIG + 2));
        if (t < 21) {
          const int lane = lane_now(), q = lane & 3;
          const uint32_t zero = lds4(SM_ZERO);
          float s[4], s2[4];
#pragma unroll
          for (int x = 0; x < 4; x++) {
            float a0 = x ? __uint_as_float(__float_as_uint(s[x - 1]) & zero) : 0.f, b0 = x ? __uint_as_float(__float_as_uint(s2[x - 1]) & zero) : 0.f;
#pragma unroll
            for (int j = 0; j < 32; j++) { const float d = acc[x >> 1][(j >> 1) * 4 + (x & 1) * 2 + (j & 1)]; a0 += d; b0 = fmaf(d, d, b0); }
            s[x] = a0; s2[x] = b0;
          }
#pragma unroll
          for (int x = 0; x < 2; x++) {
            s[x] = (q & 2 ? s[x + 2] : s[x]) + __shfl_xor_sync(0xffffffffu, q & 2 ? s[x] : s[x + 2], 2);
            s2[x] = (q & 2 ? s2[x + 2] : s2[x]) + __shfl_xor_sync(0xffffffffu, q & 2 ? s2[x] : s2[x + 2], 2);
          }
          const float r = (q & 1 ? s[1] : s[0]) + __shfl_xor_sync(0xffffffffu, q & 1 ? s[0] : s[1], 1);
          const float r2 = (q & 1 ? s2[1] : s2[0]) + __shfl_xor_sync(0xffffffffu, q & 1 ? s2[0] : s2[1], 1);
          asm volatile("st.global.v2.f32 [%0], {%1, %2};" ::"l"(&sc->stat[i == 10 ? 1 : l * 2][m][c][(q >> 1) * 64 + w * 16 + (q & 1) * 8 + (lane >> 2)]), "f"(r), "f"(r2) : "memory");
          mbar_arrive_warp(bar(B_SIG + 3));
        }
      }
    }
  }
}

typedef CUresult (*PFN_encodeTiled)(CUtensorMap*, CUtensorMapDataType, cuuint32_t, void*, const cuuint64_t*, const cuuint64_t*, const cuuint32_t*,
                                    const cuuint32_t*, CUtensorMapInterleave, CUtensorMapSwizzle, CUtensorMapL2promotion, CUtensorMapFloatOOBfill);

void make_map(PFN_encodeTiled enc, CUtensorMap* mp, const void* ptr, int rank, const cuuint64_t* gd, const cuuint64_t* gs, const cuuint32_t* bd) {
  const cuuint32_t es[4] = {1, 1, 1, 1};
  enc(mp, CU_TENSOR_MAP_DATA_TYPE_BFLOAT16, rank, const_cast<void*>(ptr), gd, gs, bd, es, CU_TENSOR_MAP_INTERLEAVE_NONE, CU_TENSOR_MAP_SWIZZLE_128B,
      CU_TENSOR_MAP_L2_PROMOTION_L2_128B, CU_TENSOR_MAP_FLOAT_OOB_FILL_NONE);
}
void make_map_act(PFN_encodeTiled enc, CUtensorMap* mp, const void* ptr, uint64_t cols, uint64_t s1, uint64_t s2, uint64_t s3, uint32_t rows) {
  const cuuint64_t gd[4] = {64, S_ / 2, cols / 64, 2}, gs[3] = {s1, s2, s3};
  const cuuint32_t bd[4] = {64, rows, 1, 1};
  make_map(enc, mp, ptr, 4, gd, gs, bd);
}
void make_map_w(PFN_encodeTiled enc, CUtensorMap* mp, const void* ptr, uint64_t rows, uint64_t cols, uint32_t np, uint64_t sp, uint64_t tiles, uint32_t nt) {
  const cuuint64_t gd[4] = {512, rows, np, tiles}, gs[3] = {cols * 2, sp, 1024};
  const cuuint32_t bd[4] = {64, 64, np, nt};
  make_map(enc, mp, ptr, 4, gd, gs, bd);
}

}

extern "C" void kernel_launch(void* const* d_in, const int* in_sizes, int n_in, void* d_out, int out_size) {
  (void)in_sizes; (void)n_in; (void)out_size;
  static PFN_encodeTiled enc = nullptr;
  static void *p_sc, *p_ops, *p_w;
  static int by_sm = 0;
  void (*const kernels[4])(Scratch*, const Ops*, const bf16*, bf16*, Params) = {fused_kernel<0, 0>, fused_kernel<1, 0>, fused_kernel<0, 1>, fused_kernel<1, 1>};
  if (!enc) {
    void* fn = nullptr; cudaDriverEntryPointQueryResult qr;
    cudaGetDriverEntryPoint("cuTensorMapEncodeTiled", &fn, cudaEnableDefault, &qr);
    enc = (PFN_encodeTiled)fn;
    cudaGetSymbolAddress(&p_sc, g_sc); cudaGetSymbolAddress(&p_ops, g_ops); cudaGetSymbolAddress(&p_w, g_w13);
    for (int i = 0; i < 4; i++) cudaFuncSetAttribute(kernels[i], cudaFuncAttributeMaxDynamicSharedMemorySize, SM_TOTAL);
    int dev = 0, sms = 0;
    cudaGetDevice(&dev);
    cudaDeviceGetAttribute(&sms, cudaDevAttrMultiProcessorCount, dev);
    by_sm = sms == NCTA + NHELP;
    for (int i = 1; i < 4 && by_sm; i++) {
      cudaLaunchConfig_t cfg = {};
      cudaLaunchAttribute at;
      at.id = cudaLaunchAttributeClusterDimension; at.val.clusterDim.x = 1 << i; at.val.clusterDim.y = at.val.clusterDim.z = 1;
      cfg.gridDim = dim3(NCTA); cfg.blockDim = dim3(384); cfg.dynamicSmemBytes = SM_TOTAL; cfg.attrs = &at; cfg.numAttrs = 1;
      int n = 0;
      if (cudaOccupancyMaxActiveClusters(&n, kernels[0], &cfg) != cudaSuccess) { (void)cudaGetLastError(); n = 0; }
      by_sm = n == (i == 1 ? 66 : i == 2 ? 30 : 15);
    }
  }
  Params P;
  Scratch* const sc = (Scratch*)p_sc;
  make_map_act(enc, &P.tm[M_X0], d_in[0], D_, D_ * 4, 128, D_ * 2, 128);
  make_map_act(enc, &P.tm[M_O], sc->o, D_, 128, PANEL, S_ * D_, 128);
  make_map_act(enc, &P.tm[M_Y], sc->y, D_, 128, PANEL, S_ * D_, 128);
  make_map_act(enc, &P.tm[M_H], sc->h, F_, 128, PANEL, S_ * F_, 128);
  make_map_act(enc, &P.tm[M_OL], sc->o, D_, 128, PANEL, S_ * D_, PROWS);
  make_map_act(enc, &P.tm[M_YL], sc->y, D_, 128, PANEL, S_ * D_, PROWS);
  make_map_act(enc, &P.tm[M_HL], sc->h, F_, 128, PANEL, S_ * F_, PROWS);
  make_map_act(enc, &P.tm[M_O24], sc->o, D_, 128, PANEL, S_ * D_, 24);
  make_map_w(enc, &P.tm[M_WQKV], d_in[1], D_, 3 * D_, 3, D_ * 2, 2, 1);
  make_map_w(enc, &P.tm[M_WO], d_in[2], D_, D_, 2, 1024, 1, 1);
  make_map_w(enc, &P.tm[M_W2], d_in[6], F_, D_, 2, 1024, 1, 1);
  const char *w1 = (const char*)d_in[4], *w3 = (const char*)d_in[5];
  if (w1 == w3 || (uint64_t)(w1 < w3 ? w3 - w1 : w1 - w3) >> 39) {
    cudaMemcpyAsync(p_w, w1, (size_t)D_ * F_ * 2, cudaMemcpyDeviceToDevice);
    cudaMemcpyAsync((bf16*)p_w + D_ * F_, w3, (size_t)D_ * F_ * 2, cudaMemcpyDeviceToDevice);
    w1 = (const char*)p_w; w3 = w1 + (size_t)D_ * F_ * 2;
  }
  const bool swap = w3 < w1;
  make_map_w(enc, &P.tm[M_W13], swap ? w3 : w1, D_, F_, 2, swap ? w1 - w3 : w3 - w1, 7, 1);
  make_map_w(enc, &P.tm[M_W1], w1 + 1024, D_, F_, 1, 1024, 6, 1);
  make_map_w(enc, &P.tm[M_W3], w3 - 1024, D_, F_, 1, 1024, 7, 1);
  kernels[by_sm * 2 + swap]<<<NCTA + NHELP, 384, SM_TOTAL>>>(sc, (const Ops*)p_ops, (const bf16*)d_in[0], (bf16*)d_out, P);
}
```
